```python
import torch

def _softmax(x, axis=-1):
    return torch.softmax(x, dim=axis)
def _gelu(x):
    return torch.nn.functional.gelu(x, approximate="tanh")
def _silu(x):
    return torch.nn.functional.silu(x)
def _sigmoid(x):
    return torch.sigmoid(x)
def _layernorm(x, axis=-1, eps=1e-5):
    m = x.mean(dim=axis, keepdim=True)
    v = x.var(dim=axis, keepdim=True, unbiased=False)
    return (x - m) / torch.sqrt(v + eps)
def _scatter_add(tgt, idx, src, axis=0):
    return tgt.clone().index_add_(axis, idx, src)
def _segment_sum(src, seg, n):
    out = torch.zeros((n,) + src.shape[1:], dtype=src.dtype)
    return out.index_add_(0, seg, src)
def _pad(x, pw):
    flat = tuple(v for pair in reversed(pw) for v in pair)
    return torch.nn.functional.pad(x, flat)

kernel_name = 'gated_mix__ssm_conv_s5__dense_activation_squared_relu__prompt'

def setup_inputs():

    _w = (lambda a: (lambda t: t.to(torch.bfloat16) if t.is_floating_point() else t)(torch.as_tensor(a)))
    def _A_setup():
        B, S, D = 1, 2048, 1024
        P = D
        Lambda_re = -0.5 * (lambda _x: torch.exp(torch.as_tensor(_x)))((lambda *s: torch.randn(*s, dtype=torch.bfloat16) * 0.4)(P))
        Lambda_im = (lambda *s: torch.randn(*s, dtype=torch.bfloat16) * 0.8)(P) * 1.0
        B_re = (lambda *s: torch.randn(*s, dtype=torch.bfloat16) * 0.8)(P, D) * (D ** -0.5)
        B_im = (lambda *s: torch.randn(*s, dtype=torch.bfloat16) * 0.8)(P, D) * (D ** -0.5)
        C_re = (lambda *s: torch.randn(*s, dtype=torch.bfloat16) * 0.8)(D, P) * (P ** -0.5)
        C_im = (lambda *s: torch.randn(*s, dtype=torch.bfloat16) * 0.8)(D, P) * (P ** -0.5)
        log_dt = (lambda *s: torch.randn(*s, dtype=torch.bfloat16) * 0.4)(P) * 0.3 - 2.0
        Dskip = (lambda *s: torch.randn(*s, dtype=torch.bfloat16) * 0.1)(D)
        return {
            "x": _w((lambda *s: torch.randn(*s, dtype=torch.bfloat16) * 0.05)(B, S, D)),
            "Lambda_re": _w(Lambda_re),
            "Lambda_im": _w(Lambda_im),
            "B_re": _w(B_re),
            "B_im": _w(B_im),
            "C_re": _w(C_re),
            "C_im": _w(C_im),
            "log_dt": _w(log_dt),
            "Dskip": _w(Dskip),
        }
    _A_in = _A_setup()

    def _B_setup():
        B, S, D, F = 1, 2048, 1024, 3584
        return {
            "x": _w((lambda *s: torch.randn(*s, dtype=torch.bfloat16) * 0.05)(B, S, D)),
            "w1": _w((lambda *s: torch.randn(*s, dtype=torch.bfloat16) * 0.05)(D, F)),
            "b1": _w((lambda *s: torch.randn(*s, dtype=torch.bfloat16) * 0.05)(F)),
            "w2": _w((lambda *s: torch.randn(*s, dtype=torch.bfloat16) * 0.05)(F, D)),
            "b2": _w((lambda *s: torch.randn(*s, dtype=torch.bfloat16) * 0.05)(D)),
        }
    _B_in = _B_setup()

    return {
        "A_x": _A_in["x"],
        "A_Lambda_re": _A_in["Lambda_re"],
        "A_Lambda_im": _A_in["Lambda_im"],
        "A_B_re": _A_in["B_re"],
        "A_B_im": _A_in["B_im"],
        "A_C_re": _A_in["C_re"],
        "A_C_im": _A_in["C_im"],
        "A_log_dt": _A_in["log_dt"],
        "A_Dskip": _A_in["Dskip"],
        "B_x": _B_in["x"],
        "B_w1": _B_in["w1"],
        "B_b1": _B_in["b1"],
        "B_w2": _B_in["w2"],
        "B_b2": _B_in["b2"],
        "gate_w": _w((lambda *s: torch.randn(*s, dtype=torch.bfloat16) * 0.05)(1024) * 16.0),
    }

def reference(A_x, A_Lambda_re, A_Lambda_im, A_B_re, A_B_im, A_C_re, A_C_im, A_log_dt, A_Dskip, B_x, B_w1, B_b1, B_w2, B_b2, gate_w):
    def _A_ref(x, Lambda_re, Lambda_im, B_re, B_im, C_re, C_im, log_dt, Dskip):
        Bsz, L, H = x.shape
        Lam = Lambda_re + 1j * Lambda_im
        Bmat = B_re + 1j * B_im
        Cmat = C_re + 1j * C_im
        dt = torch.exp(log_dt)
        Lam_bar = torch.exp(dt * Lam)
        B_bar = ((Lam_bar - 1.0) / Lam)[:, None] * Bmat
        Bu = torch.einsum("bld,pd->blp", x + 0j, B_bar)
        h = torch.zeros_like(Bu[:, 0, :])
        hs = []
        for t in range(L):
            h = Lam_bar[None, :] * h + Bu[:, t, :]
            hs.append(h)
        hseq = torch.stack(hs, 1)
        y = 2.0 * torch.einsum("blp,dp->bld", hseq, Cmat).real + x * Dskip[None, None, :]
        return y

    def _B_ref(x, w1, b1, w2, b2):
        h = torch.einsum("bsd,df->bsf", x, w1) + b1
        zero = torch.zeros_like(h)
        r = torch.where(h > zero, h, zero)
        h = r * r
        out = torch.einsum("bsf,fd->bsd", h, w2) + b2
        return out

    x = A_x
    g = _sigmoid((x * gate_w).sum(-1, keepdims=True))
    a = _A_ref(x, A_Lambda_re, A_Lambda_im, A_B_re, A_B_im, A_C_re, A_C_im, A_log_dt, A_Dskip)
    b = _B_ref(x, B_w1, B_b1, B_w2, B_b2)
    return g * a + (1 - g) * b
```

```cpp
#include <cuda_runtime.h>
#include <cuda_bf16.h>
#include <cuda.h>
#include <stdint.h>

#define MULTICAST 1

namespace {

constexpr int kL = 2048, kD = 1024, kP = 1024, kF = 3584;
constexpr int kStages = 4;
constexpr int kStageBytes = 49152;
constexpr int kABytes = 16384;
constexpr int kAux = kStages * kStageBytes;
constexpr int kGateOff = kAux;
constexpr int kGateBytesWG = 4 * 68 * 4;
constexpr int kBiasOff = kGateOff + 2 * kGateBytesWG;
constexpr int kBiasBytesWG = 56 * 16;
constexpr int kBarOff = kBiasOff + 2 * kBiasBytesWG;
constexpr int kSmemBytes = kBarOff + 128;
constexpr uint32_t kSmemOrg = 1024;
constexpr unsigned kSpinLimit = 1u << 24;

__device__ __align__(1024) __nv_bfloat16 g_Hs[2048 * 2048];
__device__ __align__(1024) __nv_bfloat16 g_Hf[2048 * 3584];
__device__ __align__(1024) __nv_bfloat16 g_Bcopy[2 * 1024 * 1024];
__device__ uint4 g_agg[8 * 1024];
__device__ uint2 g_gate[2048];
__device__ unsigned g_cnt[72 * 32];
__device__ unsigned g_epoch;
__device__ unsigned g_done;

#define TRAP() break
#define PIN_F(x) asm volatile("" : "+f"(x))
#define PIN_R(x) asm volatile("" : "+r"(x))
__device__ __forceinline__ uint32_t smem_u32(const void* p) { return (uint32_t)__cvta_generic_to_shared(p); }
__device__ __forceinline__ void mbar_init(uint32_t bar, uint32_t count) {
    asm volatile("mbarrier.init.shared::cta.b64 [%0], %1;" ::"r"(bar), "r"(count) : "memory");
}
__device__ __forceinline__ void mbar_expect_tx(uint32_t bar, uint32_t bytes) {
    asm volatile("mbarrier.arrive.expect_tx.shared::cta.b64 _, [%0], %1;" ::"r"(bar), "r"(bytes) : "memory");
}
__device__ __forceinline__ bool mbar_try(uint32_t bar, uint32_t parity) {
    uint32_t ok;
    asm volatile(
        "{\n.reg .pred p;\nmbarrier.try_wait.parity.shared::cta.b64 p, [%1], %2;\nselp.u32 %0, 1, 0, p;\n}\n"
        : "=r"(ok) : "r"(bar), "r"(parity) : "memory");
    return ok != 0;
}
__device__ __forceinline__ bool mbar_try_cluster(uint32_t bar, uint32_t parity) {
    uint32_t ok;
    asm volatile(
        "{\n.reg .pred p;\nmbarrier.try_wait.parity.acquire.cluster.shared::cta.b64 p, [%1], %2;\nselp.u32 %0, 1, 0, p;\n}\n"
        : "=r"(ok) : "r"(bar), "r"(parity) : "memory");
    return ok != 0;
}
__device__ __forceinline__ void mbar_wait(uint32_t bar, uint32_t parity) {
    if (mbar_try(bar, parity)) return;
    unsigned n = 0;
    while (!mbar_try(bar, parity)) {
        if (++n > kSpinLimit) TRAP();
    }
}
__device__ __forceinline__ void mbar_wait_cluster(uint32_t bar, uint32_t parity) {
    unsigned n = 0;
    while (!mbar_try_cluster(bar, parity)) {
        if (++n > kSpinLimit) TRAP();
    }
}
__device__ __forceinline__ void mbar_arrive_local(uint32_t bar) {
    asm volatile("mbarrier.arrive.shared::cta.b64 _, [%0];" ::"r"(bar) : "memory");
}
__device__ __forceinline__ void mbar_arrive_cluster(uint32_t cluster_addr) {
    asm volatile("mbarrier.arrive.shared::cluster.b64 _, [%0];" ::"r"(cluster_addr) : "memory");
}
__device__ __forceinline__ uint32_t mapa(uint32_t addr, uint32_t rank) {
    uint32_t r;
    asm("mapa.shared::cluster.u32 %0, %1, %2;" : "=r"(r) : "r"(addr), "r"(rank));
    return r;
}
__device__ __forceinline__ void cluster_sync_all() {
    asm volatile("barrier.cluster.arrive.release.aligned;\nbarrier.cluster.wait.acquire.aligned;" ::: "memory");
}
template <int ID, int N>
__device__ __forceinline__ void bar_sync() { asm volatile("bar.sync %0, %1;" ::"n"(ID), "n"(N) : "memory"); }
template <int ID, int N>
__device__ __forceinline__ void bar_arrive() { asm volatile("bar.arrive %0, %1;" ::"n"(ID), "n"(N) : "memory"); }

__device__ __forceinline__ void tma2(uint32_t dst, const CUtensorMap* m, uint32_t bar, int c0, int c1) {
    asm volatile("cp.async.bulk.tensor.2d.shared::cluster.global.mbarrier::complete_tx::bytes [%0], [%1, {%3, %4}], [%2];"
                 ::"r"(dst), "l"(m), "r"(bar), "r"(c0), "r"(c1) : "memory");
}
__device__ __forceinline__ void tma3(uint32_t dst, const CUtensorMap* m, uint32_t bar, int c0, int c1, int c2) {
    asm volatile("cp.async.bulk.tensor.3d.shared::cluster.global.mbarrier::complete_tx::bytes [%0], [%1, {%3, %4, %5}], [%2];"
                 ::"r"(dst), "l"(m), "r"(bar), "r"(c0), "r"(c1), "r"(c2) : "memory");
}
__device__ __forceinline__ void tma4(uint32_t dst, const CUtensorMap* m, uint32_t bar, int c0, int c1, int c2, int c3) {
    asm volatile("cp.async.bulk.tensor.4d.shared::cluster.global.mbarrier::complete_tx::bytes [%0], [%1, {%3, %4, %5, %6}], [%2];"
                 ::"r"(dst), "l"(m), "r"(bar), "r"(c0), "r"(c1), "r"(c2), "r"(c3) : "memory");
}
__device__ __forceinline__ void tma5(uint32_t dst, const CUtensorMap* m, uint32_t bar, int c0, int c1, int c2, int c3, int c4) {
    asm volatile("cp.async.bulk.tensor.5d.shared::cluster.global.mbarrier::complete_tx::bytes [%0], [%1, {%3, %4, %5, %6, %7}], [%2];"
                 ::"r"(dst), "l"(m), "r"(bar), "r"(c0), "r"(c1), "r"(c2), "r"(c3), "r"(c4) : "memory");
}
__device__ __forceinline__ void tma3_mc(uint32_t dst, const CUtensorMap* m, uint32_t bar, int c0, int c1, int c2) {
    asm volatile("cp.async.bulk.tensor.3d.shared::cluster.global.mbarrier::complete_tx::bytes.multicast::cluster [%0], [%1, {%3, %4, %5}], [%2], %6;"
                 ::"r"(dst), "l"(m), "r"(bar), "r"(c0), "r"(c1), "r"(c2), "h"((uint16_t)3) : "memory");
}
__device__ __forceinline__ void tma5_mc(uint32_t dst, const CUtensorMap* m, uint32_t bar, int c0, int c1, int c2, int c3, int c4) {
    asm volatile("cp.async.bulk.tensor.5d.shared::cluster.global.mbarrier::complete_tx::bytes.multicast::cluster [%0], [%1, {%3, %4, %5, %6, %7}], [%2], %8;"
                 ::"r"(dst), "l"(m), "r"(bar), "r"(c0), "r"(c1), "r"(c2), "r"(c3), "r"(c4), "h"((uint16_t)3) : "memory");
}
__device__ __forceinline__ void prefetch_map(const CUtensorMap* m) {
    asm volatile("prefetch.tensormap [%0];" ::"l"(m) : "memory");
}

__device__ __forceinline__ void wgmma_fence() { asm volatile("wgmma.fence.sync.aligned;" ::: "memory"); }
__device__ __forceinline__ void wgmma_commit() { asm volatile("wgmma.commit_group.sync.aligned;" ::: "memory"); }
template <int N>
__device__ __forceinline__ void wgmma_wait() { asm volatile("wgmma.wait_group.sync.aligned %0;" ::"n"(N) : "memory"); }

__device__ __forceinline__ uint32_t pack_bf16(float lo, float hi) {
    uint32_t r;
    asm("cvt.rn.bf16x2.f32 %0, %1, %2;" : "=r"(r) : "f"(hi), "f"(lo));
    return r;
}
__device__ __forceinline__ uint32_t pack_bf16_v(float lo, float hi) {
    uint32_t r;
    asm volatile("cvt.rn.bf16x2.f32 %0, %1, %2;" : "=r"(r) : "f"(hi), "f"(lo));
    return r;
}
__device__ __forceinline__ float bf_lo(uint32_t v) { return __uint_as_float(v << 16); }
__device__ __forceinline__ float bf_hi(uint32_t v) { return __uint_as_float(v & 0xffff0000u); }
__device__ __forceinline__ float bf16_round(float v) { return __bfloat162float(__float2bfloat16_rn(v)); }
__device__ __forceinline__ uint32_t bf2_mul(uint32_t a, uint32_t b) {
    uint32_t r;
    asm("mul.rn.bf16x2 %0, %1, %2;" : "=r"(r) : "r"(a), "r"(b));
    return r;
}
__device__ __forceinline__ uint32_t bf2_add_relu(uint32_t a, uint32_t b) {
    uint32_t r;
    asm("fma.rn.relu.bf16x2 %0, %1, %2, %3;" : "=r"(r) : "r"(a), "r"(0x3f803f80u), "r"(b));
    return r;
}
__device__ __forceinline__ uint4 ldg128(const void* p) {
    uint4 v;
    asm volatile("ld.global.nc.v4.u32 {%0, %1, %2, %3}, [%4];" : "=r"(v.x), "=r"(v.y), "=r"(v.z), "=r"(v.w) : "l"(p));
    return v;
}
__device__ __forceinline__ uint32_t ldg32(const void* p) {
    uint32_t v;
    asm volatile("ld.global.nc.u32 %0, [%1];" : "=r"(v) : "l"(p));
    return v;
}
__device__ __forceinline__ float ldg_bf16(const __nv_bfloat16* p) {
    uint16_t v;
    asm volatile("ld.global.nc.u16 %0, [%1];" : "=h"(v) : "l"(p));
    return __uint_as_float((uint32_t)v << 16);
}
__device__ __forceinline__ uint4 ld_relaxed128(const void* p) {
    uint4 v;
    asm volatile("ld.relaxed.gpu.global.v4.u32 {%0, %1, %2, %3}, [%4];" : "=r"(v.x), "=r"(v.y), "=r"(v.z), "=r"(v.w) : "l"(p) : "memory");
    return v;
}
__device__ __forceinline__ uint2 ld_relaxed64(const void* p) {
    unsigned long long v;
    asm volatile("ld.relaxed.gpu.global.u64 %0, [%1];" : "=l"(v) : "l"(p) : "memory");
    return make_uint2((uint32_t)v, (uint32_t)(v >> 32));
}
__device__ __forceinline__ void st_relaxed64(void* p, uint32_t lo, uint32_t hi) {
    unsigned long long v = ((unsigned long long)hi << 32) | lo;
    asm volatile("st.relaxed.gpu.global.u64 [%0], %1;" ::"l"(p), "l"(v) : "memory");
}
__device__ __forceinline__ void st_relaxed2x64(void* p, uint32_t a, uint32_t b, uint32_t c, uint32_t d) {
    unsigned long long v0 = ((unsigned long long)b << 32) | a, v1 = ((unsigned long long)d << 32) | c;
    asm volatile("st.relaxed.gpu.global.v2.u64 [%0], {%1, %2};" ::"l"(p), "l"(v0), "l"(v1) : "memory");
}
__device__ __forceinline__ uint4 ld_relaxed2x64(const void* p) {
    unsigned long long v0, v1;
    asm volatile("ld.relaxed.gpu.global.v2.u64 {%0, %1}, [%2];" : "=l"(v0), "=l"(v1) : "l"(p) : "memory");
    return make_uint4((uint32_t)v0, (uint32_t)(v0 >> 32), (uint32_t)v1, (uint32_t)(v1 >> 32));
}
__device__ __forceinline__ void stg128(void* p, uint32_t a, uint32_t b, uint32_t c, uint32_t d) {
    asm volatile("st.global.v4.u32 [%0], {%1, %2, %3, %4};" ::"l"(p), "r"(a), "r"(b), "r"(c), "r"(d) : "memory");
}
__device__ __forceinline__ void stg64f(void* p, float a, float b) {
    asm volatile("st.global.v2.f32 [%0], {%1, %2};" ::"l"(p), "f"(a), "f"(b) : "memory");
}
__device__ __forceinline__ uint4 lds128(uint32_t a) {
    uint4 v;
    asm volatile("ld.shared.v4.u32 {%0, %1, %2, %3}, [%4];" : "=r"(v.x), "=r"(v.y), "=r"(v.z), "=r"(v.w) : "r"(a) : "memory");
    return v;
}
__device__ __forceinline__ float lds32f(uint32_t a) {
    float v;
    asm volatile("ld.shared.f32 %0, [%1];" : "=f"(v) : "r"(a) : "memory");
    return v;
}
__device__ __forceinline__ void sts128(uint32_t a, uint32_t x, uint32_t y, uint32_t z, uint32_t w) {
    asm volatile("st.shared.v4.u32 [%0], {%1, %2, %3, %4};" ::"r"(a), "r"(x), "r"(y), "r"(z), "r"(w) : "memory");
}
__device__ __forceinline__ void sts32(uint32_t a, uint32_t x) {
    asm volatile("st.shared.u32 [%0], %1;" ::"r"(a), "r"(x) : "memory");
}
__device__ __forceinline__ void st_async128(uint32_t dst, float a, float b, float c, float d, uint32_t bar) {
    asm volatile("st.async.shared::cluster.mbarrier::complete_tx::bytes.v4.f32 [%0], {%1, %2, %3, %4}, [%5];"
                 ::"r"(dst), "f"(a), "f"(b), "f"(c), "f"(d), "r"(bar) : "memory");
}
__device__ __forceinline__ void wait_counter(const unsigned* p, unsigned target) {
    unsigned n = 0, v;
    while (true) {
        asm volatile("ld.acquire.gpu.global.u32 %0, [%1];" : "=r"(v) : "l"(p) : "memory");
        if ((int)(v - target) >= 0) break;
        if (++n > kSpinLimit) TRAP();
        __nanosleep(64);
    }
    asm volatile("fence.proxy.async.global;" ::: "memory");
}
#define STAMP(cond, slot) do { } while (0)

template <int TA, int TB>
__device__ __forceinline__ void wgmma_n256(float (&d)[128], uint64_t da, uint64_t db) {
    asm volatile(
        "{\n.reg .pred p;\nsetp.ne.b32 p, 1, 0;\n"
        "wgmma.mma_async.sync.aligned.m64n256k16.f32.bf16.bf16 "
        "{%0, %1, %2, %3, %4, %5, %6, %7, %8, %9, %10, %11, %12, %13, %14, %15, "
        "%16, %17, %18, %19, %20, %21, %22, %23, %24, %25, %26, %27, %28, %29, %30, %31, "
        "%32, %33, %34, %35, %36, %37, %38, %39, %40, %41, %42, %43, %44, %45, %46, %47, "
        "%48, %49, %50, %51, %52, %53, %54, %55, %56, %57, %58, %59, %60, %61, %62, %63, "
        "%64, %65, %66, %67, %68, %69, %70, %71, %72, %73, %74, %75, %76, %77, %78, %79, "
        "%80, %81, %82, %83, %84, %85, %86, %87, %88, %89, %90, %91, %92, %93, %94, %95, "
        "%96, %97, %98, %99, %100, %101, %102, %103, %104, %105, %106, %107, %108, %109, %110, %111, "
        "%112, %113, %114, %115, %116, %117, %118, %119, %120, %121, %122, %123, %124, %125, %126, %127}, "
        "%128, %129, p, 1, 1, %130, %131;\n}\n"
        : "+f"(d[0]), "+f"(d[1]), "+f"(d[2]), "+f"(d[3]), "+f"(d[4]), "+f"(d[5]), "+f"(d[6]), "+f"(d[7]),
          "+f"(d[8]), "+f"(d[9]), "+f"(d[10]), "+f"(d[11]), "+f"(d[12]), "+f"(d[13]), "+f"(d[14]), "+f"(d[15]),
          "+f"(d[16]), "+f"(d[17]), "+f"(d[18]), "+f"(d[19]), "+f"(d[20]), "+f"(d[21]), "+f"(d[22]), "+f"(d[23]),
          "+f"(d[24]), "+f"(d[25]), "+f"(d[26]), "+f"(d[27]), "+f"(d[28]), "+f"(d[29]), "+f"(d[30]), "+f"(d[31]),
          "+f"(d[32]), "+f"(d[33]), "+f"(d[34]), "+f"(d[35]), "+f"(d[36]), "+f"(d[37]), "+f"(d[38]), "+f"(d[39]),
          "+f"(d[40]), "+f"(d[41]), "+f"(d[42]), "+f"(d[43]), "+f"(d[44]), "+f"(d[45]), "+f"(d[46]), "+f"(d[47]),
          "+f"(d[48]), "+f"(d[49]), "+f"(d[50]), "+f"(d[51]), "+f"(d[52]), "+f"(d[53]), "+f"(d[54]), "+f"(d[55]),
          "+f"(d[56]), "+f"(d[57]), "+f"(d[58]), "+f"(d[59]), "+f"(d[60]), "+f"(d[61]), "+f"(d[62]), "+f"(d[63]),
          "+f"(d[64]), "+f"(d[65]), "+f"(d[66]), "+f"(d[67]), "+f"(d[68]), "+f"(d[69]), "+f"(d[70]), "+f"(d[71]),
          "+f"(d[72]), "+f"(d[73]), "+f"(d[74]), "+f"(d[75]), "+f"(d[76]), "+f"(d[77]), "+f"(d[78]), "+f"(d[79]),
          "+f"(d[80]), "+f"(d[81]), "+f"(d[82]), "+f"(d[83]), "+f"(d[84]), "+f"(d[85]), "+f"(d[86]), "+f"(d[87]),
          "+f"(d[88]), "+f"(d[89]), "+f"(d[90]), "+f"(d[91]), "+f"(d[92]), "+f"(d[93]), "+f"(d[94]), "+f"(d[95]),
          "+f"(d[96]), "+f"(d[97]), "+f"(d[98]), "+f"(d[99]), "+f"(d[100]), "+f"(d[101]), "+f"(d[102]), "+f"(d[103]),
          "+f"(d[104]), "+f"(d[105]), "+f"(d[106]), "+f"(d[107]), "+f"(d[108]), "+f"(d[109]), "+f"(d[110]), "+f"(d[111]),
          "+f"(d[112]), "+f"(d[113]), "+f"(d[114]), "+f"(d[115]), "+f"(d[116]), "+f"(d[117]), "+f"(d[118]), "+f"(d[119]),
          "+f"(d[120]), "+f"(d[121]), "+f"(d[122]), "+f"(d[123]), "+f"(d[124]), "+f"(d[125]), "+f"(d[126]), "+f"(d[127])
        : "l"(da), "l"(db), "n"(TA), "n"(TB));
}
template <int TA, int TB>
__device__ __forceinline__ void wgmma_n256_first(float (&d)[128], uint64_t da, uint64_t db) {
    asm volatile(
        "{\n.reg .pred p;\nsetp.ne.b32 p, 0, 0;\n"
        "wgmma.mma_async.sync.aligned.m64n256k16.f32.bf16.bf16 "
        "{%0, %1, %2, %3, %4, %5, %6, %7, %8, %9, %10, %11, %12, %13, %14, %15, "
        "%16, %17, %18, %19, %20, %21, %22, %23, %24, %25, %26, %27, %28, %29, %30, %31, "
        "%32, %33, %34, %35, %36, %37, %38, %39, %40, %41, %42, %43, %44, %45, %46, %47, "
        "%48, %49, %50, %51, %52, %53, %54, %55, %56, %57, %58, %59, %60, %61, %62, %63, "
        "%64, %65, %66, %67, %68, %69, %70, %71, %72, %73, %74, %75, %76, %77, %78, %79, "
        "%80, %81, %82, %83, %84, %85, %86, %87, %88, %89, %90, %91, %92, %93, %94, %95, "
        "%96, %97, %98, %99, %100, %101, %102, %103, %104, %105, %106, %107, %108, %109, %110, %111, "
        "%112, %113, %114, %115, %116, %117, %118, %119, %120, %121, %122, %123, %124, %125, %126, %127}, "
        "%128, %129, p, 1, 1, %130, %131;\n}\n"
        : "=f"(d[0]), "=f"(d[1]), "=f"(d[2]), "=f"(d[3]), "=f"(d[4]), "=f"(d[5]), "=f"(d[6]), "=f"(d[7]),
          "=f"(d[8]), "=f"(d[9]), "=f"(d[10]), "=f"(d[11]), "=f"(d[12]), "=f"(d[13]), "=f"(d[14]), "=f"(d[15]),
          "=f"(d[16]), "=f"(d[17]), "=f"(d[18]), "=f"(d[19]), "=f"(d[20]), "=f"(d[21]), "=f"(d[22]), "=f"(d[23]),
          "=f"(d[24]), "=f"(d[25]), "=f"(d[26]), "=f"(d[27]), "=f"(d[28]), "=f"(d[29]), "=f"(d[30]), "=f"(d[31]),
          "=f"(d[32]), "=f"(d[33]), "=f"(d[34]), "=f"(d[35]), "=f"(d[36]), "=f"(d[37]), "=f"(d[38]), "=f"(d[39]),
          "=f"(d[40]), "=f"(d[41]), "=f"(d[42]), "=f"(d[43]), "=f"(d[44]), "=f"(d[45]), "=f"(d[46]), "=f"(d[47]),
          "=f"(d[48]), "=f"(d[49]), "=f"(d[50]), "=f"(d[51]), "=f"(d[52]), "=f"(d[53]), "=f"(d[54]), "=f"(d[55]),
          "=f"(d[56]), "=f"(d[57]), "=f"(d[58]), "=f"(d[59]), "=f"(d[60]), "=f"(d[61]), "=f"(d[62]), "=f"(d[63]),
          "=f"(d[64]), "=f"(d[65]), "=f"(d[66]), "=f"(d[67]), "=f"(d[68]), "=f"(d[69]), "=f"(d[70]), "=f"(d[71]),
          "=f"(d[72]), "=f"(d[73]), "=f"(d[74]), "=f"(d[75]), "=f"(d[76]), "=f"(d[77]), "=f"(d[78]), "=f"(d[79]),
          "=f"(d[80]), "=f"(d[81]), "=f"(d[82]), "=f"(d[83]), "=f"(d[84]), "=f"(d[85]), "=f"(d[86]), "=f"(d[87]),
          "=f"(d[88]), "=f"(d[89]), "=f"(d[90]), "=f"(d[91]), "=f"(d[92]), "=f"(d[93]), "=f"(d[94]), "=f"(d[95]),
          "=f"(d[96]), "=f"(d[97]), "=f"(d[98]), "=f"(d[99]), "=f"(d[100]), "=f"(d[101]), "=f"(d[102]), "=f"(d[103]),
          "=f"(d[104]), "=f"(d[105]), "=f"(d[106]), "=f"(d[107]), "=f"(d[108]), "=f"(d[109]), "=f"(d[110]), "=f"(d[111]),
          "=f"(d[112]), "=f"(d[113]), "=f"(d[114]), "=f"(d[115]), "=f"(d[116]), "=f"(d[117]), "=f"(d[118]), "=f"(d[119]),
          "=f"(d[120]), "=f"(d[121]), "=f"(d[122]), "=f"(d[123]), "=f"(d[124]), "=f"(d[125]), "=f"(d[126]), "=f"(d[127])
        : "l"(da), "l"(db), "n"(TA), "n"(TB));
}
template <int TA, int TB>
__device__ __forceinline__ void wgmma_n192(float (&d)[128], uint64_t da, uint64_t db) {
    asm volatile(
        "{\n.reg .pred p;\nsetp.ne.b32 p, 1, 0;\n"
        "wgmma.mma_async.sync.aligned.m64n192k16.f32.bf16.bf16 "
        "{%0, %1, %2, %3, %4, %5, %6, %7, %8, %9, %10, %11, %12, %13, %14, %15, "
        "%16, %17, %18, %19, %20, %21, %22, %23, %24, %25, %26, %27, %28, %29, %30, %31, "
        "%32, %33, %34, %35, %36, %37, %38, %39, %40, %41, %42, %43, %44, %45, %46, %47, "
        "%48, %49, %50, %51, %52, %53, %54, %55, %56, %57, %58, %59, %60, %61, %62, %63, "
        "%64, %65, %66, %67, %68, %69, %70, %71, %72, %73, %74, %75, %76, %77, %78, %79, "
        "%80, %81, %82, %83, %84, %85, %86, %87, %88, %89, %90, %91, %92, %93, %94, %95}, "
        "%96, %97, p, 1, 1, %98, %99;\n}\n"
        : "+f"(d[0]), "+f"(d[1]), "+f"(d[2]), "+f"(d[3]), "+f"(d[4]), "+f"(d[5]), "+f"(d[6]), "+f"(d[7]),
          "+f"(d[8]), "+f"(d[9]), "+f"(d[10]), "+f"(d[11]), "+f"(d[12]), "+f"(d[13]), "+f"(d[14]), "+f"(d[15]),
          "+f"(d[16]), "+f"(d[17]), "+f"(d[18]), "+f"(d[19]), "+f"(d[20]), "+f"(d[21]), "+f"(d[22]), "+f"(d[23]),
          "+f"(d[24]), "+f"(d[25]), "+f"(d[26]), "+f"(d[27]), "+f"(d[28]), "+f"(d[29]), "+f"(d[30]), "+f"(d[31]),
          "+f"(d[32]), "+f"(d[33]), "+f"(d[34]), "+f"(d[35]), "+f"(d[36]), "+f"(d[37]), "+f"(d[38]), "+f"(d[39]),
          "+f"(d[40]), "+f"(d[41]), "+f"(d[42]), "+f"(d[43]), "+f"(d[44]), "+f"(d[45]), "+f"(d[46]), "+f"(d[47]),
          "+f"(d[48]), "+f"(d[49]), "+f"(d[50]), "+f"(d[51]), "+f"(d[52]), "+f"(d[53]), "+f"(d[54]), "+f"(d[55]),
          "+f"(d[56]), "+f"(d[57]), "+f"(d[58]), "+f"(d[59]), "+f"(d[60]), "+f"(d[61]), "+f"(d[62]), "+f"(d[63]),
          "+f"(d[64]), "+f"(d[65]), "+f"(d[66]), "+f"(d[67]), "+f"(d[68]), "+f"(d[69]), "+f"(d[70]), "+f"(d[71]),
          "+f"(d[72]), "+f"(d[73]), "+f"(d[74]), "+f"(d[75]), "+f"(d[76]), "+f"(d[77]), "+f"(d[78]), "+f"(d[79]),
          "+f"(d[80]), "+f"(d[81]), "+f"(d[82]), "+f"(d[83]), "+f"(d[84]), "+f"(d[85]), "+f"(d[86]), "+f"(d[87]),
          "+f"(d[88]), "+f"(d[89]), "+f"(d[90]), "+f"(d[91]), "+f"(d[92]), "+f"(d[93]), "+f"(d[94]), "+f"(d[95])
        : "l"(da), "l"(db), "n"(TA), "n"(TB));
}
template <int TA, int TB>
__device__ __forceinline__ void wgmma_n192_first(float (&d)[128], uint64_t da, uint64_t db) {
    asm volatile(
        "{\n.reg .pred p;\nsetp.ne.b32 p, 0, 0;\n"
        "wgmma.mma_async.sync.aligned.m64n192k16.f32.bf16.bf16 "
        "{%0, %1, %2, %3, %4, %5, %6, %7, %8, %9, %10, %11, %12, %13, %14, %15, "
        "%16, %17, %18, %19, %20, %21, %22, %23, %24, %25, %26, %27, %28, %29, %30, %31, "
        "%32, %33, %34, %35, %36, %37, %38, %39, %40, %41, %42, %43, %44, %45, %46, %47, "
        "%48, %49, %50, %51, %52, %53, %54, %55, %56, %57, %58, %59, %60, %61, %62, %63, "
        "%64, %65, %66, %67, %68, %69, %70, %71, %72, %73, %74, %75, %76, %77, %78, %79, "
        "%80, %81, %82, %83, %84, %85, %86, %87, %88, %89, %90, %91, %92, %93, %94, %95}, "
        "%96, %97, p, 1, 1, %98, %99;\n}\n"
        : "=f"(d[0]), "=f"(d[1]), "=f"(d[2]), "=f"(d[3]), "=f"(d[4]), "=f"(d[5]), "=f"(d[6]), "=f"(d[7]),
          "=f"(d[8]), "=f"(d[9]), "=f"(d[10]), "=f"(d[11]), "=f"(d[12]), "=f"(d[13]), "=f"(d[14]), "=f"(d[15]),
          "=f"(d[16]), "=f"(d[17]), "=f"(d[18]), "=f"(d[19]), "=f"(d[20]), "=f"(d[21]), "=f"(d[22]), "=f"(d[23]),
          "=f"(d[24]), "=f"(d[25]), "=f"(d[26]), "=f"(d[27]), "=f"(d[28]), "=f"(d[29]), "=f"(d[30]), "=f"(d[31]),
          "=f"(d[32]), "=f"(d[33]), "=f"(d[34]), "=f"(d[35]), "=f"(d[36]), "=f"(d[37]), "=f"(d[38]), "=f"(d[39]),
          "=f"(d[40]), "=f"(d[41]), "=f"(d[42]), "=f"(d[43]), "=f"(d[44]), "=f"(d[45]), "=f"(d[46]), "=f"(d[47]),
          "=f"(d[48]), "=f"(d[49]), "=f"(d[50]), "=f"(d[51]), "=f"(d[52]), "=f"(d[53]), "=f"(d[54]), "=f"(d[55]),
          "=f"(d[56]), "=f"(d[57]), "=f"(d[58]), "=f"(d[59]), "=f"(d[60]), "=f"(d[61]), "=f"(d[62]), "=f"(d[63]),
          "=f"(d[64]), "=f"(d[65]), "=f"(d[66]), "=f"(d[67]), "=f"(d[68]), "=f"(d[69]), "=f"(d[70]), "=f"(d[71]),
          "=f"(d[72]), "=f"(d[73]), "=f"(d[74]), "=f"(d[75]), "=f"(d[76]), "=f"(d[77]), "=f"(d[78]), "=f"(d[79]),
          "=f"(d[80]), "=f"(d[81]), "=f"(d[82]), "=f"(d[83]), "=f"(d[84]), "=f"(d[85]), "=f"(d[86]), "=f"(d[87]),
          "=f"(d[88]), "=f"(d[89]), "=f"(d[90]), "=f"(d[91]), "=f"(d[92]), "=f"(d[93]), "=f"(d[94]), "=f"(d[95])
        : "l"(da), "l"(db), "n"(TA), "n"(TB));
}

template <int MODE, bool FIRST>
__device__ __forceinline__ void mma_kblock(float (&acc)[128], uint32_t a_lo, uint32_t b_lo) {
    constexpr uint64_t HI = (uint64_t)(64u | 0x40000000u) << 32;
    constexpr uint32_t HALF = (MODE == 1) ? 12288u : 16384u;
    constexpr bool BN = (MODE == 1 || MODE == 2);
#pragma unroll
    for (int kk = 0; kk < 4; ++kk) {
        const uint32_t ao = (MODE == 3) ? kk * 2048u : kk * 32u;
        const uint32_t bo = BN ? ((kk >> 1) * HALF + (kk & 1) * 2048u) : kk * 32u;
        const uint64_t da = HI | (uint64_t)(a_lo + (ao >> 4) + (1u << 16));
        const uint64_t db = HI | (uint64_t)(b_lo + (bo >> 4) + (BN ? (256u << 16) : (1u << 16)));
        if (MODE == 1) {
            if (FIRST && kk == 0) wgmma_n192_first<0, 1>(acc, da, db); else wgmma_n192<0, 1>(acc, da, db);
        } else {
            if (FIRST && kk == 0) wgmma_n256_first<(MODE == 3), BN>(acc, da, db);
            else wgmma_n256<(MODE == 3), BN>(acc, da, db);
        }
    }
}

struct Params {
    const __nv_bfloat16* x;
    const __nv_bfloat16* lam_re;
    const __nv_bfloat16* lam_im;
    const __nv_bfloat16* log_dt;
    const __nv_bfloat16* dskip;
    const __nv_bfloat16* b1;
    const __nv_bfloat16* b2;
    const __nv_bfloat16* gate_w;
    float* out;
    int swap;
};

#define CMUL(rr, ri, ar, ai, br, bi) do { float _r = (ar) * (br) - (ai) * (bi); float _i = (ar) * (bi) + (ai) * (br); rr = _r; ri = _i; } while (0)
#define CFMA(rr, ri, ar, ai, br, bi) do { float _r = fmaf(-(ai), (bi), fmaf((ar), (br), rr)); float _i = fmaf((ai), (br), fmaf((ar), (bi), ri)); rr = _r; ri = _i; } while (0)

#define KBLOCK_BEGIN(MODE, FIRST, IT)                                                            \
    mbar_wait(bar_full + 8 * ((IT) & 3), ((IT) >> 2) & 1);                                       \
    wgmma_fence();                                                                               \
    mma_kblock<MODE, FIRST>(acc, a_lo + ((IT) & 3) * (kStageBytes >> 4), b_lo + ((IT) & 3) * (kStageBytes >> 4)); \
    wgmma_commit();
#define RELEASE_STAGE(S) do { if (lane < (MULTICAST ? 2 : 1)) mbar_arrive_cluster(rel_addr + 8 * (S)); } while (0)

template <int KEEP>
__device__ __forceinline__ void finish(float (&acc)[128], float (&e)[64], uint32_t sbase, uint32_t bar_xfree, uint32_t bar_xdata,
                                       uint32_t rank, int tid, float* o0, float* o1) {
    constexpr int SEND = 64 - KEEP;
    const uint32_t peer = rank ^ 1u;
    mbar_wait_cluster(bar_xfree, 0);
    const uint32_t dst = mapa(sbase + tid * 16, peer), dbar = mapa(bar_xdata, peer);
#pragma unroll
    for (int i = 0; i < 16; ++i)
        st_async128(dst + i * 4096, acc[SEND + 4 * i], acc[SEND + 4 * i + 1], acc[SEND + 4 * i + 2], acc[SEND + 4 * i + 3], dbar);
    mbar_wait_cluster(bar_xdata, 0);
#pragma unroll
    for (int i = 0; i < 16; ++i) {
        uint4 v = lds128(sbase + tid * 16 + i * 4096);
        stg64f(o0 + 8 * i, acc[KEEP + 4 * i] + __uint_as_float(v.x) + e[4 * i], acc[KEEP + 4 * i + 1] + __uint_as_float(v.y) + e[4 * i + 1]);
        stg64f(o1 + 8 * i, acc[KEEP + 4 * i + 2] + __uint_as_float(v.z) + e[4 * i + 2], acc[KEEP + 4 * i + 3] + __uint_as_float(v.w) + e[4 * i + 3]);
    }
}

__global__ void __cluster_dims__(2, 1, 1) __launch_bounds__(384, 1)
fused_kernel(const __grid_constant__ CUtensorMap mB, const __grid_constant__ CUtensorMap mXs, const __grid_constant__ CUtensorMap mXf,
             const __grid_constant__ CUtensorMap mW1a, const __grid_constant__ CUtensorMap mW1b, const __grid_constant__ CUtensorMap mHs,
             const __grid_constant__ CUtensorMap mHf, const __grid_constant__ CUtensorMap mCre, const __grid_constant__ CUtensorMap mCim,
             const __grid_constant__ CUtensorMap mW2, const Params p) {
    extern __shared__ __align__(1024) uint8_t smem_raw[];
    const uint32_t sbase = smem_u32(smem_raw);
    if ((sbase & 0x3ffffu) != kSmemOrg) return;
    const uint32_t bar_full = sbase + kBarOff, bar_empty = bar_full + 32, bar_xfree = bar_full + 64, bar_xdata = bar_full + 72;

    const int tid = threadIdx.x, lane = tid & 31;
    const int warp = __shfl_sync(0xffffffffu, tid >> 5, 0);
    const uint32_t rank = blockIdx.x & 1;
    const int cl = blockIdx.x >> 1;
    const int c = cl >> 3;
    const int j8 = cl & 7;
    const int cb = j8 * 2 + (int)rank;
    const int rb = 2 * c + (int)rank;
    const int h2 = j8 >> 2, db = j8 & 3;

    STAMP(tid == 0, 0);
    if (tid == 256) {
        prefetch_map(&mB); prefetch_map(&mXs);
#pragma unroll
        for (int s = 0; s < kStages; ++s) {
            mbar_init(bar_full + 8 * s, 1);
            mbar_init(bar_empty + 8 * s, MULTICAST ? 16 : 8);
        }
        mbar_init(bar_xfree, 8);
        mbar_init(bar_xdata, 1);
        asm volatile("fence.mbarrier_init.release.cluster;" ::: "memory");
        mbar_expect_tx(bar_xdata, 65536);
    }
    unsigned tag;
    asm volatile("ld.relaxed.gpu.global.u32 %0, [%1];" : "=r"(tag) : "l"(&g_epoch) : "memory");
    tag += 1;
    cluster_sync_all();

    if (warp >= 8) {
        asm volatile("setmaxnreg.dec.sync.aligned.u32 24;");
        if (warp == 8) {
            if (lane == 0) {
                int it = 0;
#define ACQUIRE(BYTES)                                                   \
    const uint32_t st = sbase + (it & 3) * kStageBytes, fb = bar_full + 8 * (it & 3); \
    mbar_wait(bar_empty + 8 * (it & 3), ((it >> 2) & 1) ^ 1);            \
    mbar_expect_tx(fb, BYTES);
                for (int kb = 0; kb < 16; ++kb, ++it) {
                    ACQUIRE(49152);
                    tma4(st, &mB, fb, kb * 64, 0, 0, cb * 8);
                    tma5_mc(st + kABytes + rank * 16384, &mXs, fb, kb * 64, 0, 0, rank * 16, c);
                    if (kb == 3) { prefetch_map(&mXf); prefetch_map(&mW1b); prefetch_map(&mW1a); }
                }
                for (int kb = 0; kb < 16; ++kb, ++it) {
                    ACQUIRE(40960);
                    tma5(st, &mXf, fb, kb * 64, 0, 0, rank * 4, c);
                    tma3_mc(st + kABytes + rank * 12288, &mW1b, fb, 0, kb * 64 + rank * 32, 32 + 3 * j8);
                }
                prefetch_map(&mHs); prefetch_map(&mHf); prefetch_map(rank ? &mCim : &mCre); prefetch_map(&mW2);
                for (int kb = 0; kb < 16; ++kb, ++it) {
                    ACQUIRE(49152);
                    tma5(st, &mXf, fb, kb * 64, 0, 0, rank * 4, c);
                    tma3_mc(st + kABytes + rank * 16384, &mW1a, fb, 0, kb * 64 + rank * 32, 4 * j8);
                }
                const int rb2 = 2 * c + h2;
                const CUtensorMap* mC = rank ? &mCim : &mCre;
                STAMP(true, 8);
                wait_counter(&g_cnt[c * 32], tag * 16u);
                STAMP(true, 9);
                for (int kb = 0; kb < 16; ++kb, ++it) {
                    ACQUIRE(49152);
                    tma3(st, &mHs, fb, 0, rank * 1024 + kb * 64, rb2 * 2);
                    tma2(st + kABytes, mC, fb, kb * 64, db * 256);
                }
                wait_counter(&g_cnt[(8 + rb2 * 2 + rank) * 32], tag * 4u);
                STAMP(true, 10);
                for (int kb = 0; kb < 28; ++kb, ++it) {
                    if (kb == 12) { wait_counter(&g_cnt[(40 + rb2 * 2 + rank) * 32], tag * 4u); STAMP(true, 11); }
                    const int f0 = (kb < 12) ? 2048 + 768 * rank + 64 * kb : 1024 * rank + 64 * (kb - 12);
                    ACQUIRE(49152);
                    tma2(st, &mHf, fb, f0, rb2 * 128);
                    tma5(st + kABytes, &mW2, fb, 0, 0, f0 >> 3, 0, db * 4);
                    tma5(st + kABytes + 16384, &mW2, fb, 0, 0, (f0 >> 3) + 4, 0, db * 4);
                }
            }
        } else if (warp == 9) {
#pragma unroll
            for (int ev = 0; ev < 3; ++ev) {
                if (ev == 0) bar_sync<3, 288>(); else if (ev == 1) bar_sync<4, 288>(); else bar_sync<5, 288>();
                if (lane == 0) {
                    unsigned* cnt = &g_cnt[(ev == 0 ? c : (ev == 1 ? 8 : 40) + rb * 2 + (j8 >> 2)) * 32];
                    asm volatile("fence.acq_rel.gpu;\nfence.proxy.async.global;" ::: "memory");
                    asm volatile("red.relaxed.gpu.global.add.u32 [%0], 1;" ::"l"(cnt) : "memory");
                }
            }
        }
        __syncwarp();
        cluster_sync_all();
    } else {
        asm volatile("setmaxnreg.inc.sync.aligned.u32 240;");
        const int wg = warp >> 2, w = warp & 3, r = lane >> 2, q = lane & 3, tw = tid & 127;
        const uint32_t a_lo = (kSmemOrg + wg * 8192) >> 4;
        constexpr uint32_t b_lo = (kSmemOrg + kABytes) >> 4;
        const uint32_t rel_addr = mapa(bar_empty, MULTICAST ? (uint32_t)(lane & 1) : rank);
        const uint32_t gate_s = sbase + kGateOff + wg * kGateBytesWG, bias_s = sbase + kBiasOff + wg * kBiasBytesWG;
        float acc[128];
        uint32_t pk[64];

        const int ch = cb * 64 + warp * 8 + r;
        float lr, li, m00, m01, m10, m11;
        {
            uint4 gx[8], gw[4];
            const int grow = c * 256 + cb * 16 + warp * 2;
#pragma unroll
            for (int i = 0; i < 4; ++i) gw[i] = ldg128(p.gate_w + i * 256 + lane * 8);
#pragma unroll
            for (int i = 0; i < 8; ++i) gx[i] = ldg128(p.x + (size_t)(grow + (i >> 2)) * kD + (i & 3) * 256 + lane * 8);
            const float Lr = ldg_bf16(p.lam_re + ch), Li = ldg_bf16(p.lam_im + ch), Ldt = ldg_bf16(p.log_dt + ch);
            uint32_t bz[4] = {0, 0, 0, 0};
            if (tw < 56) {
                const int J = tw >> 2, f0 = (J < 6) ? 2048 + 192 * j8 + 32 * J : 256 * j8 + 32 * (J - 6);
#pragma unroll
                for (int jj = 0; jj < 4; ++jj) bz[jj] = ldg32(p.b1 + f0 + 8 * jj + 2 * (tw & 3));
            }
            uint2 gv0, gv1;
#pragma unroll
            for (int kb = 0; kb < 16; ++kb) {
                if (kb == 0) { KBLOCK_BEGIN(0, true, kb); STAMP(tid == 0, 1); } else { KBLOCK_BEGIN(0, false, kb); }
                if (kb == 1) {
                    float s0 = 0.f, s1 = 0.f;
#pragma unroll
                    for (int i = 0; i < 4; ++i) {
                        const uint32_t wv[4] = {gw[i].x, gw[i].y, gw[i].z, gw[i].w};
                        const uint32_t xa[4] = {gx[i].x, gx[i].y, gx[i].z, gx[i].w};
                        const uint32_t xb[4] = {gx[4 + i].x, gx[4 + i].y, gx[4 + i].z, gx[4 + i].w};
#pragma unroll
                        for (int k = 0; k < 4; ++k) {
                            const uint32_t pa = bf2_mul(xa[k], wv[k]), pb = bf2_mul(xb[k], wv[k]);
                            s0 += bf_lo(pa) + bf_hi(pa);
                            s1 += bf_lo(pb) + bf_hi(pb);
                        }
                    }
#pragma unroll
                    for (int o = 16; o > 0; o >>= 1) {
                        s0 += __shfl_xor_sync(0xffffffffu, s0, o);
                        s1 += __shfl_xor_sync(0xffffffffu, s1, o);
                    }
                    if (lane < 2) {
                        const float z = bf16_round(lane ? s1 : s0);
                        const float g = bf16_round(1.0f / (1.0f + expf(-z)));
                        st_relaxed64(&g_gate[grow + lane], __float_as_uint(g), tag);
                    }
                }
                if (kb == 2) {
                    const float dt = bf16_round(expf(Ldt));
                    const float ea = expf(dt * Lr);
                    float sn, cs;
                    sincospif((dt * Li) * 0.31830988618379067f, &sn, &cs);
                    lr = ea * cs; li = ea * sn;
                    const float nr = lr - 1.0f, ni = li;
                    float cr, ci;
                    if (fabsf(Lr) >= fabsf(Li)) {
                        const float t = Li / Lr, d = 1.0f / fmaf(Li, t, Lr);
                        cr = fmaf(ni, t, nr) * d; ci = fmaf(-nr, t, ni) * d;
                    } else {
                        const float t = Lr / Li, d = 1.0f / fmaf(Lr, t, Li);
                        cr = fmaf(nr, t, ni) * d; ci = fmaf(ni, t, -nr) * d;
                    }
                    if (p.swap) { li = -li; m00 = -2.f * ci; m01 = 2.f * cr; m10 = -2.f * cr; m11 = -2.f * ci; }
                    else { m00 = 2.f * cr; m01 = -2.f * ci; m10 = -2.f * ci; m11 = -2.f * cr; }
                    PIN_F(lr); PIN_F(li); PIN_F(m00); PIN_F(m01); PIN_F(m10); PIN_F(m11);
                }
                if (kb == 3) {
                    if (tw < 56) sts128(bias_s + tw * 16, bz[0], bz[1], bz[2], bz[3]);
                }
                if (kb == 10) {
                    gv0 = ld_relaxed64(&g_gate[c * 256 + tw]);
                    gv1 = ld_relaxed64(&g_gate[c * 256 + 128 + tw]);
                }
                if (kb == 12) {
                    unsigned n = 0;
                    while (gv0.y != tag || gv1.y != tag) {
                        if (++n > kSpinLimit) TRAP();
                        gv0 = ld_relaxed64(&g_gate[c * 256 + tw]);
                        gv1 = ld_relaxed64(&g_gate[c * 256 + 128 + tw]);
                    }
                    sts32(gate_s + ((tw >> 6) * 68 + (tw & 63)) * 4, gv0.x);
                    sts32(gate_s + ((2 + (tw >> 6)) * 68 + (tw & 63)) * 4, gv1.x);
                    __syncwarp();
                }
                if (kb == 13) { if (wg == 0) bar_sync<1, 128>(); else bar_sync<2, 128>(); }
                if (kb > 0) { wgmma_wait<1>(); RELEASE_STAGE((kb - 1) & 3); }
            }
            wgmma_wait<0>();
            RELEASE_STAGE(3);
        }
        STAMP(tid == 0, 2);
#pragma unroll
        for (int s = 0; s < 64; ++s) pk[s] = pack_bf16_v(acc[4 * (s >> 1) + (s & 1)], acc[4 * (s >> 1) + 2 + (s & 1)]);

        {
            float hr = 0.f, hi = 0.f;
            float l64r, l64i, l128r, l128i;
            uint4 av0, av1;
            __nv_bfloat16* hs = g_Hs + (size_t)ch * 2048 + c * 256 + q * 8;
#pragma unroll
            for (int kb = 0; kb < 16; ++kb) {
                if (kb == 0) { KBLOCK_BEGIN(1, true, kb); } else { KBLOCK_BEGIN(1, false, kb); }
                if (kb < 4) {
#pragma unroll
                    for (int s = kb * 16; s < kb * 16 + 16; ++s) {
                        float nr = bf_lo(pk[s]), ni = bf_hi(pk[s]);
                        CFMA(nr, ni, lr, li, hr, hi);
                        hr = nr; hi = ni;
                    }
                    PIN_F(hr); PIN_F(hi);
                }
                if (kb == 0) {
                    l64r = lr; l64i = li;
#pragma unroll
                    for (int i = 0; i < 6; ++i) CMUL(l64r, l64i, l64r, l64i, l64r, l64i);
                    CMUL(l128r, l128i, l64r, l64i, l64r, l64i);
                    PIN_F(l64r); PIN_F(l64i); PIN_F(l128r); PIN_F(l128i);
                }
                if (kb == 3) {
                    float tr = __shfl_up_sync(0xffffffffu, hr, 1, 4), ti = __shfl_up_sync(0xffffffffu, hi, 1, 4);
                    if (q >= 1) CFMA(hr, hi, l64r, l64i, tr, ti);
                    tr = __shfl_up_sync(0xffffffffu, hr, 2, 4); ti = __shfl_up_sync(0xffffffffu, hi, 2, 4);
                    if (q >= 2) CFMA(hr, hi, l128r, l128i, tr, ti);
                    if (q == 3) st_relaxed2x64(&g_agg[c * 1024 + ch], __float_as_uint(hr), tag, __float_as_uint(hi), tag);
                    tr = __shfl_up_sync(0xffffffffu, hr, 1, 4); ti = __shfl_up_sync(0xffffffffu, hi, 1, 4);
                    hr = (q >= 1) ? tr : 0.f; hi = (q >= 1) ? ti : 0.f;
                }
                if (kb == 5) {
                    av0 = make_uint4(0, tag, 0, tag); av1 = av0;
                    if (q < c) av0 = ld_relaxed2x64(&g_agg[q * 1024 + ch]);
                    if (q + 4 < c) av1 = ld_relaxed2x64(&g_agg[(q + 4) * 1024 + ch]);
                }
                if (kb == 6) {
                    unsigned n = 0;
                    while (av0.y != tag || av0.w != tag || av1.y != tag || av1.w != tag) {
                        if (++n > kSpinLimit) TRAP();
                        if (q < c) av0 = ld_relaxed2x64(&g_agg[q * 1024 + ch]);
                        if (q + 4 < c) av1 = ld_relaxed2x64(&g_agg[(q + 4) * 1024 + ch]);
                    }
                    __syncwarp();
                    float l256r, l256i, l512r, l512i, l1kr, l1ki;
                    CMUL(l256r, l256i, l128r, l128i, l128r, l128i);
                    CMUL(l512r, l512i, l256r, l256i, l256r, l256i);
                    CMUL(l1kr, l1ki, l512r, l512i, l512r, l512i);
                    float vr = __uint_as_float(av0.x), vi = __uint_as_float(av0.z);
                    int n2 = c - 1 - q;
                    if (q + 4 < c) {
                        float ur = __uint_as_float(av1.x), ui = __uint_as_float(av1.z);
                        CFMA(ur, ui, l1kr, l1ki, vr, vi);
                        vr = ur; vi = ui; n2 -= 4;
                    }
                    if (n2 > 0 && (n2 & 1)) CMUL(vr, vi, vr, vi, l256r, l256i);
                    if (n2 > 0 && (n2 & 2)) CMUL(vr, vi, vr, vi, l512r, l512i);
                    vr += __shfl_xor_sync(0xffffffffu, vr, 1); vi += __shfl_xor_sync(0xffffffffu, vi, 1);
                    vr += __shfl_xor_sync(0xffffffffu, vr, 2); vi += __shfl_xor_sync(0xffffffffu, vi, 2);
                    if (q & 1) CMUL(vr, vi, vr, vi, l64r, l64i);
                    if (q & 2) CMUL(vr, vi, vr, vi, l128r, l128i);
                    hr += vr; hi += vi;
                }
                if (kb >= 7 && kb < 15) {
                    const int i = kb - 7;
                    const uint4 ga = lds128(gate_s + (q * 68 + 8 * i) * 4), gb = lds128(gate_s + (q * 68 + 8 * i + 4) * 4);
                    const uint32_t gg[8] = {ga.x, ga.y, ga.z, ga.w, gb.x, gb.y, gb.z, gb.w};
                    float orr[8], oii[8];
#pragma unroll
                    for (int s = 0; s < 8; ++s) {
                        PIN_R(pk[8 * i + s]);
                        float nr = bf_lo(pk[8 * i + s]), ni = bf_hi(pk[8 * i + s]);
                        CFMA(nr, ni, lr, li, hr, hi);
                        hr = nr; hi = ni;
                        const float g = __uint_as_float(gg[s]);
                        orr[s] = fmaf(m00, hr, m01 * hi) * g;
                        oii[s] = fmaf(m10, hr, m11 * hi) * g;
                    }
                    stg128(hs + 32 * i, pack_bf16(orr[0], orr[1]), pack_bf16(orr[2], orr[3]), pack_bf16(orr[4], orr[5]), pack_bf16(orr[6], orr[7]));
                    stg128(hs + 1024 * 2048 + 32 * i, pack_bf16(oii[0], oii[1]), pack_bf16(oii[2], oii[3]), pack_bf16(oii[4], oii[5]), pack_bf16(oii[6], oii[7]));
                    if (kb == 14) bar_arrive<3, 288>();
                }
                if (kb > 0) { wgmma_wait<1>(); RELEASE_STAGE((kb - 1) & 3); }
            }
            wgmma_wait<0>();
            RELEASE_STAGE(3);
        }
        STAMP(tid == 0, 3);
#pragma unroll
        for (int i = 0; i < 48; ++i) pk[i] = pack_bf16_v(acc[2 * i], acc[2 * i + 1]);

        uint32_t om0, om1;
        {
            const int gi = (2 * (w & 1)) * 68 + 8 * (4 * rank + 2 * wg + (w >> 1)) + r;
            const float a = 1.0f - lds32f(gate_s + gi * 4), b = 1.0f - lds32f(gate_s + (gi + 68) * 4);
            om0 = pack_bf16(a, a); om1 = pack_bf16(b, b);
        }
        __nv_bfloat16* hf = g_Hf + (size_t)(rb * 128 + wg * 64 + w * 16 + r) * kF + q * 8;
#define FFN_SLICE(J, BIAS_ENTRY, F0)                                                                   \
    {                                                                                                  \
        const uint4 bv = lds128(bias_s + ((BIAS_ENTRY) * 4 + q) * 16);                                 \
        const uint32_t bb[4] = {bv.x, bv.y, bv.z, bv.w};                                               \
        uint32_t o0[4], o1[4];                                                                         \
        _Pragma("unroll") for (int jj = 0; jj < 4; ++jj) {                                             \
            const uint32_t r0 = bf2_add_relu(pk[8 * (J) + 2 * jj], bb[jj]), r1 = bf2_add_relu(pk[8 * (J) + 2 * jj + 1], bb[jj]); \
            o0[jj] = bf2_mul(bf2_mul(r0, r0), om0);                                                    \
            o1[jj] = bf2_mul(bf2_mul(r1, r1), om1);                                                    \
        }                                                                                              \
        stg128(hf + (F0) + 32 * (J), o0[0], o0[1], o0[2], o0[3]);                                      \
        stg128(hf + 8 * kF + (F0) + 32 * (J), o1[0], o1[1], o1[2], o1[3]);                             \
    }

        {
            const int f0 = 2048 + 192 * j8;
#pragma unroll
            for (int kb = 0; kb < 16; ++kb) {
                if (kb == 0) { KBLOCK_BEGIN(2, true, kb); } else { KBLOCK_BEGIN(2, false, kb); }
                if (kb < 6) FFN_SLICE(kb, kb, f0);
                if (kb == 5) bar_arrive<4, 288>();
                if (kb > 0) { wgmma_wait<1>(); RELEASE_STAGE((kb - 1) & 3); }
            }
            wgmma_wait<0>();
            RELEASE_STAGE(3);
        }
        STAMP(tid == 0, 4);
#pragma unroll
        for (int i = 0; i < 64; ++i) pk[i] = pack_bf16_v(acc[2 * i], acc[2 * i + 1]);

        float e[64];
        const int t0 = c * 256 + 128 * (w & 1) + 8 * (4 * h2 + 2 * wg + (w >> 1)) + r;
        const int d0 = db * 256 + rank * 128 + 2 * q;
        {
            const int f0 = 256 * j8;
            uint32_t xv[8], dv[4], bv2[4];
            float g0, g1, o0f, o1f;
#pragma unroll
            for (int kb = 0; kb < 16; ++kb) {
                if (kb == 0) { KBLOCK_BEGIN(3, true, kb); } else { KBLOCK_BEGIN(3, false, kb); }
                if (kb < 8) FFN_SLICE(kb, 6 + kb, f0);
                if (kb == 7) bar_arrive<5, 288>();
                if (kb == 8) {
                    const int gi = (2 * (w & 1)) * 68 + 8 * (4 * h2 + 2 * wg + (w >> 1)) + r;
                    g0 = lds32f(gate_s + gi * 4); g1 = lds32f(gate_s + (gi + 68) * 4);
                    o0f = bf16_round(1.0f - g0); o1f = bf16_round(1.0f - g1);
                }
                if (kb >= 9 && kb < 13) {
                    const int jb = (kb - 9) * 4;
#pragma unroll
                    for (int jj = 0; jj < 4; ++jj) {
                        const uint32_t x0 = bf2_mul(xv[2 * jj], dv[jj]), x1 = bf2_mul(xv[2 * jj + 1], dv[jj]);
                        const float bl = bf_lo(bv2[jj]), bh = bf_hi(bv2[jj]);
                        e[4 * (jb + jj) + 0] = fmaf(g0, bf_lo(x0), o0f * bl);
                        e[4 * (jb + jj) + 1] = fmaf(g0, bf_hi(x0), o0f * bh);
                        e[4 * (jb + jj) + 2] = fmaf(g1, bf_lo(x1), o1f * bl);
                        e[4 * (jb + jj) + 3] = fmaf(g1, bf_hi(x1), o1f * bh);
                        PIN_F(e[4 * (jb + jj)]); PIN_F(e[4 * (jb + jj) + 1]); PIN_F(e[4 * (jb + jj) + 2]); PIN_F(e[4 * (jb + jj) + 3]);
                    }
                }
                if (kb >= 8 && kb < 12) {
                    const int jb = (kb - 8) * 4;
#pragma unroll
                    for (int jj = 0; jj < 4; ++jj) {
                        xv[2 * jj] = ldg32(p.x + (size_t)t0 * kD + d0 + 8 * (jb + jj));
                        xv[2 * jj + 1] = ldg32(p.x + (size_t)(t0 + 64) * kD + d0 + 8 * (jb + jj));
                        dv[jj] = ldg32(p.dskip + d0 + 8 * (jb + jj));
                        bv2[jj] = ldg32(p.b2 + d0 + 8 * (jb + jj));
                    }
                }
                if (kb > 0) { wgmma_wait<1>(); RELEASE_STAGE((kb - 1) & 3); }
            }
        }
        STAMP(tid == 0, 5);
#pragma unroll 1
        for (int k4 = 0; k4 < 7; ++k4) {
#pragma unroll
            for (int s = 0; s < 4; ++s) {
                mbar_wait(bar_full + 8 * s, k4 & 1);
                wgmma_fence();
                mma_kblock<2, false>(acc, a_lo + s * (kStageBytes >> 4), b_lo + s * (kStageBytes >> 4));
                wgmma_commit();
                wgmma_wait<1>();
                RELEASE_STAGE((s + 3) & 3);
            }
        }
        wgmma_wait<0>();
        STAMP(tid == 0, 6);
        if (lane == 0) mbar_arrive_cluster(mapa(bar_xfree, rank ^ 1u));
        {
            float* o0 = p.out + (size_t)t0 * kD + d0;
            float* o1 = o0 + 64 * kD;
            if (rank == 0) finish<0>(acc, e, sbase, bar_xfree, bar_xdata, rank, tid, o0, o1);
            else finish<64>(acc, e, sbase, bar_xfree, bar_xdata, rank, tid, o0, o1);
        }
        STAMP(tid == 0, 7);
        if (tid == 0) {
            unsigned old = atomicInc(&g_done, 127u);
            if (old == 127u) asm volatile("st.relaxed.gpu.global.u32 [%0], %1;" ::"l"(&g_epoch), "r"(tag) : "memory");
        }
        __syncwarp();
        cluster_sync_all();
    }
}

typedef CUresult (*EncodeFn)(CUtensorMap*, CUtensorMapDataType, cuuint32_t, void*, const cuuint64_t*, const cuuint64_t*,
                             const cuuint32_t*, const cuuint32_t*, CUtensorMapInterleave, CUtensorMapSwizzle,
                             CUtensorMapL2promotion, CUtensorMapFloatOOBfill);

bool encode(EncodeFn fn, CUtensorMap* m, const void* base, int rank, const cuuint64_t* dims, const cuuint64_t* strides,
            const cuuint32_t* box) {
    cuuint32_t es[5] = {1, 1, 1, 1, 1};
    return fn(m, CU_TENSOR_MAP_DATA_TYPE_BFLOAT16, rank, const_cast<void*>(base), dims, strides, box, es,
              CU_TENSOR_MAP_INTERLEAVE_NONE, CU_TENSOR_MAP_SWIZZLE_128B, CU_TENSOR_MAP_L2_PROMOTION_L2_256B,
              CU_TENSOR_MAP_FLOAT_OOB_FILL_NONE) == CUDA_SUCCESS;
}

}

extern "C" void kernel_launch(void* const* d_in, const int* in_sizes, int n_in, void* d_out, int out_size) {
    (void)in_sizes; (void)n_in; (void)out_size;
    typedef const __nv_bfloat16* bp;
    bp x = (bp)d_in[0], lam_re = (bp)d_in[1], lam_im = (bp)d_in[2], B_re = (bp)d_in[3], B_im = (bp)d_in[4];
    bp C_re = (bp)d_in[5], C_im = (bp)d_in[6], log_dt = (bp)d_in[7], dskip = (bp)d_in[8];
    bp w1 = (bp)d_in[10], b1 = (bp)d_in[11], w2 = (bp)d_in[12], b2 = (bp)d_in[13], gate_w = (bp)d_in[14];

    static EncodeFn fn = nullptr;
    static void *pHs = nullptr, *pHf = nullptr, *pBc = nullptr;
    if (!fn) {
        void* f = nullptr;
        cudaDriverEntryPointQueryResult qr;
        cudaGetDriverEntryPoint("cuTensorMapEncodeTiled", &f, cudaEnableDefault, &qr);
        fn = (EncodeFn)f;
        cudaGetSymbolAddress(&pHs, g_Hs);
        cudaGetSymbolAddress(&pHf, g_Hf);
        cudaGetSymbolAddress(&pBc, g_Bcopy);
        cudaFuncSetAttribute(fused_kernel, cudaFuncAttributeMaxDynamicSharedMemorySize, kSmemBytes);
    }
    cudaStream_t stream = cudaStreamPerThread;

    Params p;
    p.x = x; p.lam_re = lam_re; p.lam_im = lam_im; p.log_dt = log_dt; p.dskip = dskip; p.b1 = b1; p.b2 = b2;
    p.gate_w = gate_w; p.out = (float*)d_out;

    const char* lo = (const char*)B_re; const char* hi = (const char*)B_im;
    p.swap = 0;
    if (hi < lo) { const char* t = lo; lo = hi; hi = t; p.swap = 1; }
    unsigned long long diff = (unsigned long long)(hi - lo);
    if (diff >= (1ull << 40) || (diff & 15) || diff == 0) {
        cudaMemcpyAsync(pBc, B_re, 2u << 20, cudaMemcpyDeviceToDevice, stream);
        cudaMemcpyAsync((char*)pBc + (2u << 20), B_im, 2u << 20, cudaMemcpyDeviceToDevice, stream);
        lo = (const char*)pBc; diff = 2u << 20; p.swap = 0;
    }

    CUtensorMap mB, mXs, mXf, mW1a, mW1b, mHs, mHf, mCre, mCim, mW2;
    bool ok = true;
    { cuuint64_t d[4] = {1024, 8, 2, 128}, s[3] = {2048, diff, 16384}; cuuint32_t b[4] = {64, 8, 2, 8};
      ok &= encode(fn, &mB, lo, 4, d, s, b); }
    { cuuint64_t d[5] = {1024, 2, 4, 32, 8}, s[4] = {2048, 64 * 2048, 2 * 2048, 256 * 2048}; cuuint32_t b[5] = {64, 2, 4, 16, 1};
      ok &= encode(fn, &mXs, x, 5, d, s, b); }
    { cuuint64_t d[5] = {1024, 8, 4, 8, 8}, s[4] = {2048, 64 * 2048, 8 * 2048, 256 * 2048}; cuuint32_t b[5] = {64, 8, 4, 4, 1};
      ok &= encode(fn, &mXf, x, 5, d, s, b); }
    { cuuint64_t d[3] = {64, 1024, 56}, s[2] = {7168, 128}; cuuint32_t ba[3] = {64, 32, 4}, bb[3] = {64, 32, 3};
      ok &= encode(fn, &mW1a, w1, 3, d, s, ba); ok &= encode(fn, &mW1b, w1, 3, d, s, bb); }
    { cuuint64_t d[3] = {64, 2048, 32}, s[2] = {4096, 128}; cuuint32_t b[3] = {64, 64, 2};
      ok &= encode(fn, &mHs, pHs, 3, d, s, b); }
    { cuuint64_t d[2] = {3584, 2048}, s[1] = {7168}; cuuint32_t b[2] = {64, 128};
      ok &= encode(fn, &mHf, pHf, 2, d, s, b); }
    { cuuint64_t d[2] = {1024, 1024}, s[1] = {2048}; cuuint32_t b[2] = {64, 256};
      ok &= encode(fn, &mCre, C_re, 2, d, s, b); ok &= encode(fn, &mCim, C_im, 2, d, s, b); }
    { cuuint64_t d[5] = {64, 2, 448, 4, 16}, s[4] = {2048, 8 * 2048, 2 * 2048, 128}; cuuint32_t b[5] = {64, 2, 4, 4, 4};
      ok &= encode(fn, &mW2, w2, 5, d, s, b); }
    if (!ok) return;

    fused_kernel<<<128, 384, kSmemBytes, stream>>>(mB, mXs, mXf, mW1a, mW1b, mHs, mHf, mCre, mCim, mW2, p);
}
```

```cpp
#include <cuda_runtime.h>
#include <cuda_bf16.h>
#include <cuda.h>
#include <stdint.h>

#define MTAIL 12

#define FIRSTN 1

#define GATE_LD 5

#define PF0LINES 2

namespace {

constexpr int kD = 1024, kF = 3584;
constexpr int kStages = 4;
constexpr int kStageBytes = 49152;
constexpr int kABytes = 16384;
constexpr int kAux = kStages * kStageBytes;
constexpr int kGateOff = kAux;
constexpr int kGateBytesWG = 4 * 68 * 4;
constexpr int kBiasOff = kGateOff + 2 * kGateBytesWG;
constexpr int kBiasBytesWG = 88 * 16;
constexpr int kBarOff = kBiasOff + 2 * kBiasBytesWG;
constexpr int kSmemBytes = kBarOff + 256;
constexpr uint32_t kSmemOrg = 1024;
constexpr unsigned kSpinLimit = 1u << 22;
constexpr int kTail = MTAIL;
constexpr int kNA = (32 - kTail) / 2;
constexpr int kNF = 12 + kNA;
constexpr int kTotal = 64 + kNF + kTail;

__device__ __align__(1024) __nv_bfloat16 g_Hs[2048 * 2048];
__device__ __align__(1024) __nv_bfloat16 g_Hf[2048 * 3584];
__device__ __align__(1024) __nv_bfloat16 g_Bcopy[2 * 1024 * 1024];
__device__ uint4 g_agg[8 * 1024];
__device__ uint2 g_gate[2048];
__device__ unsigned g_cnt[40 * 32];
__device__ __align__(1024) float g_X[128 * 16384];
__device__ unsigned g_xflag[128 * 32];
__device__ __align__(16) unsigned g_claim[64];
__device__ unsigned g_epoch;
__device__ unsigned g_done;

#define TRAP() break
#define PIN_F(x) asm volatile("" : "+f"(x))
#define PIN_R(x) asm volatile("" : "+r"(x))
__device__ __forceinline__ uint32_t smem_u32(const void* p) { return (uint32_t)__cvta_generic_to_shared(p); }
__device__ __forceinline__ void mbar_init(uint32_t bar, uint32_t count) {
    asm volatile("mbarrier.init.shared::cta.b64 [%0], %1;" ::"r"(bar), "r"(count) : "memory");
}
__device__ __forceinline__ void mbar_expect_tx(uint32_t bar, uint32_t bytes) {
    asm volatile("mbarrier.arrive.expect_tx.shared::cta.b64 _, [%0], %1;" ::"r"(bar), "r"(bytes) : "memory");
}
__device__ __forceinline__ void mbar_wait(uint32_t bar, uint32_t parity) {
    asm volatile(
        "{\n.reg .pred p;\n.reg .u32 n;\n"
        "mbarrier.try_wait.parity.shared::cta.b64 p, [%0], %1;\n"
        "@p bra DONE;\n"
        "mov.u32 n, 0;\n"
        "LOOP:\n"
        "mbarrier.try_wait.parity.shared::cta.b64 p, [%0], %1;\n"
        "@p bra DONE;\n"
        "add.u32 n, n, 1;\n"
        "setp.lt.u32 p, n, %2;\n"
        "@p bra LOOP;\n"
        "DONE:\n}\n"
        ::"r"(bar), "r"(parity), "n"(kSpinLimit) : "memory");
}
__device__ __forceinline__ void mbar_arrive_local(uint32_t bar) {
    asm volatile("mbarrier.arrive.shared::cta.b64 _, [%0];" ::"r"(bar) : "memory");
}
__device__ __forceinline__ void mbar_arrive_cluster(uint32_t cluster_addr) {
    asm volatile("mbarrier.arrive.shared::cluster.b64 _, [%0];" ::"r"(cluster_addr) : "memory");
}
__device__ __forceinline__ uint32_t mapa(uint32_t addr, uint32_t rank) {
    uint32_t r;
    asm("mapa.shared::cluster.u32 %0, %1, %2;" : "=r"(r) : "r"(addr), "r"(rank));
    return r;
}
__device__ __forceinline__ void cluster_arrive() { asm volatile("barrier.cluster.arrive.relaxed.aligned;" ::: "memory"); }
__device__ __forceinline__ void cluster_wait() { asm volatile("barrier.cluster.wait.acquire.aligned;" ::: "memory"); }
template <int ID, int N>
__device__ __forceinline__ void bar_sync() { asm volatile("bar.sync %0, %1;" ::"n"(ID), "n"(N) : "memory"); }
template <int ID, int N>
__device__ __forceinline__ void bar_arrive() { asm volatile("bar.arrive %0, %1;" ::"n"(ID), "n"(N) : "memory"); }

__device__ __forceinline__ void tma2(uint32_t dst, const CUtensorMap* m, uint32_t bar, int c0, int c1) {
    asm volatile("cp.async.bulk.tensor.2d.shared::cluster.global.mbarrier::complete_tx::bytes [%0], [%1, {%3, %4}], [%2];"
                 ::"r"(dst), "l"(m), "r"(bar), "r"(c0), "r"(c1) : "memory");
}
__device__ __forceinline__ void tma3(uint32_t dst, const CUtensorMap* m, uint32_t bar, int c0, int c1, int c2) {
    asm volatile("cp.async.bulk.tensor.3d.shared::cluster.global.mbarrier::complete_tx::bytes [%0], [%1, {%3, %4, %5}], [%2];"
                 ::"r"(dst), "l"(m), "r"(bar), "r"(c0), "r"(c1), "r"(c2) : "memory");
}
__device__ __forceinline__ void tma4(uint32_t dst, const CUtensorMap* m, uint32_t bar, int c0, int c1, int c2, int c3) {
    asm volatile("cp.async.bulk.tensor.4d.shared::cluster.global.mbarrier::complete_tx::bytes [%0], [%1, {%3, %4, %5, %6}], [%2];"
                 ::"r"(dst), "l"(m), "r"(bar), "r"(c0), "r"(c1), "r"(c2), "r"(c3) : "memory");
}
__device__ __forceinline__ void tma5(uint32_t dst, const CUtensorMap* m, uint32_t bar, int c0, int c1, int c2, int c3, int c4) {
    asm volatile("cp.async.bulk.tensor.5d.shared::cluster.global.mbarrier::complete_tx::bytes [%0], [%1, {%3, %4, %5, %6, %7}], [%2];"
                 ::"r"(dst), "l"(m), "r"(bar), "r"(c0), "r"(c1), "r"(c2), "r"(c3), "r"(c4) : "memory");
}
__device__ __forceinline__ void tma2_mc(uint32_t dst, const CUtensorMap* m, uint32_t bar, int c0, int c1) {
    asm volatile("cp.async.bulk.tensor.2d.shared::cluster.global.mbarrier::complete_tx::bytes.multicast::cluster [%0], [%1, {%3, %4}], [%2], %5;"
                 ::"r"(dst), "l"(m), "r"(bar), "r"(c0), "r"(c1), "h"((uint16_t)3) : "memory");
}
__device__ __forceinline__ void tma3_mc(uint32_t dst, const CUtensorMap* m, uint32_t bar, int c0, int c1, int c2) {
    asm volatile("cp.async.bulk.tensor.3d.shared::cluster.global.mbarrier::complete_tx::bytes.multicast::cluster [%0], [%1, {%3, %4, %5}], [%2], %6;"
                 ::"r"(dst), "l"(m), "r"(bar), "r"(c0), "r"(c1), "r"(c2), "h"((uint16_t)3) : "memory");
}
__device__ __forceinline__ void tma5_mc(uint32_t dst, const CUtensorMap* m, uint32_t bar, int c0, int c1, int c2, int c3, int c4) {
    asm volatile("cp.async.bulk.tensor.5d.shared::cluster.global.mbarrier::complete_tx::bytes.multicast::cluster [%0], [%1, {%3, %4, %5, %6, %7}], [%2], %8;"
                 ::"r"(dst), "l"(m), "r"(bar), "r"(c0), "r"(c1), "r"(c2), "r"(c3), "r"(c4), "h"((uint16_t)3) : "memory");
}
__device__ __forceinline__ void bulk_store(void* dst, uint32_t src, uint32_t bytes) {
    asm volatile("cp.async.bulk.global.shared::cta.bulk_group [%0], [%1], %2;" ::"l"(dst), "r"(src), "r"(bytes) : "memory");
}
__device__ __forceinline__ void bulk_load(uint32_t dst, const void* src, uint32_t bytes, uint32_t bar) {
    asm volatile("cp.async.bulk.shared::cluster.global.mbarrier::complete_tx::bytes [%0], [%1], %2, [%3];"
                 ::"r"(dst), "l"(src), "r"(bytes), "r"(bar) : "memory");
}
__device__ __forceinline__ unsigned atom_exch(unsigned* p, unsigned v) {
    unsigned r;
    asm volatile("atom.relaxed.gpu.global.exch.b32 %0, [%1], %2;" : "=r"(r) : "l"(p), "r"(v) : "memory");
    return r;
}
__device__ __forceinline__ uint32_t lds32_cluster(uint32_t a) {
    uint32_t v;
    asm volatile("ld.shared::cluster.u32 %0, [%1];" : "=r"(v) : "r"(a) : "memory");
    return v;
}
__device__ __forceinline__ void sts128f(uint32_t a, float x, float y, float z, float w) {
    asm volatile("st.shared.v4.f32 [%0], {%1, %2, %3, %4};" ::"r"(a), "f"(x), "f"(y), "f"(z), "f"(w) : "memory");
}
__device__ __forceinline__ void prefetch_map(const CUtensorMap* m) {
    asm volatile("prefetch.tensormap [%0];" ::"l"(m) : "memory");
}

__device__ __forceinline__ void prefetch_l2(const void* p, uint32_t bytes) {
    asm volatile("cp.async.bulk.prefetch.L2.global [%0], %1;" ::"l"(p), "r"(bytes) : "memory");
}

__device__ __forceinline__ void wgmma_fence() { asm volatile("wgmma.fence.sync.aligned;" ::: "memory"); }
__device__ __forceinline__ void wgmma_commit() { asm volatile("wgmma.commit_group.sync.aligned;" ::: "memory"); }
template <int N>
__device__ __forceinline__ void wgmma_wait() { asm volatile("wgmma.wait_group.sync.aligned %0;" ::"n"(N) : "memory"); }

__device__ __forceinline__ uint32_t pack_bf16(float lo, float hi) {
    uint32_t r;
    asm("cvt.rn.bf16x2.f32 %0, %1, %2;" : "=r"(r) : "f"(hi), "f"(lo));
    return r;
}
__device__ __forceinline__ uint32_t pack_bf16_v(float lo, float hi) {
    uint32_t r;
    asm volatile("cvt.rn.bf16x2.f32 %0, %1, %2;" : "=r"(r) : "f"(hi), "f"(lo));
    return r;
}
__device__ __forceinline__ float bf_lo(uint32_t v) { return __uint_as_float(v << 16); }
__device__ __forceinline__ float bf_hi(uint32_t v) { return __uint_as_float(v & 0xffff0000u); }
__device__ __forceinline__ float bf16_round(float v) { return __bfloat162float(__float2bfloat16_rn(v)); }
__device__ __forceinline__ uint32_t bf2_mul(uint32_t a, uint32_t b) {
    uint32_t r;
    asm("mul.rn.bf16x2 %0, %1, %2;" : "=r"(r) : "r"(a), "r"(b));
    return r;
}
__device__ __forceinline__ uint32_t bf2_add_relu(uint32_t a, uint32_t b) {
    uint32_t r;
    asm("fma.rn.relu.bf16x2 %0, %1, %2, %3;" : "=r"(r) : "r"(a), "r"(0x3f803f80u), "r"(b));
    return r;
}
__device__ __forceinline__ uint4 ldg128(const void* p) {
    uint4 v;
    asm volatile("ld.global.nc.v4.u32 {%0, %1, %2, %3}, [%4];" : "=r"(v.x), "=r"(v.y), "=r"(v.z), "=r"(v.w) : "l"(p));
    return v;
}
__device__ __forceinline__ uint32_t ldg32(const void* p) {
    uint32_t v;
    asm volatile("ld.global.nc.u32 %0, [%1];" : "=r"(v) : "l"(p));
    return v;
}
__device__ __forceinline__ uint32_t ldg16(const __nv_bfloat16* p) {
    uint32_t v;
    asm volatile("ld.global.nc.u16 %0, [%1];" : "=r"(v) : "l"(p));
    return v;
}
__device__ __forceinline__ uint4 ld_relaxed128(const void* p) {
    uint4 v;
    asm volatile("ld.relaxed.gpu.global.v4.u32 {%0, %1, %2, %3}, [%4];" : "=r"(v.x), "=r"(v.y), "=r"(v.z), "=r"(v.w) : "l"(p) : "memory");
    return v;
}
__device__ __forceinline__ uint2 ld_relaxed64(const void* p) {
    unsigned long long v;
    asm volatile("ld.relaxed.gpu.global.u64 %0, [%1];" : "=l"(v) : "l"(p) : "memory");
    return make_uint2((uint32_t)v, (uint32_t)(v >> 32));
}
__device__ __forceinline__ void st_relaxed64(void* p, uint32_t lo, uint32_t hi) {
    unsigned long long v = ((unsigned long long)hi << 32) | lo;
    asm volatile("st.relaxed.gpu.global.u64 [%0], %1;" ::"l"(p), "l"(v) : "memory");
}
__device__ __forceinline__ void st_relaxed2x64(void* p, uint32_t a, uint32_t b, uint32_t c, uint32_t d) {
    unsigned long long v0 = ((unsigned long long)b << 32) | a, v1 = ((unsigned long long)d << 32) | c;
    asm volatile("st.relaxed.gpu.global.v2.u64 [%0], {%1, %2};" ::"l"(p), "l"(v0), "l"(v1) : "memory");
}
__device__ __forceinline__ uint4 ld_relaxed2x64(const void* p) {
    unsigned long long v0, v1;
    asm volatile("ld.relaxed.gpu.global.v2.u64 {%0, %1}, [%2];" : "=l"(v0), "=l"(v1) : "l"(p) : "memory");
    return make_uint4((uint32_t)v0, (uint32_t)(v0 >> 32), (uint32_t)v1, (uint32_t)(v1 >> 32));
}
__device__ __forceinline__ void stg128(void* p, uint32_t a, uint32_t b, uint32_t c, uint32_t d) {
    asm volatile("st.global.v4.u32 [%0], {%1, %2, %3, %4};" ::"l"(p), "r"(a), "r"(b), "r"(c), "r"(d) : "memory");
}
__device__ __forceinline__ void stg64f(void* p, float a, float b) {
    asm volatile("st.global.v2.f32 [%0], {%1, %2};" ::"l"(p), "f"(a), "f"(b) : "memory");
}
__device__ __forceinline__ uint4 lds128(uint32_t a) {
    uint4 v;
    asm volatile("ld.shared.v4.u32 {%0, %1, %2, %3}, [%4];" : "=r"(v.x), "=r"(v.y), "=r"(v.z), "=r"(v.w) : "r"(a) : "memory");
    return v;
}
__device__ __forceinline__ float lds32f(uint32_t a) {
    float v;
    asm volatile("ld.shared.f32 %0, [%1];" : "=f"(v) : "r"(a) : "memory");
    return v;
}
__device__ __forceinline__ void sts128(uint32_t a, uint32_t x, uint32_t y, uint32_t z, uint32_t w) {
    asm volatile("st.shared.v4.u32 [%0], {%1, %2, %3, %4};" ::"r"(a), "r"(x), "r"(y), "r"(z), "r"(w) : "memory");
}
__device__ __forceinline__ void sts32(uint32_t a, uint32_t x) {
    asm volatile("st.shared.u32 [%0], %1;" ::"r"(a), "r"(x) : "memory");
}
__device__ __forceinline__ void stg128f(void* p, float a, float b, float c, float d) {
    asm volatile("st.global.v4.f32 [%0], {%1, %2, %3, %4};" ::"l"(p), "f"(a), "f"(b), "f"(c), "f"(d) : "memory");
}
__device__ __forceinline__ unsigned ld_relaxed32(const unsigned* p) {
    unsigned v;
    asm volatile("ld.relaxed.gpu.global.u32 %0, [%1];" : "=r"(v) : "l"(p) : "memory");
    return v;
}
__device__ __forceinline__ void wait_counter(const unsigned* p, unsigned target) {
    unsigned n = 0, v;
    while (true) {
        asm volatile("ld.acquire.gpu.global.u32 %0, [%1];" : "=r"(v) : "l"(p) : "memory");
        if ((int)(v - target) >= 0) break;
        if (++n > kSpinLimit) TRAP();
        __nanosleep(32);
    }
}
#define KT(IT, W) do { } while (0)
#define STAMP(cond, slot) do { } while (0)

template <int TA, int TB>
__device__ __forceinline__ void wgmma_n256(float (&d)[128], uint64_t da, uint64_t db) {
    asm volatile(
        "{\n.reg .pred p;\nsetp.ne.b32 p, 1, 0;\n"
        "wgmma.mma_async.sync.aligned.m64n256k16.f32.bf16.bf16 "
        "{%0, %1, %2, %3, %4, %5, %6, %7, %8, %9, %10, %11, %12, %13, %14, %15, "
        "%16, %17, %18, %19, %20, %21, %22, %23, %24, %25, %26, %27, %28, %29, %30, %31, "
        "%32, %33, %34, %35, %36, %37, %38, %39, %40, %41, %42, %43, %44, %45, %46, %47, "
        "%48, %49, %50, %51, %52, %53, %54, %55, %56, %57, %58, %59, %60, %61, %62, %63, "
        "%64, %65, %66, %67, %68, %69, %70, %71, %72, %73, %74, %75, %76, %77, %78, %79, "
        "%80, %81, %82, %83, %84, %85, %86, %87, %88, %89, %90, %91, %92, %93, %94, %95, "
        "%96, %97, %98, %99, %100, %101, %102, %103, %104, %105, %106, %107, %108, %109, %110, %111, "
        "%112, %113, %114, %115, %116, %117, %118, %119, %120, %121, %122, %123, %124, %125, %126, %127}, "
        "%128, %129, p, 1, 1, %130, %131;\n}\n"
        : "+f"(d[0]), "+f"(d[1]), "+f"(d[2]), "+f"(d[3]), "+f"(d[4]), "+f"(d[5]), "+f"(d[6]), "+f"(d[7]),
          "+f"(d[8]), "+f"(d[9]), "+f"(d[10]), "+f"(d[11]), "+f"(d[12]), "+f"(d[13]), "+f"(d[14]), "+f"(d[15]),
          "+f"(d[16]), "+f"(d[17]), "+f"(d[18]), "+f"(d[19]), "+f"(d[20]), "+f"(d[21]), "+f"(d[22]), "+f"(d[23]),
          "+f"(d[24]), "+f"(d[25]), "+f"(d[26]), "+f"(d[27]), "+f"(d[28]), "+f"(d[29]), "+f"(d[30]), "+f"(d[31]),
          "+f"(d[32]), "+f"(d[33]), "+f"(d[34]), "+f"(d[35]), "+f"(d[36]), "+f"(d[37]), "+f"(d[38]), "+f"(d[39]),
          "+f"(d[40]), "+f"(d[41]), "+f"(d[42]), "+f"(d[43]), "+f"(d[44]), "+f"(d[45]), "+f"(d[46]), "+f"(d[47]),
          "+f"(d[48]), "+f"(d[49]), "+f"(d[50]), "+f"(d[51]), "+f"(d[52]), "+f"(d[53]), "+f"(d[54]), "+f"(d[55]),
          "+f"(d[56]), "+f"(d[57]), "+f"(d[58]), "+f"(d[59]), "+f"(d[60]), "+f"(d[61]), "+f"(d[62]), "+f"(d[63]),
          "+f"(d[64]), "+f"(d[65]), "+f"(d[66]), "+f"(d[67]), "+f"(d[68]), "+f"(d[69]), "+f"(d[70]), "+f"(d[71]),
          "+f"(d[72]), "+f"(d[73]), "+f"(d[74]), "+f"(d[75]), "+f"(d[76]), "+f"(d[77]), "+f"(d[78]), "+f"(d[79]),
          "+f"(d[80]), "+f"(d[81]), "+f"(d[82]), "+f"(d[83]), "+f"(d[84]), "+f"(d[85]), "+f"(d[86]), "+f"(d[87]),
          "+f"(d[88]), "+f"(d[89]), "+f"(d[90]), "+f"(d[91]), "+f"(d[92]), "+f"(d[93]), "+f"(d[94]), "+f"(d[95]),
          "+f"(d[96]), "+f"(d[97]), "+f"(d[98]), "+f"(d[99]), "+f"(d[100]), "+f"(d[101]), "+f"(d[102]), "+f"(d[103]),
          "+f"(d[104]), "+f"(d[105]), "+f"(d[106]), "+f"(d[107]), "+f"(d[108]), "+f"(d[109]), "+f"(d[110]), "+f"(d[111]),
          "+f"(d[112]), "+f"(d[113]), "+f"(d[114]), "+f"(d[115]), "+f"(d[116]), "+f"(d[117]), "+f"(d[118]), "+f"(d[119]),
          "+f"(d[120]), "+f"(d[121]), "+f"(d[122]), "+f"(d[123]), "+f"(d[124]), "+f"(d[125]), "+f"(d[126]), "+f"(d[127])
        : "l"(da), "l"(db), "n"(TA), "n"(TB));
}
template <int TA, int TB>
__device__ __forceinline__ void wgmma_n256_first(float (&d)[128], uint64_t da, uint64_t db) {
    asm volatile(
        "{\n.reg .pred p;\nsetp.ne.b32 p, 0, 0;\n"
        "wgmma.mma_async.sync.aligned.m64n256k16.f32.bf16.bf16 "
        "{%0, %1, %2, %3, %4, %5, %6, %7, %8, %9, %10, %11, %12, %13, %14, %15, "
        "%16, %17, %18, %19, %20, %21, %22, %23, %24, %25, %26, %27, %28, %29, %30, %31, "
        "%32, %33, %34, %35, %36, %37, %38, %39, %40, %41, %42, %43, %44, %45, %46, %47, "
        "%48, %49, %50, %51, %52, %53, %54, %55, %56, %57, %58, %59, %60, %61, %62, %63, "
        "%64, %65, %66, %67, %68, %69, %70, %71, %72, %73, %74, %75, %76, %77, %78, %79, "
        "%80, %81, %82, %83, %84, %85, %86, %87, %88, %89, %90, %91, %92, %93, %94, %95, "
        "%96, %97, %98, %99, %100, %101, %102, %103, %104, %105, %106, %107, %108, %109, %110, %111, "
        "%112, %113, %114, %115, %116, %117, %118, %119, %120, %121, %122, %123, %124, %125, %126, %127}, "
        "%128, %129, p, 1, 1, %130, %131;\n}\n"
        : "=f"(d[0]), "=f"(d[1]), "=f"(d[2]), "=f"(d[3]), "=f"(d[4]), "=f"(d[5]), "=f"(d[6]), "=f"(d[7]),
          "=f"(d[8]), "=f"(d[9]), "=f"(d[10]), "=f"(d[11]), "=f"(d[12]), "=f"(d[13]), "=f"(d[14]), "=f"(d[15]),
          "=f"(d[16]), "=f"(d[17]), "=f"(d[18]), "=f"(d[19]), "=f"(d[20]), "=f"(d[21]), "=f"(d[22]), "=f"(d[23]),
          "=f"(d[24]), "=f"(d[25]), "=f"(d[26]), "=f"(d[27]), "=f"(d[28]), "=f"(d[29]), "=f"(d[30]), "=f"(d[31]),
          "=f"(d[32]), "=f"(d[33]), "=f"(d[34]), "=f"(d[35]), "=f"(d[36]), "=f"(d[37]), "=f"(d[38]), "=f"(d[39]),
          "=f"(d[40]), "=f"(d[41]), "=f"(d[42]), "=f"(d[43]), "=f"(d[44]), "=f"(d[45]), "=f"(d[46]), "=f"(d[47]),
          "=f"(d[48]), "=f"(d[49]), "=f"(d[50]), "=f"(d[51]), "=f"(d[52]), "=f"(d[53]), "=f"(d[54]), "=f"(d[55]),
          "=f"(d[56]), "=f"(d[57]), "=f"(d[58]), "=f"(d[59]), "=f"(d[60]), "=f"(d[61]), "=f"(d[62]), "=f"(d[63]),
          "=f"(d[64]), "=f"(d[65]), "=f"(d[66]), "=f"(d[67]), "=f"(d[68]), "=f"(d[69]), "=f"(d[70]), "=f"(d[71]),
          "=f"(d[72]), "=f"(d[73]), "=f"(d[74]), "=f"(d[75]), "=f"(d[76]), "=f"(d[77]), "=f"(d[78]), "=f"(d[79]),
          "=f"(d[80]), "=f"(d[81]), "=f"(d[82]), "=f"(d[83]), "=f"(d[84]), "=f"(d[85]), "=f"(d[86]), "=f"(d[87]),
          "=f"(d[88]), "=f"(d[89]), "=f"(d[90]), "=f"(d[91]), "=f"(d[92]), "=f"(d[93]), "=f"(d[94]), "=f"(d[95]),
          "=f"(d[96]), "=f"(d[97]), "=f"(d[98]), "=f"(d[99]), "=f"(d[100]), "=f"(d[101]), "=f"(d[102]), "=f"(d[103]),
          "=f"(d[104]), "=f"(d[105]), "=f"(d[106]), "=f"(d[107]), "=f"(d[108]), "=f"(d[109]), "=f"(d[110]), "=f"(d[111]),
          "=f"(d[112]), "=f"(d[113]), "=f"(d[114]), "=f"(d[115]), "=f"(d[116]), "=f"(d[117]), "=f"(d[118]), "=f"(d[119]),
          "=f"(d[120]), "=f"(d[121]), "=f"(d[122]), "=f"(d[123]), "=f"(d[124]), "=f"(d[125]), "=f"(d[126]), "=f"(d[127])
        : "l"(da), "l"(db), "n"(TA), "n"(TB));
}
template <int TA, int TB>
__device__ __forceinline__ void wgmma_n192(float (&d)[128], uint64_t da, uint64_t db) {
    asm volatile(
        "{\n.reg .pred p;\nsetp.ne.b32 p, 1, 0;\n"
        "wgmma.mma_async.sync.aligned.m64n192k16.f32.bf16.bf16 "
        "{%0, %1, %2, %3, %4, %5, %6, %7, %8, %9, %10, %11, %12, %13, %14, %15, "
        "%16, %17, %18, %19, %20, %21, %22, %23, %24, %25, %26, %27, %28, %29, %30, %31, "
        "%32, %33, %34, %35, %36, %37, %38, %39, %40, %41, %42, %43, %44, %45, %46, %47, "
        "%48, %49, %50, %51, %52, %53, %54, %55, %56, %57, %58, %59, %60, %61, %62, %63, "
        "%64, %65, %66, %67, %68, %69, %70, %71, %72, %73, %74, %75, %76, %77, %78, %79, "
        "%80, %81, %82, %83, %84, %85, %86, %87, %88, %89, %90, %91, %92, %93, %94, %95}, "
        "%96, %97, p, 1, 1, %98, %99;\n}\n"
        : "+f"(d[0]), "+f"(d[1]), "+f"(d[2]), "+f"(d[3]), "+f"(d[4]), "+f"(d[5]), "+f"(d[6]), "+f"(d[7]),
          "+f"(d[8]), "+f"(d[9]), "+f"(d[10]), "+f"(d[11]), "+f"(d[12]), "+f"(d[13]), "+f"(d[14]), "+f"(d[15]),
          "+f"(d[16]), "+f"(d[17]), "+f"(d[18]), "+f"(d[19]), "+f"(d[20]), "+f"(d[21]), "+f"(d[22]), "+f"(d[23]),
          "+f"(d[24]), "+f"(d[25]), "+f"(d[26]), "+f"(d[27]), "+f"(d[28]), "+f"(d[29]), "+f"(d[30]), "+f"(d[31]),
          "+f"(d[32]), "+f"(d[33]), "+f"(d[34]), "+f"(d[35]), "+f"(d[36]), "+f"(d[37]), "+f"(d[38]), "+f"(d[39]),
          "+f"(d[40]), "+f"(d[41]), "+f"(d[42]), "+f"(d[43]), "+f"(d[44]), "+f"(d[45]), "+f"(d[46]), "+f"(d[47]),
          "+f"(d[48]), "+f"(d[49]), "+f"(d[50]), "+f"(d[51]), "+f"(d[52]), "+f"(d[53]), "+f"(d[54]), "+f"(d[55]),
          "+f"(d[56]), "+f"(d[57]), "+f"(d[58]), "+f"(d[59]), "+f"(d[60]), "+f"(d[61]), "+f"(d[62]), "+f"(d[63]),
          "+f"(d[64]), "+f"(d[65]), "+f"(d[66]), "+f"(d[67]), "+f"(d[68]), "+f"(d[69]), "+f"(d[70]), "+f"(d[71]),
          "+f"(d[72]), "+f"(d[73]), "+f"(d[74]), "+f"(d[75]), "+f"(d[76]), "+f"(d[77]), "+f"(d[78]), "+f"(d[79]),
          "+f"(d[80]), "+f"(d[81]), "+f"(d[82]), "+f"(d[83]), "+f"(d[84]), "+f"(d[85]), "+f"(d[86]), "+f"(d[87]),
          "+f"(d[88]), "+f"(d[89]), "+f"(d[90]), "+f"(d[91]), "+f"(d[92]), "+f"(d[93]), "+f"(d[94]), "+f"(d[95])
        : "l"(da), "l"(db), "n"(TA), "n"(TB));
}
template <int TA, int TB>
__device__ __forceinline__ void wgmma_n192_first(float (&d)[128], uint64_t da, uint64_t db) {
    asm volatile(
        "{\n.reg .pred p;\nsetp.ne.b32 p, 0, 0;\n"
        "wgmma.mma_async.sync.aligned.m64n192k16.f32.bf16.bf16 "
        "{%0, %1, %2, %3, %4, %5, %6, %7, %8, %9, %10, %11, %12, %13, %14, %15, "
        "%16, %17, %18, %19, %20, %21, %22, %23, %24, %25, %26, %27, %28, %29, %30, %31, "
        "%32, %33, %34, %35, %36, %37, %38, %39, %40, %41, %42, %43, %44, %45, %46, %47, "
        "%48, %49, %50, %51, %52, %53, %54, %55, %56, %57, %58, %59, %60, %61, %62, %63, "
        "%64, %65, %66, %67, %68, %69, %70, %71, %72, %73, %74, %75, %76, %77, %78, %79, "
        "%80, %81, %82, %83, %84, %85, %86, %87, %88, %89, %90, %91, %92, %93, %94, %95}, "
        "%96, %97, p, 1, 1, %98, %99;\n}\n"
        : "=f"(d[0]), "=f"(d[1]), "=f"(d[2]), "=f"(d[3]), "=f"(d[4]), "=f"(d[5]), "=f"(d[6]), "=f"(d[7]),
          "=f"(d[8]), "=f"(d[9]), "=f"(d[10]), "=f"(d[11]), "=f"(d[12]), "=f"(d[13]), "=f"(d[14]), "=f"(d[15]),
          "=f"(d[16]), "=f"(d[17]), "=f"(d[18]), "=f"(d[19]), "=f"(d[20]), "=f"(d[21]), "=f"(d[22]), "=f"(d[23]),
          "=f"(d[24]), "=f"(d[25]), "=f"(d[26]), "=f"(d[27]), "=f"(d[28]), "=f"(d[29]), "=f"(d[30]), "=f"(d[31]),
          "=f"(d[32]), "=f"(d[33]), "=f"(d[34]), "=f"(d[35]), "=f"(d[36]), "=f"(d[37]), "=f"(d[38]), "=f"(d[39]),
          "=f"(d[40]), "=f"(d[41]), "=f"(d[42]), "=f"(d[43]), "=f"(d[44]), "=f"(d[45]), "=f"(d[46]), "=f"(d[47]),
          "=f"(d[48]), "=f"(d[49]), "=f"(d[50]), "=f"(d[51]), "=f"(d[52]), "=f"(d[53]), "=f"(d[54]), "=f"(d[55]),
          "=f"(d[56]), "=f"(d[57]), "=f"(d[58]), "=f"(d[59]), "=f"(d[60]), "=f"(d[61]), "=f"(d[62]), "=f"(d[63]),
          "=f"(d[64]), "=f"(d[65]), "=f"(d[66]), "=f"(d[67]), "=f"(d[68]), "=f"(d[69]), "=f"(d[70]), "=f"(d[71]),
          "=f"(d[72]), "=f"(d[73]), "=f"(d[74]), "=f"(d[75]), "=f"(d[76]), "=f"(d[77]), "=f"(d[78]), "=f"(d[79]),
          "=f"(d[80]), "=f"(d[81]), "=f"(d[82]), "=f"(d[83]), "=f"(d[84]), "=f"(d[85]), "=f"(d[86]), "=f"(d[87]),
          "=f"(d[88]), "=f"(d[89]), "=f"(d[90]), "=f"(d[91]), "=f"(d[92]), "=f"(d[93]), "=f"(d[94]), "=f"(d[95])
        : "l"(da), "l"(db), "n"(TA), "n"(TB));
}
template <int TA, int TB>
__device__ __forceinline__ void wgmma_n128(float (&d)[128], uint64_t da, uint64_t db) {
    asm volatile(
        "{\n.reg .pred p;\nsetp.ne.b32 p, 1, 0;\n"
        "wgmma.mma_async.sync.aligned.m64n128k16.f32.bf16.bf16 "
        "{%0, %1, %2, %3, %4, %5, %6, %7, %8, %9, %10, %11, %12, %13, %14, %15, "
        "%16, %17, %18, %19, %20, %21, %22, %23, %24, %25, %26, %27, %28, %29, %30, %31, "
        "%32, %33, %34, %35, %36, %37, %38, %39, %40, %41, %42, %43, %44, %45, %46, %47, "
        "%48, %49, %50, %51, %52, %53, %54, %55, %56, %57, %58, %59, %60, %61, %62, %63}, "
        "%64, %65, p, 1, 1, %66, %67;\n}\n"
        : "+f"(d[0]), "+f"(d[1]), "+f"(d[2]), "+f"(d[3]), "+f"(d[4]), "+f"(d[5]), "+f"(d[6]), "+f"(d[7]),
          "+f"(d[8]), "+f"(d[9]), "+f"(d[10]), "+f"(d[11]), "+f"(d[12]), "+f"(d[13]), "+f"(d[14]), "+f"(d[15]),
          "+f"(d[16]), "+f"(d[17]), "+f"(d[18]), "+f"(d[19]), "+f"(d[20]), "+f"(d[21]), "+f"(d[22]), "+f"(d[23]),
          "+f"(d[24]), "+f"(d[25]), "+f"(d[26]), "+f"(d[27]), "+f"(d[28]), "+f"(d[29]), "+f"(d[30]), "+f"(d[31]),
          "+f"(d[32]), "+f"(d[33]), "+f"(d[34]), "+f"(d[35]), "+f"(d[36]), "+f"(d[37]), "+f"(d[38]), "+f"(d[39]),
          "+f"(d[40]), "+f"(d[41]), "+f"(d[42]), "+f"(d[43]), "+f"(d[44]), "+f"(d[45]), "+f"(d[46]), "+f"(d[47]),
          "+f"(d[48]), "+f"(d[49]), "+f"(d[50]), "+f"(d[51]), "+f"(d[52]), "+f"(d[53]), "+f"(d[54]), "+f"(d[55]),
          "+f"(d[56]), "+f"(d[57]), "+f"(d[58]), "+f"(d[59]), "+f"(d[60]), "+f"(d[61]), "+f"(d[62]), "+f"(d[63])
        : "l"(da), "l"(db), "n"(TA), "n"(TB));
}

template <int MODE, bool FIRST>
__device__ __forceinline__ void mma_kblock(float (&acc)[128], uint32_t a_lo, uint32_t b_lo) {
    constexpr uint64_t HI = (uint64_t)(64u | 0x40000000u) << 32;
    constexpr uint32_t HALF = (MODE == 1) ? 12288u : 16384u;
    constexpr bool BN = (MODE == 1 || MODE == 2 || MODE == 4);
#pragma unroll
    for (int kk = 0; kk < 4; ++kk) {
        const uint32_t ao = (MODE == 3) ? kk * 2048u : kk * 32u;
        const uint32_t bo = BN ? ((kk >> 1) * HALF + (kk & 1) * 2048u) : kk * 32u;
        const uint64_t da = HI | (uint64_t)(a_lo + (ao >> 4) + (1u << 16));
        const uint64_t db = HI | (uint64_t)(b_lo + (bo >> 4) + (BN ? (256u << 16) : (1u << 16)));
        if (MODE == 1) {
            if (FIRST && kk == 0) wgmma_n192_first<0, 1>(acc, da, db); else wgmma_n192<0, 1>(acc, da, db);
        } else if (MODE == 4) {
            wgmma_n128<0, 1>(acc, da, db);
        } else {
            if (FIRST && kk == 0) wgmma_n256_first<(MODE == 3), BN>(acc, da, db);
            else wgmma_n256<(MODE == 3), BN>(acc, da, db);
        }
    }
}

struct Params {
    const __nv_bfloat16* x;
    const __nv_bfloat16* lam_re;
    const __nv_bfloat16* lam_im;
    const __nv_bfloat16* log_dt;
    const __nv_bfloat16* dskip;
    const __nv_bfloat16* b1;
    const __nv_bfloat16* b2;
    const __nv_bfloat16* gate_w;
    const __nv_bfloat16* w1;
    const __nv_bfloat16* w2;
    const __nv_bfloat16* c_re;
    const __nv_bfloat16* c_im;
    const __nv_bfloat16* b_re;
    const __nv_bfloat16* b_im;
    float* out;
    int swap;
};

#define CMUL(rr, ri, ar, ai, br, bi) do { float _r = (ar) * (br) - (ai) * (bi); float _i = (ar) * (bi) + (ai) * (br); rr = _r; ri = _i; } while (0)
#define CFMA(rr, ri, ar, ai, br, bi) do { float _r = fmaf(-(ai), (bi), fmaf((ar), (br), rr)); float _i = fmaf((ai), (br), fmaf((ar), (bi), ri)); rr = _r; ri = _i; } while (0)

#define KBLOCK_BEGIN(MODE, FIRST, IT)                                                            \
    KT(kt0 + (IT), 0);                                                                           \
    PIN_R(a_lo);                                                                                 \
    mbar_wait(bar_full + 8 * ((IT) & 3), ((IT) >> 2) & 1);                                       \
    KT(kt0 + (IT), 1);                                                                           \
    wgmma_fence();                                                                               \
    mma_kblock<MODE, FIRST>(acc, a_lo + ((IT) & 3) * (kStageBytes >> 4), b_lo + ((IT) & 3) * (kStageBytes >> 4)); \
    wgmma_commit();                                                                              \
    KBLOCK_EARLY(MODE, IT)
#define RELEASE_STAGE(S) do { if (lane < 2) mbar_arrive_cluster(rel_addr + 8 * (S)); } while (0)
#define KBLOCK_EARLY(MODE, IT) if ((MODE) != 4 && (IT) > 0) { wgmma_wait<1>(); RELEASE_STAGE(((IT) - 1) & 3); }
#define KBLOCK_END(IT) KT(kt0 + (IT), 2);

__global__ void __cluster_dims__(2, 1, 1) __launch_bounds__(384, 1)
fused_kernel(const __grid_constant__ CUtensorMap mB, const __grid_constant__ CUtensorMap mXs, const __grid_constant__ CUtensorMap mXf,
             const __grid_constant__ CUtensorMap mW1a, const __grid_constant__ CUtensorMap mW1b, const __grid_constant__ CUtensorMap mHs,
             const __grid_constant__ CUtensorMap mHf, const __grid_constant__ CUtensorMap mCre, const __grid_constant__ CUtensorMap mCim,
             const __grid_constant__ CUtensorMap mW2, const Params p) {
    extern __shared__ __align__(1024) uint8_t smem_raw[];
    const uint32_t sbase = smem_u32(smem_raw);
    if ((sbase & 0x3ffffu) != kSmemOrg) return;
    const uint32_t bar_full = sbase + kBarOff, bar_empty = bar_full + 32, bar_dep = bar_full + 64;
    const uint32_t bar_sent = bar_full + 96, bar_free = bar_full + 128, bar_recv = bar_full + 160, role_s = bar_full + 192;

    const int tid = threadIdx.x, lane = tid & 31;
    const int warp = __shfl_sync(0xffffffffu, tid >> 5, 0);
    const uint32_t rank = blockIdx.x & 1;

    int pref;
    {
        unsigned smid;
        asm("mov.u32 %0, %%smid;" : "=r"(smid));
        const int t = smid >> 1, u = t - 32, d = (u * 37) >> 8;
        pref = (t < 32) ? (t & 7) * 8 + (t >> 3) : (t < 60) ? (1 + u - 7 * d) * 8 + 4 + d : ((t - 58) & 7);
    }
#define FIRST_FILL(ROLE)                                                                     \
    _Pragma("unroll 1") for (int kb = 0; kb < FIRSTN; ++kb) {                                \
        const uint32_t st = sbase + kb * kStageBytes, fb = bar_full + 8 * kb;                \
        mbar_expect_tx(fb, 49152);                                                           \
        tma4(st, &mB, fb, kb * 64, 0, 0, (((ROLE) & 7) * 2 + (int)rank) * 8);                \
        tma5(st + kABytes, &mXs, fb, kb * 64, 0, 0, 0, (ROLE) >> 3);                         \
        tma5(st + kABytes + 16384, &mXs, fb, kb * 64, 0, 0, 16, (ROLE) >> 3);                \
    }
    STAMP(tid == 0, 0);
    if (tid == 0) {
        prefetch_map(&mB); prefetch_map(&mXs);
#pragma unroll
        for (int s = 0; s < kStages; ++s) {
            mbar_init(bar_full + 8 * s, 1);
            mbar_init(bar_empty + 8 * s, 16);
            mbar_init(bar_dep + 8 * s, 1);
            mbar_init(bar_sent + 8 * s, 8);
            mbar_init(bar_free + 8 * s, 1);
            mbar_init(bar_recv + 8 * s, 1);
        }
        asm volatile("fence.mbarrier_init.release.cluster;\nfence.proxy.async.shared::cta;" ::: "memory");
        FIRST_FILL(pref);
        STAMP(true, 12);
    } else if (tid == 32) {
        if (rank == 0) {
            int role = pref;
            unsigned taken = atom_exch(&g_claim[pref], 1u);
#pragma unroll 1
            for (int i = 0; taken != 0 && i < 64; ++i) { role = i; taken = atom_exch(&g_claim[i], 1u); }
            sts32(role_s, role);
            asm volatile("fence.acq_rel.cluster;" ::: "memory");
        }
    }
    else if (tid >= 128 && tid < 128 + 32 * PF0LINES) {
        const int row = blockIdx.x * 32 + lane;
        const __nv_bfloat16* src = (row < 2048) ? p.x + (size_t)row * kD : (row < 3072) ? p.b_re + (size_t)(row - 2048) * kD : p.b_im + (size_t)(row - 3072) * kD;
        asm volatile("prefetch.global.L2 [%0];" ::"l"(src + (warp - 4) * 64) : "memory");
    }
    __syncwarp();
    cluster_arrive();
#define TAKE_ROLE()                                                                          \
    cluster_wait();                                                                          \
    const int role = __shfl_sync(0xffffffffu, (int)lds32_cluster(mapa(role_s, 0)), 0);       \
    if (role != pref) {                                                                      \
        if (tid == 0) {                                                                      \
            _Pragma("unroll 1") for (int kb = 0; kb < FIRSTN; ++kb) {                        \
                mbar_wait(bar_full + 8 * kb, 0);                                             \
                asm volatile("mbarrier.inval.shared::cta.b64 [%0];" ::"r"(bar_full + 8 * kb) : "memory"); \
                mbar_init(bar_full + 8 * kb, 1);                                             \
            }                                                                                \
            asm volatile("fence.mbarrier_init.release.cluster;\nfence.proxy.async.shared::cta;" ::: "memory"); \
            FIRST_FILL(role);                                                                \
        }                                                                                    \
        __syncwarp();                                                                        \
        bar_sync<0, 384>();                                                                  \
    }                                                                                        \
    const int c = role >> 3;                                         \
    const int j8 = role & 7;                                    \
    const int cb = j8 * 2 + (int)rank;                         \
    const int rb = 2 * c + (int)rank;                           \
    const int kh = j8 >> 2;                \
    const int colK = (j8 & 3) * 256 + kh * 128, colS = colK ^ 128;    \
    (void)cb; (void)rb; (void)colS;

    if (warp >= 8) {
        asm volatile("setmaxnreg.dec.sync.aligned.u32 24;");
        TAKE_ROLE();
        if (warp == 8) {
            if (lane == 0) {
                int it = FIRSTN;
#define ACQUIRE(BYTES)                                                   \
    const uint32_t st = sbase + (it & 3) * kStageBytes, fb = bar_full + 8 * (it & 3); \
    mbar_wait(bar_empty + 8 * (it & 3), ((it >> 2) & 1) ^ 1);            \
    mbar_expect_tx(fb, BYTES);
                prefetch_map(&mXf); prefetch_map(&mW1b); prefetch_map(&mW1a);
#pragma unroll 1
                for (int kb = FIRSTN; kb < 16; ++kb, ++it) {
                    ACQUIRE(49152);
                    tma4(st, &mB, fb, kb * 64, 0, 0, cb * 8);
                    tma5_mc(st + kABytes + rank * 16384, &mXs, fb, kb * 64, 0, 0, rank * 16, c);
                    if (kb >= 4 && kb < 12) prefetch_l2(p.w1 + (size_t)(blockIdx.x * 8 + (kb - 4)) * kF, kF * 2);
                }
#pragma unroll 1
                for (int kb = 0; kb < 16; ++kb, ++it) {
                    ACQUIRE(40960);
                    tma5(st, &mXf, fb, kb * 64, 0, 0, rank * 4, c);
                    tma3_mc(st + kABytes + rank * 12288, &mW1b, fb, 0, kb * 64 + rank * 32, 32 + 3 * j8);
                    if (kb < 8) prefetch_l2(((kb & 1) ? p.c_im : p.c_re) + (size_t)(blockIdx.x * 4 + (kb >> 1)) * 2048, 4096);
                }
                const CUtensorMap* mC = kh ? &mCim : &mCre;
                prefetch_map(&mHs); prefetch_map(&mHf); prefetch_map(mC); prefetch_map(&mW2);
#pragma unroll 1
                for (int kb = 0; kb < 16; ++kb, ++it) {
                    ACQUIRE(49152);
                    tma5(st, &mXf, fb, kb * 64, 0, 0, rank * 4, c);
                    tma3_mc(st + kABytes + rank * 16384, &mW1a, fb, 0, kb * 64 + rank * 32, 4 * j8);
                    if (kb < 14) prefetch_l2(p.w2 + (size_t)(blockIdx.x * 14 + kb) * 2048, 4096);
                }
                STAMP(true, 8);
                mbar_wait(bar_dep, 0);
                asm volatile("fence.proxy.async.global;" ::: "memory");
                STAMP(true, 9);
#pragma unroll 1
                for (int kb = 0; kb < 16; ++kb, ++it) {
                    ACQUIRE(49152);
                    tma3(st, &mHs, fb, 0, kh * 1024 + kb * 64, rb * 2);
                    tma2_mc(st + kABytes + rank * 16384, mC, fb, kb * 64, rank ? colS : colK);
                }
                mbar_wait(bar_dep + 8, 0);
                asm volatile("fence.proxy.async.global;" ::: "memory");
                STAMP(true, 10);
#pragma unroll 1
                for (int kb = 0; kb < kNF + kTail; ++kb, ++it) {
                    if (kb == 12) {
                        mbar_wait(bar_dep + 16, 0);
                        asm volatile("fence.proxy.async.global;" ::: "memory");
                        STAMP(true, 11);
                    }
                    const int f0 = (kb < 12) ? 2048 + 768 * kh + 64 * kb : (kb < kNF ? 64 * (kNA * kh + kb - 12) : 64 * (kNA + kb - 12));
                    ACQUIRE(kb < kNF ? 49152 : 32768);
                    tma2(st, &mHf, fb, f0, rb * 128);
                    tma5_mc(st + kABytes + rank * 16384, &mW2, fb, 0, 0, (f0 >> 3) + 4 * rank, 0, colK >> 6);
                    if (kb < kNF) tma5_mc(st + kABytes + rank * 16384 + 8192, &mW2, fb, 0, 0, (f0 >> 3) + 4 * rank, 0, colS >> 6);
                }
            }
        } else if (warp == 9) {
            const unsigned tag = ld_relaxed32(&g_epoch) + 1;
#pragma unroll
            for (int ev = 0; ev < 3; ++ev) {
                if (ev == 0) bar_sync<3, 288>(); else if (ev == 1) bar_sync<4, 288>(); else bar_sync<5, 288>();
                if (lane == 0) {
                    unsigned* cnt = &g_cnt[(ev == 0 ? c : (ev == 1 ? 8 : 24) + rb) * 32];
                    asm volatile("fence.acq_rel.gpu;\nfence.proxy.async.global;" ::: "memory");
                    asm volatile("red.relaxed.gpu.global.add.u32 [%0], 1;" ::"l"(cnt) : "memory");
                }
            }
            if (lane == 0) {
                float* dst = g_X + (size_t)(role * 2 + rank) * 16384;
                unsigned* flag = &g_xflag[(role * 2 + rank) * 32];
#pragma unroll 1
                for (int j = 0; j < 5; ++j) {
                    if (j < 4) {
                        const uint32_t src = sbase + ((64 + kNF + j) & 3) * kStageBytes + kABytes + 8192;
                        mbar_wait(bar_sent + 8 * j, 0);
                        bulk_store(dst + j * 4096, src, 8192);
                        bulk_store(dst + j * 4096 + 2048, src + 16384, 8192);
                        asm volatile("cp.async.bulk.commit_group;" ::: "memory");
                        if (j == 0) continue;
                        asm volatile("cp.async.bulk.wait_group 1;" ::: "memory");
                    } else {
                        asm volatile("cp.async.bulk.wait_group 0;" ::: "memory");
                    }
                    asm volatile("st.release.gpu.global.u32 [%0], %1;" ::"l"(flag), "r"(tag * 4u + j - 4u) : "memory");
                    mbar_arrive_local(bar_free + 8 * (j - 1));
                }
                STAMP(true, 13);
            }
        } else if (warp == 10) {
            if (lane == 0) {
                const unsigned tag = ld_relaxed32(&g_epoch) + 1;
                wait_counter(&g_cnt[c * 32], tag * 16u);
                mbar_arrive_local(bar_dep);
                if (atomicInc(&g_done, 127u) == 127u) {
                    asm volatile("st.relaxed.gpu.global.u32 [%0], %1;" ::"l"(&g_epoch), "r"(tag) : "memory");
#pragma unroll 1
                    for (int i = 0; i < 64; i += 4) stg128(&g_claim[i], 0, 0, 0, 0);
                }
                wait_counter(&g_cnt[(8 + rb) * 32], tag * 8u);
                mbar_arrive_local(bar_dep + 8);
                wait_counter(&g_cnt[(24 + rb) * 32], tag * 8u);
                mbar_arrive_local(bar_dep + 16);
                const float* src = g_X + (size_t)((role ^ 4) * 2 + rank) * 16384;
                const unsigned* flag = &g_xflag[((role ^ 4) * 2 + rank) * 32];
#pragma unroll 1
                for (int j = 0; j < 4; ++j) {
                    const uint32_t dst = sbase + ((64 + kNF + j) & 3) * kStageBytes + kABytes + 8192;
                    mbar_wait(bar_free + 8 * j, 0);
                    wait_counter(flag, tag * 4u + j - 3u);
                    asm volatile("fence.proxy.async.global;" ::: "memory");
                    mbar_expect_tx(bar_recv + 8 * j, 16384);
                    bulk_load(dst, src + j * 4096, 8192, bar_recv + 8 * j);
                    bulk_load(dst + 16384, src + j * 4096 + 2048, 8192, bar_recv + 8 * j);
                }
                STAMP(true, 14);
            }
        }
    } else {
        asm volatile("setmaxnreg.inc.sync.aligned.u32 240;");
        TAKE_ROLE();
        const int wg = warp >> 2, w = warp & 3, r = lane >> 2, q = lane & 3, tw = tid & 127;
        uint32_t a_lo = (kSmemOrg + wg * 8192) >> 4;
        constexpr uint32_t b_lo = (kSmemOrg + kABytes) >> 4;
        const uint32_t rel_addr = mapa(bar_empty, (uint32_t)(lane & 1));
        const uint32_t gate_s = sbase + kGateOff + wg * kGateBytesWG, bias_s = sbase + kBiasOff + wg * kBiasBytesWG;
        float acc[128];
        int kt0 = 0; (void)kt0;
        uint32_t pk[64];
        unsigned tag = ld_relaxed32(&g_epoch);

        const int ch = cb * 64 + warp * 8 + r;
        float lr, li, m00, m01, m10, m11;
        {
            uint4 gx[8], gw[4];
            const int grow = c * 256 + cb * 16 + warp * 2;
            uint32_t Lr_ = ldg16(p.lam_re + ch), Li_ = ldg16(p.lam_im + ch), Ldt_ = ldg16(p.log_dt + ch);
            uint32_t bz[4] = {0, 0, 0, 0};
            if (tw < 88) {
                const int J = tw >> 2;
                const __nv_bfloat16* src = (J < 6) ? p.b1 + 2048 + 192 * j8 + 32 * J
                                         : (J < 14) ? p.b1 + 256 * j8 + 32 * (J - 6)
                                         : (J < 18) ? p.dskip + colK + 32 * (J - 14) : p.b2 + colK + 32 * (J - 18);
#pragma unroll
                for (int jj = 0; jj < 4; ++jj) bz[jj] = ldg32(src + 8 * jj + 2 * (tw & 3));
            }
            uint2 gv0, gv1;
#pragma unroll
            for (int kb = 0; kb < 16; ++kb) {
                if (kb == 0) { KBLOCK_BEGIN(0, true, kb); STAMP(tid == 0, 1); } else { KBLOCK_BEGIN(0, false, kb); }
                if (kb == GATE_LD) {
#pragma unroll
                    for (int i = 0; i < 4; ++i) gw[i] = ldg128(p.gate_w + i * 256 + lane * 8);
#pragma unroll
                    for (int i = 0; i < 8; ++i) gx[i] = ldg128(p.x + (size_t)(grow + (i >> 2)) * kD + (i & 3) * 256 + lane * 8);
                }
                if (kb == GATE_LD + 3) {
                    float s0 = 0.f, s1 = 0.f;
#pragma unroll
                    for (int i = 0; i < 4; ++i) {
                        PIN_R(gw[i].x);
                        const uint32_t wv[4] = {gw[i].x, gw[i].y, gw[i].z, gw[i].w};
                        const uint32_t xa[4] = {gx[i].x, gx[i].y, gx[i].z, gx[i].w};
                        const uint32_t xb[4] = {gx[4 + i].x, gx[4 + i].y, gx[4 + i].z, gx[4 + i].w};
#pragma unroll
                        for (int k = 0; k < 4; ++k) {
                            const uint32_t pa = bf2_mul(xa[k], wv[k]), pb = bf2_mul(xb[k], wv[k]);
                            s0 += bf_lo(pa) + bf_hi(pa);
                            s1 += bf_lo(pb) + bf_hi(pb);
                        }
                    }
#pragma unroll
                    for (int o = 16; o > 0; o >>= 1) {
                        s0 += __shfl_xor_sync(0xffffffffu, s0, o);
                        s1 += __shfl_xor_sync(0xffffffffu, s1, o);
                    }
                    if (lane < 2) {
                        const float z = bf16_round(lane ? s1 : s0);
                        const float g = bf16_round(1.0f / (1.0f + expf(-z)));
                        st_relaxed64(&g_gate[grow + lane], __float_as_uint(g), tag);
                    }
                }
                if (kb == 1) {
                    PIN_R(Lr_); PIN_R(Li_); PIN_R(Ldt_);
                    const float Lr = bf_lo(Lr_), Li = bf_lo(Li_), Ldt = bf_lo(Ldt_);
                    const float dt = bf16_round(expf(Ldt));
                    const float ea = expf(dt * Lr);
                    float sn, cs;
                    sincospif((dt * Li) * 0.31830988618379067f, &sn, &cs);
                    lr = ea * cs; li = ea * sn;
                    const float nr = lr - 1.0f, ni = li;
                    float cr, ci;
                    if (fabsf(Lr) >= fabsf(Li)) {
                        const float t = Li / Lr, d = 1.0f / fmaf(Li, t, Lr);
                        cr = fmaf(ni, t, nr) * d; ci = fmaf(-nr, t, ni) * d;
                    } else {
                        const float t = Lr / Li, d = 1.0f / fmaf(Lr, t, Li);
                        cr = fmaf(nr, t, ni) * d; ci = fmaf(ni, t, -nr) * d;
                    }
                    if (p.swap) { li = -li; m00 = -2.f * ci; m01 = 2.f * cr; m10 = -2.f * cr; m11 = -2.f * ci; }
                    else { m00 = 2.f * cr; m01 = -2.f * ci; m10 = -2.f * ci; m11 = -2.f * cr; }
                    PIN_F(lr); PIN_F(li); PIN_F(m00); PIN_F(m01); PIN_F(m10); PIN_F(m11);
                }
                if (kb == 2) {
                    PIN_R(tag); tag += 1;
                    if (tw < 88) sts128(bias_s + tw * 16, bz[0], bz[1], bz[2], bz[3]);
                }
                if (kb == 12) {
                    gv0 = ld_relaxed64(&g_gate[c * 256 + tw]);
                    gv1 = ld_relaxed64(&g_gate[c * 256 + 128 + tw]);
                }
                if (kb == 14) {
                    unsigned n = 0;
                    while (gv0.y != tag || gv1.y != tag) {
                        if (++n > kSpinLimit) TRAP();
                        gv0 = ld_relaxed64(&g_gate[c * 256 + tw]);
                        gv1 = ld_relaxed64(&g_gate[c * 256 + 128 + tw]);
                    }
                    sts32(gate_s + ((tw >> 6) * 68 + (tw & 63)) * 4, gv0.x);
                    sts32(gate_s + ((2 + (tw >> 6)) * 68 + (tw & 63)) * 4, gv1.x);
                    __syncwarp();
                }
                if (kb == 15) { if (wg == 0) bar_sync<1, 128>(); else bar_sync<2, 128>(); }
                KBLOCK_END(kb);
            }
            wgmma_wait<0>();
            RELEASE_STAGE(3);
        }
        STAMP(tid == 0, 2); kt0 = 16;
#pragma unroll
        for (int s = 0; s < 64; ++s) pk[s] = pack_bf16_v(acc[4 * (s >> 1) + (s & 1)], acc[4 * (s >> 1) + 2 + (s & 1)]);

        {
            float hr = 0.f, hi = 0.f;
            float l64r, l64i, l128r, l128i;
            uint4 av0, av1;
            __nv_bfloat16* hs = g_Hs + (size_t)ch * 2048 + c * 256 + q * 8;
#pragma unroll
            for (int kb = 0; kb < 16; ++kb) {
                if (kb == 0) { KBLOCK_BEGIN(1, true, kb); } else { KBLOCK_BEGIN(1, false, kb); }
                if (kb < 4) {
#pragma unroll
                    for (int s = kb * 16; s < kb * 16 + 16; ++s) {
                        float nr = bf_lo(pk[s]), ni = bf_hi(pk[s]);
                        CFMA(nr, ni, lr, li, hr, hi);
                        hr = nr; hi = ni;
                    }
                    PIN_F(hr); PIN_F(hi);
                }
                if (kb == 0) {
                    l64r = lr; l64i = li;
#pragma unroll
                    for (int i = 0; i < 6; ++i) CMUL(l64r, l64i, l64r, l64i, l64r, l64i);
                    CMUL(l128r, l128i, l64r, l64i, l64r, l64i);
                    PIN_F(l64r); PIN_F(l64i); PIN_F(l128r); PIN_F(l128i);
                }
                if (kb == 3) {
                    float tr = __shfl_up_sync(0xffffffffu, hr, 1, 4), ti = __shfl_up_sync(0xffffffffu, hi, 1, 4);
                    if (q >= 1) CFMA(hr, hi, l64r, l64i, tr, ti);
                    tr = __shfl_up_sync(0xffffffffu, hr, 2, 4); ti = __shfl_up_sync(0xffffffffu, hi, 2, 4);
                    if (q >= 2) CFMA(hr, hi, l128r, l128i, tr, ti);
                    if (q == 3) st_relaxed2x64(&g_agg[c * 1024 + ch], __float_as_uint(hr), tag, __float_as_uint(hi), tag);
                    tr = __shfl_up_sync(0xffffffffu, hr, 1, 4); ti = __shfl_up_sync(0xffffffffu, hi, 1, 4);
                    hr = (q >= 1) ? tr : 0.f; hi = (q >= 1) ? ti : 0.f;
                }
                if (kb == 5) {
                    av0 = make_uint4(0, tag, 0, tag); av1 = av0;
                    if (q < c) av0 = ld_relaxed2x64(&g_agg[q * 1024 + ch]);
                    if (q + 4 < c) av1 = ld_relaxed2x64(&g_agg[(q + 4) * 1024 + ch]);
                }
                if (kb == 6) {
                    unsigned n = 0;
                    while (av0.y != tag || av0.w != tag || av1.y != tag || av1.w != tag) {
                        if (++n > kSpinLimit) TRAP();
                        if (q < c) av0 = ld_relaxed2x64(&g_agg[q * 1024 + ch]);
                        if (q + 4 < c) av1 = ld_relaxed2x64(&g_agg[(q + 4) * 1024 + ch]);
                    }
                    __syncwarp();
                    float l256r, l256i, l512r, l512i, l1kr, l1ki;
                    CMUL(l256r, l256i, l128r, l128i, l128r, l128i);
                    CMUL(l512r, l512i, l256r, l256i, l256r, l256i);
                    CMUL(l1kr, l1ki, l512r, l512i, l512r, l512i);
                    float vr = __uint_as_float(av0.x), vi = __uint_as_float(av0.z);
                    int n2 = c - 1 - q;
                    if (q + 4 < c) {
                        float ur = __uint_as_float(av1.x), ui = __uint_as_float(av1.z);
                        CFMA(ur, ui, l1kr, l1ki, vr, vi);
                        vr = ur; vi = ui; n2 -= 4;
                    }
                    if (n2 > 0 && (n2 & 1)) CMUL(vr, vi, vr, vi, l256r, l256i);
                    if (n2 > 0 && (n2 & 2)) CMUL(vr, vi, vr, vi, l512r, l512i);
                    vr += __shfl_xor_sync(0xffffffffu, vr, 1); vi += __shfl_xor_sync(0xffffffffu, vi, 1);
                    vr += __shfl_xor_sync(0xffffffffu, vr, 2); vi += __shfl_xor_sync(0xffffffffu, vi, 2);
                    if (q & 1) CMUL(vr, vi, vr, vi, l64r, l64i);
                    if (q & 2) CMUL(vr, vi, vr, vi, l128r, l128i);
                    hr += vr; hi += vi;
                    PIN_F(hr); PIN_F(hi);
                }
                if (kb >= 7 && kb < 15) {
                    const int i = kb - 7;
                    const uint4 ga = lds128(gate_s + (q * 68 + 8 * i) * 4), gb = lds128(gate_s + (q * 68 + 8 * i + 4) * 4);
                    const uint32_t gg[8] = {ga.x, ga.y, ga.z, ga.w, gb.x, gb.y, gb.z, gb.w};
                    float orr[8], oii[8];
#pragma unroll
                    for (int s = 0; s < 8; ++s) {
                        PIN_R(pk[8 * i + s]);
                        float nr = bf_lo(pk[8 * i + s]), ni = bf_hi(pk[8 * i + s]);
                        CFMA(nr, ni, lr, li, hr, hi);
                        hr = nr; hi = ni;
                        const float g = __uint_as_float(gg[s]);
                        orr[s] = fmaf(m00, hr, m01 * hi) * g;
                        oii[s] = fmaf(m10, hr, m11 * hi) * g;
                    }
                    stg128(hs + 32 * i, pack_bf16(orr[0], orr[1]), pack_bf16(orr[2], orr[3]), pack_bf16(orr[4], orr[5]), pack_bf16(orr[6], orr[7]));
                    stg128(hs + 1024 * 2048 + 32 * i, pack_bf16(oii[0], oii[1]), pack_bf16(oii[2], oii[3]), pack_bf16(oii[4], oii[5]), pack_bf16(oii[6], oii[7]));
                    if (kb == 14) bar_arrive<3, 288>();
                }
                KBLOCK_END(kb);
            }
            wgmma_wait<0>();
            RELEASE_STAGE(3);
        }
        STAMP(tid == 0, 3); kt0 = 32;
#pragma unroll
        for (int i = 0; i < 48; ++i) pk[i] = pack_bf16_v(acc[2 * i], acc[2 * i + 1]);

        const uint32_t gate_row = gate_s + ((2 * (w & 1)) * 68 + 8 * (4 * rank + 2 * wg + (w >> 1)) + r) * 4;
        uint32_t om0, om1;
        __nv_bfloat16* hf = g_Hf + (size_t)(rb * 128 + wg * 64 + w * 16 + r) * kF + q * 8;
#define FFN_SLICE(J, BIAS_ENTRY, F0)                                                                   \
    {                                                                                                  \
        const uint4 bv = lds128(bias_s + ((BIAS_ENTRY) * 4 + q) * 16);                                 \
        const uint32_t bb[4] = {bv.x, bv.y, bv.z, bv.w};                                               \
        uint32_t o0[4], o1[4];                                                                         \
        _Pragma("unroll") for (int jj = 0; jj < 4; ++jj) {                                             \
            const uint32_t r0 = bf2_add_relu(pk[8 * (J) + 2 * jj], bb[jj]), r1 = bf2_add_relu(pk[8 * (J) + 2 * jj + 1], bb[jj]); \
            o0[jj] = bf2_mul(bf2_mul(r0, r0), om0);                                                    \
            o1[jj] = bf2_mul(bf2_mul(r1, r1), om1);                                                    \
        }                                                                                              \
        stg128(hf + (F0) + 32 * (J), o0[0], o0[1], o0[2], o0[3]);                                      \
        stg128(hf + 8 * kF + (F0) + 32 * (J), o1[0], o1[1], o1[2], o1[3]);                             \
    }

        {
            const int f0 = 2048 + 192 * j8;
#pragma unroll
            for (int kb = 0; kb < 16; ++kb) {
                if (kb == 0) { KBLOCK_BEGIN(2, true, kb); } else { KBLOCK_BEGIN(2, false, kb); }
                if (kb == 0) {
                    const float a = 1.0f - lds32f(gate_row), b = 1.0f - lds32f(gate_row + 68 * 4);
                    om0 = pack_bf16(a, a); om1 = pack_bf16(b, b);
                }
                if (kb < 6) FFN_SLICE(kb, kb, f0);
                if (kb == 5) bar_arrive<4, 288>();
                KBLOCK_END(kb);
            }
            wgmma_wait<0>();
            RELEASE_STAGE(3);
        }
        STAMP(tid == 0, 4); kt0 = 48;
#pragma unroll
        for (int i = 0; i < 64; ++i) pk[i] = pack_bf16_v(acc[2 * i], acc[2 * i + 1]);

        float e[64];
        const int tb = c * 256 + 128 * (w & 1) + 8 * (4 * rank + 2 * wg + (w >> 1));
        {
            const int f0 = 256 * j8;
            const __nv_bfloat16* xr = p.x + (size_t)(tb + r) * kD + colK + 2 * q;
            uint32_t xv[32];
#pragma unroll
            for (int kb = 0; kb < 16; ++kb) {
                if (kb == 0) { KBLOCK_BEGIN(3, true, kb); } else { KBLOCK_BEGIN(3, false, kb); }
                if (kb < 8) FFN_SLICE(kb, 6 + kb, f0);
                if (kb == 7) bar_arrive<5, 288>();
                if (kb >= 8 && kb < 12) {
                    const int jb = (kb - 8) * 4;
#pragma unroll
                    for (int jj = 0; jj < 4; ++jj) {
                        xv[2 * (jb + jj)] = ldg32(xr + 8 * (jb + jj));
                        xv[2 * (jb + jj) + 1] = ldg32(xr + 64 * kD + 8 * (jb + jj));
                    }
                }
                if (kb >= 11 && kb < 15) {
                    const int jb = (kb - 11) * 4;
                    const float g0 = lds32f(gate_row), g1 = lds32f(gate_row + 68 * 4);
                    const float o0f = bf_lo(om0), o1f = bf_lo(om1);
                    const uint4 dq = lds128(bias_s + ((14 + kb - 11) * 4 + q) * 16), bq = lds128(bias_s + ((18 + kb - 11) * 4 + q) * 16);
                    const uint32_t dv[4] = {dq.x, dq.y, dq.z, dq.w}, bv2[4] = {bq.x, bq.y, bq.z, bq.w};
#pragma unroll
                    for (int jj = 0; jj < 4; ++jj) {
                        const uint32_t x0 = bf2_mul(xv[2 * (jb + jj)], dv[jj]), x1 = bf2_mul(xv[2 * (jb + jj) + 1], dv[jj]);
                        const float bl = bf_lo(bv2[jj]), bh = bf_hi(bv2[jj]);
                        e[4 * (jb + jj) + 0] = fmaf(g0, bf_lo(x0), o0f * bl);
                        e[4 * (jb + jj) + 1] = fmaf(g0, bf_hi(x0), o0f * bh);
                        e[4 * (jb + jj) + 2] = fmaf(g1, bf_lo(x1), o1f * bl);
                        e[4 * (jb + jj) + 3] = fmaf(g1, bf_hi(x1), o1f * bh);
                        PIN_F(e[4 * (jb + jj)]); PIN_F(e[4 * (jb + jj) + 1]); PIN_F(e[4 * (jb + jj) + 2]); PIN_F(e[4 * (jb + jj) + 3]);
                    }
                }
                KBLOCK_END(kb);
            }
        }
        STAMP(tid == 0, 5);
#pragma unroll 1
        for (int k4 = 0; k4 < kNF / 4; ++k4) {
#pragma unroll
            for (int s = 0; s < 4; ++s) {
                KT(64 + k4 * 4 + s, 0);
                mbar_wait(bar_full + 8 * s, k4 & 1);
                KT(64 + k4 * 4 + s, 1);
                wgmma_fence();
                mma_kblock<2, false>(acc, a_lo + s * (kStageBytes >> 4), b_lo + s * (kStageBytes >> 4));
                wgmma_commit();
                KT(64 + k4 * 4 + s, 2);
                wgmma_wait<1>();
                RELEASE_STAGE((s + 3) & 3);
            }
        }
        kt0 = 0;
#pragma unroll
        for (int it = 64 + (kNF & ~3); it < 64 + kNF; ++it) {
            KBLOCK_BEGIN(2, false, it);
            KBLOCK_END(it);
        }
        {
            const uint32_t xs = sbase + kABytes + 8192 + wg * 16384 + tw * 16;
#pragma unroll
            for (int kb = 0; kb < kTail; ++kb) {
                const int it = 64 + kNF + kb;
                KBLOCK_BEGIN(4, false, it);
                if (kb < kTail - 1) wgmma_wait<1>();
                if (it - 1 < kTotal - kStages) RELEASE_STAGE((it - 1) & 3);
                if (kb == 0) STAMP(tid == 0, 15);
                if (kb < 4) {
#pragma unroll
                    for (int i = 0; i < 4; ++i) {
                        const int v = 64 + 16 * kb + 4 * i;
                        sts128f(xs + (it & 3) * kStageBytes + i * 2048, acc[v], acc[v + 1], acc[v + 2], acc[v + 3]);
                    }
                    asm volatile("fence.proxy.async.shared::cta;" ::: "memory");
                    __syncwarp();
                    if (lane == 0) mbar_arrive_local(bar_sent + 8 * kb);
                }
                if (kb >= kTail - 2) {
#pragma unroll
                    for (int j = (kb - (kTail - 2)) * 2; j < (kb - (kTail - 2)) * 2 + 2; ++j) {
                        mbar_wait(bar_recv + 8 * j, 0);
#pragma unroll
                        for (int i = 0; i < 4; ++i) {
                            const uint4 rv = lds128(xs + ((64 + kNF + j) & 3) * kStageBytes + i * 2048);
                            const int v = 16 * j + 4 * i;
                            e[v] += __uint_as_float(rv.x); e[v + 1] += __uint_as_float(rv.y);
                            e[v + 2] += __uint_as_float(rv.z); e[v + 3] += __uint_as_float(rv.w);
                            PIN_F(e[v]); PIN_F(e[v + 1]); PIN_F(e[v + 2]); PIN_F(e[v + 3]);
                        }
                    }
                }
                KT(it, 2);
            }
        }
        wgmma_wait<0>();
        STAMP(tid == 0, 6);
        {
            const bool odd = q & 1;
            float* o0 = p.out + (size_t)(tb + r) * kD + colK + (odd ? 2 * q + 6 : 2 * q);
#pragma unroll
            for (int i = 0; i < 16; i += 2) {
#pragma unroll
                for (int h = 0; h < 2; ++h) {
                    const int va = 4 * i + 2 * h, vb = va + 4;
                    PIN_F(acc[va]); PIN_F(acc[va + 1]); PIN_F(acc[vb]); PIN_F(acc[vb + 1]);
                    const float a0 = acc[va] + e[va], a1 = acc[va + 1] + e[va + 1], b0 = acc[vb] + e[vb], b1 = acc[vb + 1] + e[vb + 1];
                    const float t0 = __shfl_xor_sync(0xffffffffu, odd ? a0 : b0, 1), t1 = __shfl_xor_sync(0xffffffffu, odd ? a1 : b1, 1);
                    stg128f(o0 + h * 64 * kD + 8 * i, odd ? t0 : a0, odd ? t1 : a1, odd ? b0 : t0, odd ? b1 : t1);
                }
            }
        }
        STAMP(tid == 0, 7);
    }
}

typedef CUresult (*EncodeFn)(CUtensorMap*, CUtensorMapDataType, cuuint32_t, void*, const cuuint64_t*, const cuuint64_t*,
                             const cuuint32_t*, const cuuint32_t*, CUtensorMapInterleave, CUtensorMapSwizzle,
                             CUtensorMapL2promotion, CUtensorMapFloatOOBfill);

bool encode(EncodeFn fn, CUtensorMap* m, const void* base, int rank, const cuuint64_t* dims, const cuuint64_t* strides,
            const cuuint32_t* box) {
    cuuint32_t es[5] = {1, 1, 1, 1, 1};
    return fn(m, CU_TENSOR_MAP_DATA_TYPE_BFLOAT16, rank, const_cast<void*>(base), dims, strides, box, es,
              CU_TENSOR_MAP_INTERLEAVE_NONE, CU_TENSOR_MAP_SWIZZLE_128B, CU_TENSOR_MAP_L2_PROMOTION_L2_256B,
              CU_TENSOR_MAP_FLOAT_OOB_FILL_NONE) == CUDA_SUCCESS;
}

}

extern "C" void kernel_launch(void* const* d_in, const int* in_sizes, int n_in, void* d_out, int out_size) {
    (void)in_sizes; (void)n_in; (void)out_size;
    typedef const __nv_bfloat16* bp;
    bp x = (bp)d_in[0], lam_re = (bp)d_in[1], lam_im = (bp)d_in[2], B_re = (bp)d_in[3], B_im = (bp)d_in[4];
    bp C_re = (bp)d_in[5], C_im = (bp)d_in[6], log_dt = (bp)d_in[7], dskip = (bp)d_in[8];
    bp w1 = (bp)d_in[10], b1 = (bp)d_in[11], w2 = (bp)d_in[12], b2 = (bp)d_in[13], gate_w = (bp)d_in[14];

    static EncodeFn fn = nullptr;
    static void *pHs = nullptr, *pHf = nullptr, *pBc = nullptr;
    if (!fn) {
        void* f = nullptr;
        cudaDriverEntryPointQueryResult qr;
        cudaGetDriverEntryPoint("cuTensorMapEncodeTiled", &f, cudaEnableDefault, &qr);
        fn = (EncodeFn)f;
        cudaGetSymbolAddress(&pHs, g_Hs);
        cudaGetSymbolAddress(&pHf, g_Hf);
        cudaGetSymbolAddress(&pBc, g_Bcopy);
        cudaFuncSetAttribute(fused_kernel, cudaFuncAttributeMaxDynamicSharedMemorySize, kSmemBytes);
    }
    cudaStream_t stream = cudaStreamPerThread;

    Params p;
    p.x = x; p.lam_re = lam_re; p.lam_im = lam_im; p.log_dt = log_dt; p.dskip = dskip; p.b1 = b1; p.b2 = b2;
    p.gate_w = gate_w; p.w1 = w1; p.w2 = w2; p.c_re = C_re; p.c_im = C_im; p.b_re = B_re; p.b_im = B_im; p.out = (float*)d_out;

    const char* lo = (const char*)B_re; const char* hi = (const char*)B_im;
    p.swap = 0;
    if (hi < lo) { const char* t = lo; lo = hi; hi = t; p.swap = 1; }
    unsigned long long diff = (unsigned long long)(hi - lo);
    if (diff >= (1ull << 40) || (diff & 15) || diff == 0) {
        cudaMemcpyAsync(pBc, B_re, 2u << 20, cudaMemcpyDeviceToDevice, stream);
        cudaMemcpyAsync((char*)pBc + (2u << 20), B_im, 2u << 20, cudaMemcpyDeviceToDevice, stream);
        lo = (const char*)pBc; diff = 2u << 20; p.swap = 0;
    }

    CUtensorMap mB, mXs, mXf, mW1a, mW1b, mHs, mHf, mCre, mCim, mW2;
    bool ok = true;
    { cuuint64_t d[4] = {1024, 8, 2, 128}, s[3] = {2048, diff, 16384}; cuuint32_t b[4] = {64, 8, 2, 8};
      ok &= encode(fn, &mB, lo, 4, d, s, b); }
    { cuuint64_t d[5] = {1024, 2, 4, 32, 8}, s[4] = {2048, 64 * 2048, 2 * 2048, 256 * 2048}; cuuint32_t b[5] = {64, 2, 4, 16, 1};
      ok &= encode(fn, &mXs, x, 5, d, s, b); }
    { cuuint64_t d[5] = {1024, 8, 4, 8, 8}, s[4] = {2048, 64 * 2048, 8 * 2048, 256 * 2048}; cuuint32_t b[5] = {64, 8, 4, 4, 1};
      ok &= encode(fn, &mXf, x, 5, d, s, b); }
    { cuuint64_t d[3] = {64, 1024, 56}, s[2] = {7168, 128}; cuuint32_t ba[3] = {64, 32, 4}, bb[3] = {64, 32, 3};
      ok &= encode(fn, &mW1a, w1, 3, d, s, ba); ok &= encode(fn, &mW1b, w1, 3, d, s, bb); }
    { cuuint64_t d[3] = {64, 2048, 32}, s[2] = {4096, 128}; cuuint32_t b[3] = {64, 64, 2};
      ok &= encode(fn, &mHs, pHs, 3, d, s, b); }
    { cuuint64_t d[2] = {3584, 2048}, s[1] = {7168}; cuuint32_t b[2] = {64, 128};
      ok &= encode(fn, &mHf, pHf, 2, d, s, b); }
    { cuuint64_t d[2] = {1024, 1024}, s[1] = {2048}; cuuint32_t b[2] = {64, 128};
      ok &= encode(fn, &mCre, C_re, 2, d, s, b); ok &= encode(fn, &mCim, C_im, 2, d, s, b); }
    { cuuint64_t d[5] = {64, 2, 448, 4, 16}, s[4] = {2048, 8 * 2048, 2 * 2048, 128}; cuuint32_t b[5] = {64, 2, 4, 4, 2};
      ok &= encode(fn, &mW2, w2, 5, d, s, b); }
    if (!ok) return;

    fused_kernel<<<128, 384, kSmemBytes, stream>>>(mB, mXs, mXf, mW1a, mW1b, mHs, mHf, mCre, mCim, mW2, p);
}
```

```cpp
#include <cuda_runtime.h>
#include <cuda_bf16.h>
#include <cuda_fp16.h>
#include <cuda.h>
#include <stdint.h>

#define MTAIL 8

#define FIRSTN 1

#define GATE_LD 5

#define PF0LINES 2

namespace {

constexpr int kD = 1024, kF = 3584;
constexpr int kStages = 4;
constexpr int kStageBytes = 49152;
constexpr int kABytes = 16384;
constexpr int kAux = kStages * kStageBytes;
constexpr int kGateOff = kAux;
constexpr int kGateBytesWG = 4 * 68 * 4;
constexpr int kBiasOff = kGateOff + 2 * kGateBytesWG;
constexpr int kBiasBytesWG = 88 * 16;
constexpr int kBarOff = kBiasOff + 2 * kBiasBytesWG;
constexpr int kScaleOff = kBarOff + 256;
constexpr int kSmemBytes = kScaleOff + 2048;
constexpr int kXBytes = 33792;
constexpr uint32_t kSmemOrg = 1024;
constexpr unsigned kSpinLimit = 1u << 22;
constexpr int kTail = MTAIL;
constexpr int kNA = (32 - kTail) / 2;
constexpr int kNF = 12 + kNA;
constexpr int kTotal = 64 + kNF + kTail;

__device__ __align__(1024) __nv_bfloat16 g_Hs[2048 * 2048];
__device__ __align__(1024) __nv_bfloat16 g_Hf[2048 * 3584];
__device__ __align__(1024) __nv_bfloat16 g_Bcopy[2 * 1024 * 1024];
__device__ uint4 g_agg[8 * 1024];
__device__ uint2 g_gate[2048];
__device__ unsigned g_cnt[40 * 32];
__device__ __align__(1024) uint8_t g_X[128 * kXBytes];
__device__ unsigned g_xflag[128 * 64];
__device__ __align__(16) unsigned g_claim[64];
__device__ unsigned g_epoch;
__device__ unsigned g_done;

#define TRAP() break
#define PIN_F(x) asm volatile("" : "+f"(x))
#define PIN_R(x) asm volatile("" : "+r"(x))
__device__ __forceinline__ uint32_t smem_u32(const void* p) { return (uint32_t)__cvta_generic_to_shared(p); }
__device__ __forceinline__ void mbar_init(uint32_t bar, uint32_t count) {
    asm volatile("mbarrier.init.shared::cta.b64 [%0], %1;" ::"r"(bar), "r"(count) : "memory");
}
__device__ __forceinline__ void mbar_expect_tx(uint32_t bar, uint32_t bytes) {
    asm volatile("mbarrier.arrive.expect_tx.shared::cta.b64 _, [%0], %1;" ::"r"(bar), "r"(bytes) : "memory");
}
__device__ __forceinline__ void mbar_wait(uint32_t bar, uint32_t parity) {
    asm volatile(
        "{\n.reg .pred p;\n.reg .u32 n;\n"
        "mbarrier.try_wait.parity.shared::cta.b64 p, [%0], %1;\n"
        "@p bra DONE;\n"
        "mov.u32 n, 0;\n"
        "LOOP:\n"
        "mbarrier.try_wait.parity.shared::cta.b64 p, [%0], %1;\n"
        "@p bra DONE;\n"
        "add.u32 n, n, 1;\n"
        "setp.lt.u32 p, n, %2;\n"
        "@p bra LOOP;\n"
        "DONE:\n}\n"
        ::"r"(bar), "r"(parity), "n"(kSpinLimit) : "memory");
}
__device__ __forceinline__ void mbar_arrive_local(uint32_t bar) {
    asm volatile("mbarrier.arrive.shared::cta.b64 _, [%0];" ::"r"(bar) : "memory");
}
__device__ __forceinline__ void mbar_arrive_cluster(uint32_t cluster_addr) {
    asm volatile("mbarrier.arrive.shared::cluster.b64 _, [%0];" ::"r"(cluster_addr) : "memory");
}
__device__ __forceinline__ uint32_t mapa(uint32_t addr, uint32_t rank) {
    uint32_t r;
    asm("mapa.shared::cluster.u32 %0, %1, %2;" : "=r"(r) : "r"(addr), "r"(rank));
    return r;
}
__device__ __forceinline__ void cluster_arrive() { asm volatile("barrier.cluster.arrive.relaxed.aligned;" ::: "memory"); }
__device__ __forceinline__ void cluster_wait() { asm volatile("barrier.cluster.wait.acquire.aligned;" ::: "memory"); }
template <int ID, int N>
__device__ __forceinline__ void bar_sync() { asm volatile("bar.sync %0, %1;" ::"n"(ID), "n"(N) : "memory"); }
template <int ID, int N>
__device__ __forceinline__ void bar_arrive() { asm volatile("bar.arrive %0, %1;" ::"n"(ID), "n"(N) : "memory"); }

__device__ __forceinline__ void tma2(uint32_t dst, const CUtensorMap* m, uint32_t bar, int c0, int c1) {
    asm volatile("cp.async.bulk.tensor.2d.shared::cluster.global.mbarrier::complete_tx::bytes [%0], [%1, {%3, %4}], [%2];"
                 ::"r"(dst), "l"(m), "r"(bar), "r"(c0), "r"(c1) : "memory");
}
__device__ __forceinline__ void tma3(uint32_t dst, const CUtensorMap* m, uint32_t bar, int c0, int c1, int c2) {
    asm volatile("cp.async.bulk.tensor.3d.shared::cluster.global.mbarrier::complete_tx::bytes [%0], [%1, {%3, %4, %5}], [%2];"
                 ::"r"(dst), "l"(m), "r"(bar), "r"(c0), "r"(c1), "r"(c2) : "memory");
}
__device__ __forceinline__ void tma4(uint32_t dst, const CUtensorMap* m, uint32_t bar, int c0, int c1, int c2, int c3) {
    asm volatile("cp.async.bulk.tensor.4d.shared::cluster.global.mbarrier::complete_tx::bytes [%0], [%1, {%3, %4, %5, %6}], [%2];"
                 ::"r"(dst), "l"(m), "r"(bar), "r"(c0), "r"(c1), "r"(c2), "r"(c3) : "memory");
}
__device__ __forceinline__ void tma5(uint32_t dst, const CUtensorMap* m, uint32_t bar, int c0, int c1, int c2, int c3, int c4) {
    asm volatile("cp.async.bulk.tensor.5d.shared::cluster.global.mbarrier::complete_tx::bytes [%0], [%1, {%3, %4, %5, %6, %7}], [%2];"
                 ::"r"(dst), "l"(m), "r"(bar), "r"(c0), "r"(c1), "r"(c2), "r"(c3), "r"(c4) : "memory");
}
__device__ __forceinline__ void tma2_mc(uint32_t dst, const CUtensorMap* m, uint32_t bar, int c0, int c1) {
    asm volatile("cp.async.bulk.tensor.2d.shared::cluster.global.mbarrier::complete_tx::bytes.multicast::cluster [%0], [%1, {%3, %4}], [%2], %5;"
                 ::"r"(dst), "l"(m), "r"(bar), "r"(c0), "r"(c1), "h"((uint16_t)3) : "memory");
}
__device__ __forceinline__ void tma3_mc(uint32_t dst, const CUtensorMap* m, uint32_t bar, int c0, int c1, int c2) {
    asm volatile("cp.async.bulk.tensor.3d.shared::cluster.global.mbarrier::complete_tx::bytes.multicast::cluster [%0], [%1, {%3, %4, %5}], [%2], %6;"
                 ::"r"(dst), "l"(m), "r"(bar), "r"(c0), "r"(c1), "r"(c2), "h"((uint16_t)3) : "memory");
}
__device__ __forceinline__ void tma5_mc(uint32_t dst, const CUtensorMap* m, uint32_t bar, int c0, int c1, int c2, int c3, int c4) {
    asm volatile("cp.async.bulk.tensor.5d.shared::cluster.global.mbarrier::complete_tx::bytes.multicast::cluster [%0], [%1, {%3, %4, %5, %6, %7}], [%2], %8;"
                 ::"r"(dst), "l"(m), "r"(bar), "r"(c0), "r"(c1), "r"(c2), "r"(c3), "r"(c4), "h"((uint16_t)3) : "memory");
}
__device__ __forceinline__ void bulk_store(void* dst, uint32_t src, uint32_t bytes) {
    asm volatile("cp.async.bulk.global.shared::cta.bulk_group [%0], [%1], %2;" ::"l"(dst), "r"(src), "r"(bytes) : "memory");
}
__device__ __forceinline__ void bulk_load(uint32_t dst, const void* src, uint32_t bytes, uint32_t bar) {
    asm volatile("cp.async.bulk.shared::cluster.global.mbarrier::complete_tx::bytes [%0], [%1], %2, [%3];"
                 ::"r"(dst), "l"(src), "r"(bytes), "r"(bar) : "memory");
}
__device__ __forceinline__ unsigned atom_exch(unsigned* p, unsigned v) {
    unsigned r;
    asm volatile("atom.relaxed.gpu.global.exch.b32 %0, [%1], %2;" : "=r"(r) : "l"(p), "r"(v) : "memory");
    return r;
}
__device__ __forceinline__ uint32_t lds32_cluster(uint32_t a) {
    uint32_t v;
    asm volatile("ld.shared::cluster.u32 %0, [%1];" : "=r"(v) : "r"(a) : "memory");
    return v;
}
__device__ __forceinline__ void sts128f(uint32_t a, float x, float y, float z, float w) {
    asm volatile("st.shared.v4.f32 [%0], {%1, %2, %3, %4};" ::"r"(a), "f"(x), "f"(y), "f"(z), "f"(w) : "memory");
}
__device__ __forceinline__ void prefetch_map(const CUtensorMap* m) {
    asm volatile("prefetch.tensormap [%0];" ::"l"(m) : "memory");
}

__device__ __forceinline__ void prefetch_l2(const void* p, uint32_t bytes) {
    asm volatile("cp.async.bulk.prefetch.L2.global [%0], %1;" ::"l"(p), "r"(bytes) : "memory");
}

__device__ __forceinline__ void wgmma_fence() { asm volatile("wgmma.fence.sync.aligned;" ::: "memory"); }
__device__ __forceinline__ void wgmma_commit() { asm volatile("wgmma.commit_group.sync.aligned;" ::: "memory"); }
template <int N>
__device__ __forceinline__ void wgmma_wait() { asm volatile("wgmma.wait_group.sync.aligned %0;" ::"n"(N) : "memory"); }

__device__ __forceinline__ uint32_t pack_bf16(float lo, float hi) {
    uint32_t r;
    asm("cvt.rn.bf16x2.f32 %0, %1, %2;" : "=r"(r) : "f"(hi), "f"(lo));
    return r;
}
__device__ __forceinline__ uint32_t pack_f16(float lo, float hi) {
    uint32_t r;
    asm("cvt.rn.f16x2.f32 %0, %1, %2;" : "=r"(r) : "f"(hi), "f"(lo));
    return r;
}
__device__ __forceinline__ uint32_t pack_bf16_v(float lo, float hi) {
    uint32_t r;
    asm volatile("cvt.rn.bf16x2.f32 %0, %1, %2;" : "=r"(r) : "f"(hi), "f"(lo));
    return r;
}
__device__ __forceinline__ float bf_lo(uint32_t v) { return __uint_as_float(v << 16); }
__device__ __forceinline__ float bf_hi(uint32_t v) { return __uint_as_float(v & 0xffff0000u); }
__device__ __forceinline__ float bf16_round(float v) { return __bfloat162float(__float2bfloat16_rn(v)); }
__device__ __forceinline__ uint32_t bf2_mul(uint32_t a, uint32_t b) {
    uint32_t r;
    asm("mul.rn.bf16x2 %0, %1, %2;" : "=r"(r) : "r"(a), "r"(b));
    return r;
}
__device__ __forceinline__ uint32_t bf2_add_relu(uint32_t a, uint32_t b) {
    uint32_t r;
    asm("fma.rn.relu.bf16x2 %0, %1, %2, %3;" : "=r"(r) : "r"(a), "r"(0x3f803f80u), "r"(b));
    return r;
}
__device__ __forceinline__ uint4 ldg128(const void* p) {
    uint4 v;
    asm volatile("ld.global.nc.v4.u32 {%0, %1, %2, %3}, [%4];" : "=r"(v.x), "=r"(v.y), "=r"(v.z), "=r"(v.w) : "l"(p));
    return v;
}
__device__ __forceinline__ uint32_t ldg32(const void* p) {
    uint32_t v;
    asm volatile("ld.global.nc.u32 %0, [%1];" : "=r"(v) : "l"(p));
    return v;
}
__device__ __forceinline__ uint32_t ldg16(const __nv_bfloat16* p) {
    uint32_t v;
    asm volatile("ld.global.nc.u16 %0, [%1];" : "=r"(v) : "l"(p));
    return v;
}
__device__ __forceinline__ uint4 ld_relaxed128(const void* p) {
    uint4 v;
    asm volatile("ld.relaxed.gpu.global.v4.u32 {%0, %1, %2, %3}, [%4];" : "=r"(v.x), "=r"(v.y), "=r"(v.z), "=r"(v.w) : "l"(p) : "memory");
    return v;
}
__device__ __forceinline__ uint2 ld_relaxed64(const void* p) {
    unsigned long long v;
    asm volatile("ld.relaxed.gpu.global.u64 %0, [%1];" : "=l"(v) : "l"(p) : "memory");
    return make_uint2((uint32_t)v, (uint32_t)(v >> 32));
}
__device__ __forceinline__ void st_relaxed64(void* p, uint32_t lo, uint32_t hi) {
    unsigned long long v = ((unsigned long long)hi << 32) | lo;
    asm volatile("st.relaxed.gpu.global.u64 [%0], %1;" ::"l"(p), "l"(v) : "memory");
}
__device__ __forceinline__ void st_relaxed2x64(void* p, uint32_t a, uint32_t b, uint32_t c, uint32_t d) {
    unsigned long long v0 = ((unsigned long long)b << 32) | a, v1 = ((unsigned long long)d << 32) | c;
    asm volatile("st.relaxed.gpu.global.v2.u64 [%0], {%1, %2};" ::"l"(p), "l"(v0), "l"(v1) : "memory");
}
__device__ __forceinline__ uint4 ld_relaxed2x64(const void* p) {
    unsigned long long v0, v1;
    asm volatile("ld.relaxed.gpu.global.v2.u64 {%0, %1}, [%2];" : "=l"(v0), "=l"(v1) : "l"(p) : "memory");
    return make_uint4((uint32_t)v0, (uint32_t)(v0 >> 32), (uint32_t)v1, (uint32_t)(v1 >> 32));
}
__device__ __forceinline__ void stg128(void* p, uint32_t a, uint32_t b, uint32_t c, uint32_t d) {
    asm volatile("st.global.v4.u32 [%0], {%1, %2, %3, %4};" ::"l"(p), "r"(a), "r"(b), "r"(c), "r"(d) : "memory");
}
__device__ __forceinline__ void stg64f(void* p, float a, float b) {
    asm volatile("st.global.v2.f32 [%0], {%1, %2};" ::"l"(p), "f"(a), "f"(b) : "memory");
}
__device__ __forceinline__ uint4 lds128(uint32_t a) {
    uint4 v;
    asm volatile("ld.shared.v4.u32 {%0, %1, %2, %3}, [%4];" : "=r"(v.x), "=r"(v.y), "=r"(v.z), "=r"(v.w) : "r"(a) : "memory");
    return v;
}
__device__ __forceinline__ float lds32f(uint32_t a) {
    float v;
    asm volatile("ld.shared.f32 %0, [%1];" : "=f"(v) : "r"(a) : "memory");
    return v;
}
__device__ __forceinline__ void sts128(uint32_t a, uint32_t x, uint32_t y, uint32_t z, uint32_t w) {
    asm volatile("st.shared.v4.u32 [%0], {%1, %2, %3, %4};" ::"r"(a), "r"(x), "r"(y), "r"(z), "r"(w) : "memory");
}
__device__ __forceinline__ void sts32(uint32_t a, uint32_t x) {
    asm volatile("st.shared.u32 [%0], %1;" ::"r"(a), "r"(x) : "memory");
}
__device__ __forceinline__ void stg128f(void* p, float a, float b, float c, float d) {
    asm volatile("st.global.v4.f32 [%0], {%1, %2, %3, %4};" ::"l"(p), "f"(a), "f"(b), "f"(c), "f"(d) : "memory");
}
__device__ __forceinline__ unsigned ld_relaxed32(const unsigned* p) {
    unsigned v;
    asm volatile("ld.relaxed.gpu.global.u32 %0, [%1];" : "=r"(v) : "l"(p) : "memory");
    return v;
}
__device__ __forceinline__ void wait_counter(const unsigned* p, unsigned target) {
    unsigned n = 0, v;
    while (true) {
        asm volatile("ld.acquire.gpu.global.u32 %0, [%1];" : "=r"(v) : "l"(p) : "memory");
        if ((int)(v - target) >= 0) break;
        if (++n > kSpinLimit) TRAP();
        __nanosleep(32);
    }
}
#define KT(IT, W) do { } while (0)
#define STAMP(cond, slot) do { } while (0)

template <int TA, int TB>
__device__ __forceinline__ void wgmma_n256(float (&d)[128], uint64_t da, uint64_t db) {
    asm volatile(
        "{\n.reg .pred p;\nsetp.ne.b32 p, 1, 0;\n"
        "wgmma.mma_async.sync.aligned.m64n256k16.f32.bf16.bf16 "
        "{%0, %1, %2, %3, %4, %5, %6, %7, %8, %9, %10, %11, %12, %13, %14, %15, "
        "%16, %17, %18, %19, %20, %21, %22, %23, %24, %25, %26, %27, %28, %29, %30, %31, "
        "%32, %33, %34, %35, %36, %37, %38, %39, %40, %41, %42, %43, %44, %45, %46, %47, "
        "%48, %49, %50, %51, %52, %53, %54, %55, %56, %57, %58, %59, %60, %61, %62, %63, "
        "%64, %65, %66, %67, %68, %69, %70, %71, %72, %73, %74, %75, %76, %77, %78, %79, "
        "%80, %81, %82, %83, %84, %85, %86, %87, %88, %89, %90, %91, %92, %93, %94, %95, "
        "%96, %97, %98, %99, %100, %101, %102, %103, %104, %105, %106, %107, %108, %109, %110, %111, "
        "%112, %113, %114, %115, %116, %117, %118, %119, %120, %121, %122, %123, %124, %125, %126, %127}, "
        "%128, %129, p, 1, 1, %130, %131;\n}\n"
        : "+f"(d[0]), "+f"(d[1]), "+f"(d[2]), "+f"(d[3]), "+f"(d[4]), "+f"(d[5]), "+f"(d[6]), "+f"(d[7]),
          "+f"(d[8]), "+f"(d[9]), "+f"(d[10]), "+f"(d[11]), "+f"(d[12]), "+f"(d[13]), "+f"(d[14]), "+f"(d[15]),
          "+f"(d[16]), "+f"(d[17]), "+f"(d[18]), "+f"(d[19]), "+f"(d[20]), "+f"(d[21]), "+f"(d[22]), "+f"(d[23]),
          "+f"(d[24]), "+f"(d[25]), "+f"(d[26]), "+f"(d[27]), "+f"(d[28]), "+f"(d[29]), "+f"(d[30]), "+f"(d[31]),
          "+f"(d[32]), "+f"(d[33]), "+f"(d[34]), "+f"(d[35]), "+f"(d[36]), "+f"(d[37]), "+f"(d[38]), "+f"(d[39]),
          "+f"(d[40]), "+f"(d[41]), "+f"(d[42]), "+f"(d[43]), "+f"(d[44]), "+f"(d[45]), "+f"(d[46]), "+f"(d[47]),
          "+f"(d[48]), "+f"(d[49]), "+f"(d[50]), "+f"(d[51]), "+f"(d[52]), "+f"(d[53]), "+f"(d[54]), "+f"(d[55]),
          "+f"(d[56]), "+f"(d[57]), "+f"(d[58]), "+f"(d[59]), "+f"(d[60]), "+f"(d[61]), "+f"(d[62]), "+f"(d[63]),
          "+f"(d[64]), "+f"(d[65]), "+f"(d[66]), "+f"(d[67]), "+f"(d[68]), "+f"(d[69]), "+f"(d[70]), "+f"(d[71]),
          "+f"(d[72]), "+f"(d[73]), "+f"(d[74]), "+f"(d[75]), "+f"(d[76]), "+f"(d[77]), "+f"(d[78]), "+f"(d[79]),
          "+f"(d[80]), "+f"(d[81]), "+f"(d[82]), "+f"(d[83]), "+f"(d[84]), "+f"(d[85]), "+f"(d[86]), "+f"(d[87]),
          "+f"(d[88]), "+f"(d[89]), "+f"(d[90]), "+f"(d[91]), "+f"(d[92]), "+f"(d[93]), "+f"(d[94]), "+f"(d[95]),
          "+f"(d[96]), "+f"(d[97]), "+f"(d[98]), "+f"(d[99]), "+f"(d[100]), "+f"(d[101]), "+f"(d[102]), "+f"(d[103]),
          "+f"(d[104]), "+f"(d[105]), "+f"(d[106]), "+f"(d[107]), "+f"(d[108]), "+f"(d[109]), "+f"(d[110]), "+f"(d[111]),
          "+f"(d[112]), "+f"(d[113]), "+f"(d[114]), "+f"(d[115]), "+f"(d[116]), "+f"(d[117]), "+f"(d[118]), "+f"(d[119]),
          "+f"(d[120]), "+f"(d[121]), "+f"(d[122]), "+f"(d[123]), "+f"(d[124]), "+f"(d[125]), "+f"(d[126]), "+f"(d[127])
        : "l"(da), "l"(db), "n"(TA), "n"(TB));
}
template <int TA, int TB>
__device__ __forceinline__ void wgmma_n256_first(float (&d)[128], uint64_t da, uint64_t db) {
    asm volatile(
        "{\n.reg .pred p;\nsetp.ne.b32 p, 0, 0;\n"
        "wgmma.mma_async.sync.aligned.m64n256k16.f32.bf16.bf16 "
        "{%0, %1, %2, %3, %4, %5, %6, %7, %8, %9, %10, %11, %12, %13, %14, %15, "
        "%16, %17, %18, %19, %20, %21, %22, %23, %24, %25, %26, %27, %28, %29, %30, %31, "
        "%32, %33, %34, %35, %36, %37, %38, %39, %40, %41, %42, %43, %44, %45, %46, %47, "
        "%48, %49, %50, %51, %52, %53, %54, %55, %56, %57, %58, %59, %60, %61, %62, %63, "
        "%64, %65, %66, %67, %68, %69, %70, %71, %72, %73, %74, %75, %76, %77, %78, %79, "
        "%80, %81, %82, %83, %84, %85, %86, %87, %88, %89, %90, %91, %92, %93, %94, %95, "
        "%96, %97, %98, %99, %100, %101, %102, %103, %104, %105, %106, %107, %108, %109, %110, %111, "
        "%112, %113, %114, %115, %116, %117, %118, %119, %120, %121, %122, %123, %124, %125, %126, %127}, "
        "%128, %129, p, 1, 1, %130, %131;\n}\n"
        : "=f"(d[0]), "=f"(d[1]), "=f"(d[2]), "=f"(d[3]), "=f"(d[4]), "=f"(d[5]), "=f"(d[6]), "=f"(d[7]),
          "=f"(d[8]), "=f"(d[9]), "=f"(d[10]), "=f"(d[11]), "=f"(d[12]), "=f"(d[13]), "=f"(d[14]), "=f"(d[15]),
          "=f"(d[16]), "=f"(d[17]), "=f"(d[18]), "=f"(d[19]), "=f"(d[20]), "=f"(d[21]), "=f"(d[22]), "=f"(d[23]),
          "=f"(d[24]), "=f"(d[25]), "=f"(d[26]), "=f"(d[27]), "=f"(d[28]), "=f"(d[29]), "=f"(d[30]), "=f"(d[31]),
          "=f"(d[32]), "=f"(d[33]), "=f"(d[34]), "=f"(d[35]), "=f"(d[36]), "=f"(d[37]), "=f"(d[38]), "=f"(d[39]),
          "=f"(d[40]), "=f"(d[41]), "=f"(d[42]), "=f"(d[43]), "=f"(d[44]), "=f"(d[45]), "=f"(d[46]), "=f"(d[47]),
          "=f"(d[48]), "=f"(d[49]), "=f"(d[50]), "=f"(d[51]), "=f"(d[52]), "=f"(d[53]), "=f"(d[54]), "=f"(d[55]),
          "=f"(d[56]), "=f"(d[57]), "=f"(d[58]), "=f"(d[59]), "=f"(d[60]), "=f"(d[61]), "=f"(d[62]), "=f"(d[63]),
          "=f"(d[64]), "=f"(d[65]), "=f"(d[66]), "=f"(d[67]), "=f"(d[68]), "=f"(d[69]), "=f"(d[70]), "=f"(d[71]),
          "=f"(d[72]), "=f"(d[73]), "=f"(d[74]), "=f"(d[75]), "=f"(d[76]), "=f"(d[77]), "=f"(d[78]), "=f"(d[79]),
          "=f"(d[80]), "=f"(d[81]), "=f"(d[82]), "=f"(d[83]), "=f"(d[84]), "=f"(d[85]), "=f"(d[86]), "=f"(d[87]),
          "=f"(d[88]), "=f"(d[89]), "=f"(d[90]), "=f"(d[91]), "=f"(d[92]), "=f"(d[93]), "=f"(d[94]), "=f"(d[95]),
          "=f"(d[96]), "=f"(d[97]), "=f"(d[98]), "=f"(d[99]), "=f"(d[100]), "=f"(d[101]), "=f"(d[102]), "=f"(d[103]),
          "=f"(d[104]), "=f"(d[105]), "=f"(d[106]), "=f"(d[107]), "=f"(d[108]), "=f"(d[109]), "=f"(d[110]), "=f"(d[111]),
          "=f"(d[112]), "=f"(d[113]), "=f"(d[114]), "=f"(d[115]), "=f"(d[116]), "=f"(d[117]), "=f"(d[118]), "=f"(d[119]),
          "=f"(d[120]), "=f"(d[121]), "=f"(d[122]), "=f"(d[123]), "=f"(d[124]), "=f"(d[125]), "=f"(d[126]), "=f"(d[127])
        : "l"(da), "l"(db), "n"(TA), "n"(TB));
}
template <int TA, int TB>
__device__ __forceinline__ void wgmma_n192(float (&d)[128], uint64_t da, uint64_t db) {
    asm volatile(
        "{\n.reg .pred p;\nsetp.ne.b32 p, 1, 0;\n"
        "wgmma.mma_async.sync.aligned.m64n192k16.f32.bf16.bf16 "
        "{%0, %1, %2, %3, %4, %5, %6, %7, %8, %9, %10, %11, %12, %13, %14, %15, "
        "%16, %17, %18, %19, %20, %21, %22, %23, %24, %25, %26, %27, %28, %29, %30, %31, "
        "%32, %33, %34, %35, %36, %37, %38, %39, %40, %41, %42, %43, %44, %45, %46, %47, "
        "%48, %49, %50, %51, %52, %53, %54, %55, %56, %57, %58, %59, %60, %61, %62, %63, "
        "%64, %65, %66, %67, %68, %69, %70, %71, %72, %73, %74, %75, %76, %77, %78, %79, "
        "%80, %81, %82, %83, %84, %85, %86, %87, %88, %89, %90, %91, %92, %93, %94, %95}, "
        "%96, %97, p, 1, 1, %98, %99;\n}\n"
        : "+f"(d[0]), "+f"(d[1]), "+f"(d[2]), "+f"(d[3]), "+f"(d[4]), "+f"(d[5]), "+f"(d[6]), "+f"(d[7]),
          "+f"(d[8]), "+f"(d[9]), "+f"(d[10]), "+f"(d[11]), "+f"(d[12]), "+f"(d[13]), "+f"(d[14]), "+f"(d[15]),
          "+f"(d[16]), "+f"(d[17]), "+f"(d[18]), "+f"(d[19]), "+f"(d[20]), "+f"(d[21]), "+f"(d[22]), "+f"(d[23]),
          "+f"(d[24]), "+f"(d[25]), "+f"(d[26]), "+f"(d[27]), "+f"(d[28]), "+f"(d[29]), "+f"(d[30]), "+f"(d[31]),
          "+f"(d[32]), "+f"(d[33]), "+f"(d[34]), "+f"(d[35]), "+f"(d[36]), "+f"(d[37]), "+f"(d[38]), "+f"(d[39]),
          "+f"(d[40]), "+f"(d[41]), "+f"(d[42]), "+f"(d[43]), "+f"(d[44]), "+f"(d[45]), "+f"(d[46]), "+f"(d[47]),
          "+f"(d[48]), "+f"(d[49]), "+f"(d[50]), "+f"(d[51]), "+f"(d[52]), "+f"(d[53]), "+f"(d[54]), "+f"(d[55]),
          "+f"(d[56]), "+f"(d[57]), "+f"(d[58]), "+f"(d[59]), "+f"(d[60]), "+f"(d[61]), "+f"(d[62]), "+f"(d[63]),
          "+f"(d[64]), "+f"(d[65]), "+f"(d[66]), "+f"(d[67]), "+f"(d[68]), "+f"(d[69]), "+f"(d[70]), "+f"(d[71]),
          "+f"(d[72]), "+f"(d[73]), "+f"(d[74]), "+f"(d[75]), "+f"(d[76]), "+f"(d[77]), "+f"(d[78]), "+f"(d[79]),
          "+f"(d[80]), "+f"(d[81]), "+f"(d[82]), "+f"(d[83]), "+f"(d[84]), "+f"(d[85]), "+f"(d[86]), "+f"(d[87]),
          "+f"(d[88]), "+f"(d[89]), "+f"(d[90]), "+f"(d[91]), "+f"(d[92]), "+f"(d[93]), "+f"(d[94]), "+f"(d[95])
        : "l"(da), "l"(db), "n"(TA), "n"(TB));
}
template <int TA, int TB>
__device__ __forceinline__ void wgmma_n192_first(float (&d)[128], uint64_t da, uint64_t db) {
    asm volatile(
        "{\n.reg .pred p;\nsetp.ne.b32 p, 0, 0;\n"
        "wgmma.mma_async.sync.aligned.m64n192k16.f32.bf16.bf16 "
        "{%0, %1, %2, %3, %4, %5, %6, %7, %8, %9, %10, %11, %12, %13, %14, %15, "
        "%16, %17, %18, %19, %20, %21, %22, %23, %24, %25, %26, %27, %28, %29, %30, %31, "
        "%32, %33, %34, %35, %36, %37, %38, %39, %40, %41, %42, %43, %44, %45, %46, %47, "
        "%48, %49, %50, %51, %52, %53, %54, %55, %56, %57, %58, %59, %60, %61, %62, %63, "
        "%64, %65, %66, %67, %68, %69, %70, %71, %72, %73, %74, %75, %76, %77, %78, %79, "
        "%80, %81, %82, %83, %84, %85, %86, %87, %88, %89, %90, %91, %92, %93, %94, %95}, "
        "%96, %97, p, 1, 1, %98, %99;\n}\n"
        : "=f"(d[0]), "=f"(d[1]), "=f"(d[2]), "=f"(d[3]), "=f"(d[4]), "=f"(d[5]), "=f"(d[6]), "=f"(d[7]),
          "=f"(d[8]), "=f"(d[9]), "=f"(d[10]), "=f"(d[11]), "=f"(d[12]), "=f"(d[13]), "=f"(d[14]), "=f"(d[15]),
          "=f"(d[16]), "=f"(d[17]), "=f"(d[18]), "=f"(d[19]), "=f"(d[20]), "=f"(d[21]), "=f"(d[22]), "=f"(d[23]),
          "=f"(d[24]), "=f"(d[25]), "=f"(d[26]), "=f"(d[27]), "=f"(d[28]), "=f"(d[29]), "=f"(d[30]), "=f"(d[31]),
          "=f"(d[32]), "=f"(d[33]), "=f"(d[34]), "=f"(d[35]), "=f"(d[36]), "=f"(d[37]), "=f"(d[38]), "=f"(d[39]),
          "=f"(d[40]), "=f"(d[41]), "=f"(d[42]), "=f"(d[43]), "=f"(d[44]), "=f"(d[45]), "=f"(d[46]), "=f"(d[47]),
          "=f"(d[48]), "=f"(d[49]), "=f"(d[50]), "=f"(d[51]), "=f"(d[52]), "=f"(d[53]), "=f"(d[54]), "=f"(d[55]),
          "=f"(d[56]), "=f"(d[57]), "=f"(d[58]), "=f"(d[59]), "=f"(d[60]), "=f"(d[61]), "=f"(d[62]), "=f"(d[63]),
          "=f"(d[64]), "=f"(d[65]), "=f"(d[66]), "=f"(d[67]), "=f"(d[68]), "=f"(d[69]), "=f"(d[70]), "=f"(d[71]),
          "=f"(d[72]), "=f"(d[73]), "=f"(d[74]), "=f"(d[75]), "=f"(d[76]), "=f"(d[77]), "=f"(d[78]), "=f"(d[79]),
          "=f"(d[80]), "=f"(d[81]), "=f"(d[82]), "=f"(d[83]), "=f"(d[84]), "=f"(d[85]), "=f"(d[86]), "=f"(d[87]),
          "=f"(d[88]), "=f"(d[89]), "=f"(d[90]), "=f"(d[91]), "=f"(d[92]), "=f"(d[93]), "=f"(d[94]), "=f"(d[95])
        : "l"(da), "l"(db), "n"(TA), "n"(TB));
}
template <int TA, int TB>
__device__ __forceinline__ void wgmma_n128(float (&d)[128], uint64_t da, uint64_t db) {
    asm volatile(
        "{\n.reg .pred p;\nsetp.ne.b32 p, 1, 0;\n"
        "wgmma.mma_async.sync.aligned.m64n128k16.f32.bf16.bf16 "
        "{%0, %1, %2, %3, %4, %5, %6, %7, %8, %9, %10, %11, %12, %13, %14, %15, "
        "%16, %17, %18, %19, %20, %21, %22, %23, %24, %25, %26, %27, %28, %29, %30, %31, "
        "%32, %33, %34, %35, %36, %37, %38, %39, %40, %41, %42, %43, %44, %45, %46, %47, "
        "%48, %49, %50, %51, %52, %53, %54, %55, %56, %57, %58, %59, %60, %61, %62, %63}, "
        "%64, %65, p, 1, 1, %66, %67;\n}\n"
        : "+f"(d[0]), "+f"(d[1]), "+f"(d[2]), "+f"(d[3]), "+f"(d[4]), "+f"(d[5]), "+f"(d[6]), "+f"(d[7]),
          "+f"(d[8]), "+f"(d[9]), "+f"(d[10]), "+f"(d[11]), "+f"(d[12]), "+f"(d[13]), "+f"(d[14]), "+f"(d[15]),
          "+f"(d[16]), "+f"(d[17]), "+f"(d[18]), "+f"(d[19]), "+f"(d[20]), "+f"(d[21]), "+f"(d[22]), "+f"(d[23]),
          "+f"(d[24]), "+f"(d[25]), "+f"(d[26]), "+f"(d[27]), "+f"(d[28]), "+f"(d[29]), "+f"(d[30]), "+f"(d[31]),
          "+f"(d[32]), "+f"(d[33]), "+f"(d[34]), "+f"(d[35]), "+f"(d[36]), "+f"(d[37]), "+f"(d[38]), "+f"(d[39]),
          "+f"(d[40]), "+f"(d[41]), "+f"(d[42]), "+f"(d[43]), "+f"(d[44]), "+f"(d[45]), "+f"(d[46]), "+f"(d[47]),
          "+f"(d[48]), "+f"(d[49]), "+f"(d[50]), "+f"(d[51]), "+f"(d[52]), "+f"(d[53]), "+f"(d[54]), "+f"(d[55]),
          "+f"(d[56]), "+f"(d[57]), "+f"(d[58]), "+f"(d[59]), "+f"(d[60]), "+f"(d[61]), "+f"(d[62]), "+f"(d[63])
        : "l"(da), "l"(db), "n"(TA), "n"(TB));
}

template <int MODE, bool FIRST>
__device__ __forceinline__ void mma_kblock(float (&acc)[128], uint32_t a_lo, uint32_t b_lo) {
    constexpr uint64_t HI = (uint64_t)(64u | 0x40000000u) << 32;
    constexpr uint32_t HALF = (MODE == 1) ? 12288u : 16384u;
    constexpr bool BN = (MODE == 1 || MODE == 2 || MODE == 4);
#pragma unroll
    for (int kk = 0; kk < 4; ++kk) {
        const uint32_t ao = (MODE == 3) ? kk * 2048u : kk * 32u;
        const uint32_t bo = BN ? ((kk >> 1) * HALF + (kk & 1) * 2048u) : kk * 32u;
        const uint64_t da = HI | (uint64_t)(a_lo + (ao >> 4) + (1u << 16));
        const uint64_t db = HI | (uint64_t)(b_lo + (bo >> 4) + (BN ? (256u << 16) : (1u << 16)));
        if (MODE == 1) {
            if (FIRST && kk == 0) wgmma_n192_first<0, 1>(acc, da, db); else wgmma_n192<0, 1>(acc, da, db);
        } else if (MODE == 4) {
            wgmma_n128<0, 1>(acc, da, db);
        } else {
            if (FIRST && kk == 0) wgmma_n256_first<(MODE == 3), BN>(acc, da, db);
            else wgmma_n256<(MODE == 3), BN>(acc, da, db);
        }
    }
}

struct Params {
    const __nv_bfloat16* x;
    const __nv_bfloat16* lam_re;
    const __nv_bfloat16* lam_im;
    const __nv_bfloat16* log_dt;
    const __nv_bfloat16* dskip;
    const __nv_bfloat16* b1;
    const __nv_bfloat16* b2;
    const __nv_bfloat16* gate_w;
    const __nv_bfloat16* w1;
    const __nv_bfloat16* w2;
    const __nv_bfloat16* c_re;
    const __nv_bfloat16* c_im;
    const __nv_bfloat16* b_re;
    const __nv_bfloat16* b_im;
    float* out;
    int swap;
};

#define CMUL(rr, ri, ar, ai, br, bi) do { float _r = (ar) * (br) - (ai) * (bi); float _i = (ar) * (bi) + (ai) * (br); rr = _r; ri = _i; } while (0)
#define CFMA(rr, ri, ar, ai, br, bi) do { float _r = fmaf(-(ai), (bi), fmaf((ar), (br), rr)); float _i = fmaf((ai), (br), fmaf((ar), (bi), ri)); rr = _r; ri = _i; } while (0)

#define KBLOCK_BEGIN(MODE, FIRST, IT)                                                            \
    KT(kt0 + (IT), 0);                                                                           \
    PIN_R(a_lo);                                                                                 \
    mbar_wait(bar_full + 8 * ((IT) & 3), ((IT) >> 2) & 1);                                       \
    KT(kt0 + (IT), 1);                                                                           \
    wgmma_fence();                                                                               \
    mma_kblock<MODE, FIRST>(acc, a_lo + ((IT) & 3) * (kStageBytes >> 4), b_lo + ((IT) & 3) * (kStageBytes >> 4)); \
    wgmma_commit();                                                                              \
    KBLOCK_EARLY(MODE, IT)
#define RELEASE_STAGE(S) do { if (lane < 2) mbar_arrive_cluster(rel_addr + 8 * (S)); } while (0)
#define KBLOCK_EARLY(MODE, IT) if ((MODE) != 4 && (IT) > 0) { wgmma_wait<1>(); RELEASE_STAGE(((IT) - 1) & 3); }
#define KBLOCK_END(IT) KT(kt0 + (IT), 2);

__global__ void __cluster_dims__(2, 1, 1) __launch_bounds__(384, 1)
fused_kernel(const __grid_constant__ CUtensorMap mB, const __grid_constant__ CUtensorMap mXs, const __grid_constant__ CUtensorMap mXf,
             const __grid_constant__ CUtensorMap mW1a, const __grid_constant__ CUtensorMap mW1b, const __grid_constant__ CUtensorMap mHs,
             const __grid_constant__ CUtensorMap mHf, const __grid_constant__ CUtensorMap mCre, const __grid_constant__ CUtensorMap mCim,
             const __grid_constant__ CUtensorMap mW2, const Params p) {
    extern __shared__ __align__(1024) uint8_t smem_raw[];
    const uint32_t sbase = smem_u32(smem_raw);
    if ((sbase & 0x3ffffu) != kSmemOrg) return;
    const uint32_t bar_full = sbase + kBarOff, bar_empty = bar_full + 32, bar_dep = bar_full + 64;
    const uint32_t bar_sent = bar_full + 96, bar_recv = bar_full + 160, role_s = bar_full + 192;

    const int tid = threadIdx.x, lane = tid & 31;
    const int warp = __shfl_sync(0xffffffffu, tid >> 5, 0);
    const uint32_t rank = blockIdx.x & 1;

    int pref;
    {
        unsigned smid;
        asm("mov.u32 %0, %%smid;" : "=r"(smid));
        const int t = smid >> 1, u = t - 32, d = (u * 37) >> 8;
        pref = (t < 32) ? (t & 7) * 8 + (t >> 3) : (t < 60) ? (1 + u - 7 * d) * 8 + 4 + d : ((t - 58) & 7);
    }
#define FIRST_FILL(ROLE)                                                                     \
    _Pragma("unroll 1") for (int kb = 0; kb < FIRSTN; ++kb) {                                \
        const uint32_t st = sbase + kb * kStageBytes, fb = bar_full + 8 * kb;                \
        mbar_expect_tx(fb, 49152);                                                           \
        tma4(st, &mB, fb, kb * 64, 0, 0, (((ROLE) & 7) * 2 + (int)rank) * 8);                \
        tma5(st + kABytes, &mXs, fb, kb * 64, 0, 0, 0, (ROLE) >> 3);                         \
        tma5(st + kABytes + 16384, &mXs, fb, kb * 64, 0, 0, 16, (ROLE) >> 3);                \
    }
    STAMP(tid == 0, 0);
    if (tid == 0) {
        prefetch_map(&mB); prefetch_map(&mXs);
#pragma unroll
        for (int s = 0; s < kStages; ++s) {
            mbar_init(bar_full + 8 * s, 1);
            mbar_init(bar_empty + 8 * s, 16);
            mbar_init(bar_dep + 8 * s, 1);
            mbar_init(bar_sent + 8 * s, 8);
            mbar_init(bar_recv + 8 * s, 1);
        }
        asm volatile("fence.mbarrier_init.release.cluster;\nfence.proxy.async.shared::cta;" ::: "memory");
        FIRST_FILL(pref);
    } else if (tid == 32) {
        if (rank == 0) {
            int role = pref;
            unsigned taken = atom_exch(&g_claim[pref], 1u);
#pragma unroll 1
            for (int i = 0; taken != 0 && i < 64; ++i) { role = i; taken = atom_exch(&g_claim[i], 1u); }
            sts32(role_s, role);
            asm volatile("fence.acq_rel.cluster;" ::: "memory");
        }
    }
    else if (tid >= 128 && tid < 128 + 32 * PF0LINES) {
        const int row = blockIdx.x * 32 + lane;
        const __nv_bfloat16* src = (row < 2048) ? p.x + (size_t)row * kD : (row < 3072) ? p.b_re + (size_t)(row - 2048) * kD : p.b_im + (size_t)(row - 3072) * kD;
        asm volatile("prefetch.global.L2 [%0];" ::"l"(src + (warp - 4) * 64) : "memory");
    }
    __syncwarp();
    cluster_arrive();
#define TAKE_ROLE()                                                                          \
    cluster_wait();                                                                          \
    const int role = __shfl_sync(0xffffffffu, (int)lds32_cluster(mapa(role_s, 0)), 0);       \
    if (role != pref) {                                                                      \
        if (tid == 0) {                                                                      \
            _Pragma("unroll 1") for (int kb = 0; kb < FIRSTN; ++kb) {                        \
                mbar_wait(bar_full + 8 * kb, 0);                                             \
                asm volatile("mbarrier.inval.shared::cta.b64 [%0];" ::"r"(bar_full + 8 * kb) : "memory"); \
                mbar_init(bar_full + 8 * kb, 1);                                             \
            }                                                                                \
            asm volatile("fence.mbarrier_init.release.cluster;\nfence.proxy.async.shared::cta;" ::: "memory"); \
            FIRST_FILL(role);                                                                \
        }                                                                                    \
        __syncwarp();                                                                        \
        bar_sync<0, 384>();                                                                  \
    }                                                                                        \
    const int c = role >> 3;                                         \
    const int j8 = role & 7;                                    \
    const int cb = j8 * 2 + (int)rank;                         \
    const int rb = 2 * c + (int)rank;                           \
    const int kh = j8 >> 2;                \
    const int colK = (j8 & 3) * 256 + kh * 128, colS = colK ^ 128;    \
    (void)cb; (void)rb; (void)colS;

    if (warp >= 8) {
        asm volatile("setmaxnreg.dec.sync.aligned.u32 24;");
        TAKE_ROLE();
#define SEND_CHUNK(J)                                                                                           \
    if (lane == 0) {                                                                                            \
        uint8_t* dst = g_X + (size_t)(role * 2 + rank) * kXBytes + (J) * 16384;                                 \
        const uint32_t src = sbase + ((64 + kNF + (J)) & 3) * kStageBytes + kABytes + 8192;                     \
        mbar_wait(bar_sent + 8 * (J), 0);                                                                       \
        bulk_store(dst, src, 8192);                                                                             \
        bulk_store(dst + 8192, src + 16384, 8192);                                                              \
        if ((J) == 0) bulk_store(dst + 32768, sbase + kScaleOff, 1024);                                         \
        asm volatile("cp.async.bulk.commit_group;\ncp.async.bulk.wait_group 0;" ::: "memory");                  \
        asm volatile("st.release.gpu.global.u32 [%0], %1;" ::"l"(&g_xflag[(role * 2 + rank) * 64 + (J) * 32]), "r"(tag) : "memory"); \
        STAMP(true, 12 + (J));                                                                                  \
    }
        if (warp == 8) {
            if (lane == 0) {
                int it = FIRSTN;
#define ACQUIRE(BYTES)                                                   \
    const uint32_t st = sbase + (it & 3) * kStageBytes, fb = bar_full + 8 * (it & 3); \
    mbar_wait(bar_empty + 8 * (it & 3), ((it >> 2) & 1) ^ 1);            \
    mbar_expect_tx(fb, BYTES);
                prefetch_map(&mXf); prefetch_map(&mW1b); prefetch_map(&mW1a);
#pragma unroll 1
                for (int kb = FIRSTN; kb < 16; ++kb, ++it) {
                    ACQUIRE(49152);
                    tma4(st, &mB, fb, kb * 64, 0, 0, cb * 8);
                    tma5_mc(st + kABytes + rank * 16384, &mXs, fb, kb * 64, 0, 0, rank * 16, c);
                }
#pragma unroll 1
                for (int kb = 0; kb < 16; ++kb, ++it) {
                    ACQUIRE(40960);
                    tma5(st, &mXf, fb, kb * 64, 0, 0, rank * 4, c);
                    tma3_mc(st + kABytes + rank * 12288, &mW1b, fb, 0, kb * 64 + rank * 32, 32 + 3 * j8);
                }
                const CUtensorMap* mC = kh ? &mCim : &mCre;
                prefetch_map(&mHs); prefetch_map(&mHf); prefetch_map(mC); prefetch_map(&mW2);
#pragma unroll 1
                for (int kb = 0; kb < 16; ++kb, ++it) {
                    ACQUIRE(49152);
                    tma5(st, &mXf, fb, kb * 64, 0, 0, rank * 4, c);
                    tma3_mc(st + kABytes + rank * 16384, &mW1a, fb, 0, kb * 64 + rank * 32, 4 * j8);
                }
                STAMP(true, 8);
                mbar_wait(bar_dep, 0);
                asm volatile("fence.proxy.async.global;" ::: "memory");
                STAMP(true, 9);
#pragma unroll 1
                for (int kb = 0; kb < 16; ++kb, ++it) {
                    ACQUIRE(49152);
                    tma3(st, &mHs, fb, 0, kh * 1024 + kb * 64, rb * 2);
                    tma2_mc(st + kABytes + rank * 16384, mC, fb, kb * 64, rank ? colS : colK);
                }
                mbar_wait(bar_dep + 8, 0);
                asm volatile("fence.proxy.async.global;" ::: "memory");
                STAMP(true, 10);
#pragma unroll 1
                for (int kb = 0; kb < kNF + kTail; ++kb, ++it) {
                    if (kb == 12) {
                        mbar_wait(bar_dep + 16, 0);
                        asm volatile("fence.proxy.async.global;" ::: "memory");
                    }
                    const int f0 = (kb < 12) ? 2048 + 768 * kh + 64 * kb : (kb < kNF ? 64 * (kNA * kh + kb - 12) : 64 * (kNA + kb - 12));
                    ACQUIRE(kb < kNF ? 49152 : 32768);
                    tma2(st, &mHf, fb, f0, rb * 128);
                    tma5_mc(st + kABytes + rank * 16384, &mW2, fb, 0, 0, (f0 >> 3) + 4 * rank, 0, colK >> 6);
                    if (kb < kNF) tma5_mc(st + kABytes + rank * 16384 + 8192, &mW2, fb, 0, 0, (f0 >> 3) + 4 * rank, 0, colS >> 6);
                }
            }
        } else if (warp == 9) {
            const unsigned tag = ld_relaxed32(&g_epoch) + 1;
#pragma unroll
            for (int ev = 0; ev < 3; ++ev) {
                if (ev == 0) bar_sync<3, 320>(); else if (ev == 1) bar_sync<4, 288>(); else bar_sync<5, 288>();
                if (lane == 0) {
                    unsigned* cnt = &g_cnt[(ev == 0 ? c : (ev == 1 ? 8 : 24) + rb) * 32];
                    asm volatile("fence.acq_rel.gpu;\nfence.proxy.async.global;" ::: "memory");
                    asm volatile("red.relaxed.gpu.global.add.u32 [%0], 1;" ::"l"(cnt) : "memory");
                }
            }
            SEND_CHUNK(0);
        } else if (warp == 10) {
            if (lane == 0) {
                const unsigned tag = ld_relaxed32(&g_epoch) + 1;
                wait_counter(&g_cnt[c * 32], tag * 16u);
                mbar_arrive_local(bar_dep);
                if (atomicInc(&g_done, 127u) == 127u) {
                    asm volatile("st.relaxed.gpu.global.u32 [%0], %1;" ::"l"(&g_epoch), "r"(tag) : "memory");
#pragma unroll 1
                    for (int i = 0; i < 64; i += 4) stg128(&g_claim[i], 0, 0, 0, 0);
                }
                wait_counter(&g_cnt[(8 + rb) * 32], tag * 8u);
                mbar_arrive_local(bar_dep + 8);
                wait_counter(&g_cnt[(24 + rb) * 32], tag * 8u);
                mbar_arrive_local(bar_dep + 16);
                const uint8_t* src = g_X + (size_t)((role ^ 4) * 2 + rank) * kXBytes;
                mbar_wait(bar_sent + 16, 0);
#pragma unroll 1
                for (int j = 0; j < 2; ++j) {
                    const uint32_t dst = sbase + ((64 + kNF + 2 + j) & 3) * kStageBytes + kABytes + 8192;
                    wait_counter(&g_xflag[((role ^ 4) * 2 + rank) * 64 + j * 32], tag);
                    asm volatile("fence.proxy.async.global;" ::: "memory");
                    mbar_expect_tx(bar_recv + 8 * j, j ? 16384 : 17408);
                    bulk_load(dst, src + j * 16384, 8192, bar_recv + 8 * j);
                    bulk_load(dst + 16384, src + j * 16384 + 8192, 8192, bar_recv + 8 * j);
                    if (j == 0) { bulk_load(sbase + kScaleOff + 1024, src + 32768, 1024, bar_recv); STAMP(true, 11); }
                }
                STAMP(true, 14);
            }
        } else {
            const unsigned tag = ld_relaxed32(&g_epoch) + 1;
            bar_sync<3, 320>();
            SEND_CHUNK(1);
        }
    } else {
        asm volatile("setmaxnreg.inc.sync.aligned.u32 240;");
        TAKE_ROLE();
        const int wg = warp >> 2, w = warp & 3, r = lane >> 2, q = lane & 3, tw = tid & 127;
        uint32_t a_lo = (kSmemOrg + wg * 8192) >> 4;
        constexpr uint32_t b_lo = (kSmemOrg + kABytes) >> 4;
        const uint32_t rel_addr = mapa(bar_empty, (uint32_t)(lane & 1));
        const uint32_t gate_s = sbase + kGateOff + wg * kGateBytesWG, bias_s = sbase + kBiasOff + wg * kBiasBytesWG;
        float acc[128];
        int kt0 = 0; (void)kt0;
        uint32_t pk[64];
        unsigned tag = ld_relaxed32(&g_epoch);

        const int ch = cb * 64 + warp * 8 + r;
        float lr, li, m00, m01, m10, m11;
        {
            uint4 gx[8], gw[4];
            const int grow = c * 256 + cb * 16 + warp * 2;
            uint32_t Lr_ = ldg16(p.lam_re + ch), Li_ = ldg16(p.lam_im + ch), Ldt_ = ldg16(p.log_dt + ch);
            uint32_t bz[4] = {0, 0, 0, 0};
            if (tw < 88) {
                const int J = tw >> 2;
                const __nv_bfloat16* src = (J < 6) ? p.b1 + 2048 + 192 * j8 + 32 * J
                                         : (J < 14) ? p.b1 + 256 * j8 + 32 * (J - 6)
                                         : (J < 18) ? p.dskip + colK + 32 * (J - 14) : p.b2 + colK + 32 * (J - 18);
#pragma unroll
                for (int jj = 0; jj < 4; ++jj) bz[jj] = ldg32(src + 8 * jj + 2 * (tw & 3));
            }
            uint2 gv0, gv1;
#pragma unroll
            for (int kb = 0; kb < 16; ++kb) {
                if (kb == 0) { KBLOCK_BEGIN(0, true, kb); STAMP(tid == 0, 1); } else { KBLOCK_BEGIN(0, false, kb); }
                if (kb == GATE_LD) {
#pragma unroll
                    for (int i = 0; i < 4; ++i) gw[i] = ldg128(p.gate_w + i * 256 + lane * 8);
#pragma unroll
                    for (int i = 0; i < 8; ++i) gx[i] = ldg128(p.x + (size_t)(grow + (i >> 2)) * kD + (i & 3) * 256 + lane * 8);
                }
                if (kb == GATE_LD + 3) {
                    float s0 = 0.f, s1 = 0.f;
#pragma unroll
                    for (int i = 0; i < 4; ++i) {
                        PIN_R(gw[i].x);
                        const uint32_t wv[4] = {gw[i].x, gw[i].y, gw[i].z, gw[i].w};
                        const uint32_t xa[4] = {gx[i].x, gx[i].y, gx[i].z, gx[i].w};
                        const uint32_t xb[4] = {gx[4 + i].x, gx[4 + i].y, gx[4 + i].z, gx[4 + i].w};
#pragma unroll
                        for (int k = 0; k < 4; ++k) {
                            const uint32_t pa = bf2_mul(xa[k], wv[k]), pb = bf2_mul(xb[k], wv[k]);
                            s0 += bf_lo(pa) + bf_hi(pa);
                            s1 += bf_lo(pb) + bf_hi(pb);
                        }
                    }
#pragma unroll
                    for (int o = 16; o > 0; o >>= 1) {
                        s0 += __shfl_xor_sync(0xffffffffu, s0, o);
                        s1 += __shfl_xor_sync(0xffffffffu, s1, o);
                    }
                    if (lane < 2) {
                        const float z = bf16_round(lane ? s1 : s0);
                        const float g = bf16_round(1.0f / (1.0f + expf(-z)));
                        st_relaxed64(&g_gate[grow + lane], __float_as_uint(g), tag);
                    }
                }
                if (kb == 1) {
                    PIN_R(Lr_); PIN_R(Li_); PIN_R(Ldt_);
                    const float Lr = bf_lo(Lr_), Li = bf_lo(Li_), Ldt = bf_lo(Ldt_);
                    const float dt = bf16_round(expf(Ldt));
                    const float ea = expf(dt * Lr);
                    float sn, cs;
                    sincospif((dt * Li) * 0.31830988618379067f, &sn, &cs);
                    lr = ea * cs; li = ea * sn;
                    const float nr = lr - 1.0f, ni = li;
                    float cr, ci;
                    if (fabsf(Lr) >= fabsf(Li)) {
                        const float t = Li / Lr, d = 1.0f / fmaf(Li, t, Lr);
                        cr = fmaf(ni, t, nr) * d; ci = fmaf(-nr, t, ni) * d;
                    } else {
                        const float t = Lr / Li, d = 1.0f / fmaf(Lr, t, Li);
                        cr = fmaf(nr, t, ni) * d; ci = fmaf(ni, t, -nr) * d;
                    }
                    if (p.swap) { li = -li; m00 = -2.f * ci; m01 = 2.f * cr; m10 = -2.f * cr; m11 = -2.f * ci; }
                    else { m00 = 2.f * cr; m01 = -2.f * ci; m10 = -2.f * ci; m11 = -2.f * cr; }
                    PIN_F(lr); PIN_F(li); PIN_F(m00); PIN_F(m01); PIN_F(m10); PIN_F(m11);
                }
                if (kb == 2) {
                    PIN_R(tag); tag += 1;
                    if (tw < 88) sts128(bias_s + tw * 16, bz[0], bz[1], bz[2], bz[3]);
                }
                if (kb == 12) {
                    gv0 = ld_relaxed64(&g_gate[c * 256 + tw]);
                    gv1 = ld_relaxed64(&g_gate[c * 256 + 128 + tw]);
                }
                if (kb == 14) {
                    unsigned n = 0;
                    while (gv0.y != tag || gv1.y != tag) {
                        if (++n > kSpinLimit) TRAP();
                        gv0 = ld_relaxed64(&g_gate[c * 256 + tw]);
                        gv1 = ld_relaxed64(&g_gate[c * 256 + 128 + tw]);
                    }
                    sts32(gate_s + ((tw >> 6) * 68 + (tw & 63)) * 4, gv0.x);
                    sts32(gate_s + ((2 + (tw >> 6)) * 68 + (tw & 63)) * 4, gv1.x);
                    __syncwarp();
                }
                if (kb == 15) { if (wg == 0) bar_sync<1, 128>(); else bar_sync<2, 128>(); }
                KBLOCK_END(kb);
            }
            wgmma_wait<0>();
            RELEASE_STAGE(3);
        }
        STAMP(tid == 0, 2); kt0 = 16;
#pragma unroll
        for (int s = 0; s < 64; ++s) pk[s] = pack_bf16_v(acc[4 * (s >> 1) + (s & 1)], acc[4 * (s >> 1) + 2 + (s & 1)]);

        {
            float hr = 0.f, hi = 0.f;
            float l64r, l64i, l128r, l128i;
            uint4 av0, av1;
            __nv_bfloat16* hs = g_Hs + (size_t)ch * 2048 + c * 256 + q * 8;
#pragma unroll
            for (int kb = 0; kb < 16; ++kb) {
                if (kb == 0) { KBLOCK_BEGIN(1, true, kb); } else { KBLOCK_BEGIN(1, false, kb); }
                if (kb < 4) {
#pragma unroll
                    for (int s = kb * 16; s < kb * 16 + 16; ++s) {
                        float nr = bf_lo(pk[s]), ni = bf_hi(pk[s]);
                        CFMA(nr, ni, lr, li, hr, hi);
                        hr = nr; hi = ni;
                    }
                    PIN_F(hr); PIN_F(hi);
                }
                if (kb == 0) {
                    l64r = lr; l64i = li;
#pragma unroll
                    for (int i = 0; i < 6; ++i) CMUL(l64r, l64i, l64r, l64i, l64r, l64i);
                    CMUL(l128r, l128i, l64r, l64i, l64r, l64i);
                    PIN_F(l64r); PIN_F(l64i); PIN_F(l128r); PIN_F(l128i);
                }
                if (kb == 3) {
                    float tr = __shfl_up_sync(0xffffffffu, hr, 1, 4), ti = __shfl_up_sync(0xffffffffu, hi, 1, 4);
                    if (q >= 1) CFMA(hr, hi, l64r, l64i, tr, ti);
                    tr = __shfl_up_sync(0xffffffffu, hr, 2, 4); ti = __shfl_up_sync(0xffffffffu, hi, 2, 4);
                    if (q >= 2) CFMA(hr, hi, l128r, l128i, tr, ti);
                    if (q == 3) st_relaxed2x64(&g_agg[c * 1024 + ch], __float_as_uint(hr), tag, __float_as_uint(hi), tag);
                    tr = __shfl_up_sync(0xffffffffu, hr, 1, 4); ti = __shfl_up_sync(0xffffffffu, hi, 1, 4);
                    hr = (q >= 1) ? tr : 0.f; hi = (q >= 1) ? ti : 0.f;
                }
                if (kb == 5) {
                    av0 = make_uint4(0, tag, 0, tag); av1 = av0;
                    if (q < c) av0 = ld_relaxed2x64(&g_agg[q * 1024 + ch]);
                    if (q + 4 < c) av1 = ld_relaxed2x64(&g_agg[(q + 4) * 1024 + ch]);
                }
                if (kb == 6) {
                    unsigned n = 0;
                    while (av0.y != tag || av0.w != tag || av1.y != tag || av1.w != tag) {
                        if (++n > kSpinLimit) TRAP();
                        if (q < c) av0 = ld_relaxed2x64(&g_agg[q * 1024 + ch]);
                        if (q + 4 < c) av1 = ld_relaxed2x64(&g_agg[(q + 4) * 1024 + ch]);
                    }
                    __syncwarp();
                    float l256r, l256i, l512r, l512i, l1kr, l1ki;
                    CMUL(l256r, l256i, l128r, l128i, l128r, l128i);
                    CMUL(l512r, l512i, l256r, l256i, l256r, l256i);
                    CMUL(l1kr, l1ki, l512r, l512i, l512r, l512i);
                    float vr = __uint_as_float(av0.x), vi = __uint_as_float(av0.z);
                    int n2 = c - 1 - q;
                    if (q + 4 < c) {
                        float ur = __uint_as_float(av1.x), ui = __uint_as_float(av1.z);
                        CFMA(ur, ui, l1kr, l1ki, vr, vi);
                        vr = ur; vi = ui; n2 -= 4;
                    }
                    if (n2 > 0 && (n2 & 1)) CMUL(vr, vi, vr, vi, l256r, l256i);
                    if (n2 > 0 && (n2 & 2)) CMUL(vr, vi, vr, vi, l512r, l512i);
                    vr += __shfl_xor_sync(0xffffffffu, vr, 1); vi += __shfl_xor_sync(0xffffffffu, vi, 1);
                    vr += __shfl_xor_sync(0xffffffffu, vr, 2); vi += __shfl_xor_sync(0xffffffffu, vi, 2);
                    if (q & 1) CMUL(vr, vi, vr, vi, l64r, l64i);
                    if (q & 2) CMUL(vr, vi, vr, vi, l128r, l128i);
                    hr += vr; hi += vi;
                    PIN_F(hr); PIN_F(hi);
                }
                if (kb >= 7 && kb < 15) {
                    const int i = kb - 7;
                    const uint4 ga = lds128(gate_s + (q * 68 + 8 * i) * 4), gb = lds128(gate_s + (q * 68 + 8 * i + 4) * 4);
                    const uint32_t gg[8] = {ga.x, ga.y, ga.z, ga.w, gb.x, gb.y, gb.z, gb.w};
                    float orr[8], oii[8];
#pragma unroll
                    for (int s = 0; s < 8; ++s) {
                        PIN_R(pk[8 * i + s]);
                        float nr = bf_lo(pk[8 * i + s]), ni = bf_hi(pk[8 * i + s]);
                        CFMA(nr, ni, lr, li, hr, hi);
                        hr = nr; hi = ni;
                        const float g = __uint_as_float(gg[s]);
                        orr[s] = fmaf(m00, hr, m01 * hi) * g;
                        oii[s] = fmaf(m10, hr, m11 * hi) * g;
                    }
                    stg128(hs + 32 * i, pack_bf16(orr[0], orr[1]), pack_bf16(orr[2], orr[3]), pack_bf16(orr[4], orr[5]), pack_bf16(orr[6], orr[7]));
                    stg128(hs + 1024 * 2048 + 32 * i, pack_bf16(oii[0], oii[1]), pack_bf16(oii[2], oii[3]), pack_bf16(oii[4], oii[5]), pack_bf16(oii[6], oii[7]));
                    if (kb == 14) bar_arrive<3, 320>();
                }
                KBLOCK_END(kb);
            }
            wgmma_wait<0>();
            RELEASE_STAGE(3);
        }
        STAMP(tid == 0, 3); kt0 = 32;
#pragma unroll
        for (int i = 0; i < 48; ++i) pk[i] = pack_bf16_v(acc[2 * i], acc[2 * i + 1]);

        const uint32_t gate_row = gate_s + ((2 * (w & 1)) * 68 + 8 * (4 * rank + 2 * wg + (w >> 1)) + r) * 4;
        uint32_t om0, om1;
        __nv_bfloat16* hf = g_Hf + (size_t)(rb * 128 + wg * 64 + w * 16 + r) * kF + q * 8;
#define FFN_SLICE(J, BIAS_ENTRY, F0)                                                                   \
    {                                                                                                  \
        const uint4 bv = lds128(bias_s + ((BIAS_ENTRY) * 4 + q) * 16);                                 \
        const uint32_t bb[4] = {bv.x, bv.y, bv.z, bv.w};                                               \
        uint32_t o0[4], o1[4];                                                                         \
        _Pragma("unroll") for (int jj = 0; jj < 4; ++jj) {                                             \
            const uint32_t r0 = bf2_add_relu(pk[8 * (J) + 2 * jj], bb[jj]), r1 = bf2_add_relu(pk[8 * (J) + 2 * jj + 1], bb[jj]); \
            o0[jj] = bf2_mul(bf2_mul(r0, r0), om0);                                                    \
            o1[jj] = bf2_mul(bf2_mul(r1, r1), om1);                                                    \
        }                                                                                              \
        stg128(hf + (F0) + 32 * (J), o0[0], o0[1], o0[2], o0[3]);                                      \
        stg128(hf + 8 * kF + (F0) + 32 * (J), o1[0], o1[1], o1[2], o1[3]);                             \
    }

        {
            const int f0 = 2048 + 192 * j8;
#pragma unroll
            for (int kb = 0; kb < 16; ++kb) {
                if (kb == 0) { KBLOCK_BEGIN(2, true, kb); } else { KBLOCK_BEGIN(2, false, kb); }
                if (kb == 0) {
                    const float a = 1.0f - lds32f(gate_row), b = 1.0f - lds32f(gate_row + 68 * 4);
                    om0 = pack_bf16(a, a); om1 = pack_bf16(b, b);
                }
                if (kb < 6) FFN_SLICE(kb, kb, f0);
                if (kb == 5) bar_arrive<4, 288>();
                KBLOCK_END(kb);
            }
            wgmma_wait<0>();
            RELEASE_STAGE(3);
        }
        STAMP(tid == 0, 4); kt0 = 48;
#pragma unroll
        for (int i = 0; i < 64; ++i) pk[i] = pack_bf16_v(acc[2 * i], acc[2 * i + 1]);

        float e[64];
        const int tb = c * 256 + 128 * (w & 1) + 8 * (4 * rank + 2 * wg + (w >> 1));
        {
            const int f0 = 256 * j8;
            const __nv_bfloat16* xr = p.x + (size_t)(tb + r) * kD + colK + 2 * q;
            uint32_t xv[32];
#pragma unroll
            for (int kb = 0; kb < 16; ++kb) {
                if (kb == 0) { KBLOCK_BEGIN(3, true, kb); } else { KBLOCK_BEGIN(3, false, kb); }
                if (kb < 8) FFN_SLICE(kb, 6 + kb, f0);
                if (kb == 7) bar_arrive<5, 288>();
                if (kb >= 8 && kb < 12) {
                    const int jb = (kb - 8) * 4;
#pragma unroll
                    for (int jj = 0; jj < 4; ++jj) {
                        xv[2 * (jb + jj)] = ldg32(xr + 8 * (jb + jj));
                        xv[2 * (jb + jj) + 1] = ldg32(xr + 64 * kD + 8 * (jb + jj));
                    }
                }
                if (kb >= 11 && kb < 15) {
                    const int jb = (kb - 11) * 4;
                    const float g0 = lds32f(gate_row), g1 = lds32f(gate_row + 68 * 4);
                    const float o0f = bf_lo(om0), o1f = bf_lo(om1);
                    const uint4 dq = lds128(bias_s + ((14 + kb - 11) * 4 + q) * 16), bq = lds128(bias_s + ((18 + kb - 11) * 4 + q) * 16);
                    const uint32_t dv[4] = {dq.x, dq.y, dq.z, dq.w}, bv2[4] = {bq.x, bq.y, bq.z, bq.w};
#pragma unroll
                    for (int jj = 0; jj < 4; ++jj) {
                        const uint32_t x0 = bf2_mul(xv[2 * (jb + jj)], dv[jj]), x1 = bf2_mul(xv[2 * (jb + jj) + 1], dv[jj]);
                        const float bl = bf_lo(bv2[jj]), bh = bf_hi(bv2[jj]);
                        e[4 * (jb + jj) + 0] = fmaf(g0, bf_lo(x0), o0f * bl);
                        e[4 * (jb + jj) + 1] = fmaf(g0, bf_hi(x0), o0f * bh);
                        e[4 * (jb + jj) + 2] = fmaf(g1, bf_lo(x1), o1f * bl);
                        e[4 * (jb + jj) + 3] = fmaf(g1, bf_hi(x1), o1f * bh);
                        PIN_F(e[4 * (jb + jj)]); PIN_F(e[4 * (jb + jj) + 1]); PIN_F(e[4 * (jb + jj) + 2]); PIN_F(e[4 * (jb + jj) + 3]);
                    }
                }
                KBLOCK_END(kb);
            }
        }
        STAMP(tid == 0, 5);
#pragma unroll 1
        for (int k4 = 0; k4 < kNF / 4; ++k4) {
#pragma unroll
            for (int s = 0; s < 4; ++s) {
                KT(64 + k4 * 4 + s, 0);
                mbar_wait(bar_full + 8 * s, k4 & 1);
                KT(64 + k4 * 4 + s, 1);
                wgmma_fence();
                mma_kblock<2, false>(acc, a_lo + s * (kStageBytes >> 4), b_lo + s * (kStageBytes >> 4));
                wgmma_commit();
                KT(64 + k4 * 4 + s, 2);
                wgmma_wait<1>();
                RELEASE_STAGE((s + 3) & 3);
            }
        }
        kt0 = 0;
#pragma unroll
        for (int it = 64 + (kNF & ~3); it < 64 + kNF; ++it) {
            KBLOCK_BEGIN(2, false, it);
            KBLOCK_END(it);
        }
        {
            const uint32_t xs = sbase + kABytes + 8192 + wg * 16384 + tw * 16;
            float xsc = 0.f;
#pragma unroll
            for (int kb = 0; kb < kTail; ++kb) {
                const int it = 64 + kNF + kb;
                KBLOCK_BEGIN(4, false, it);
                if (kb < kTail - 1) wgmma_wait<1>();
                if (it - 1 < kTotal - kStages) RELEASE_STAGE((it - 1) & 3);
                if (kb == 0) STAMP(tid == 0, 15);
                if (kb == 0) {
                    float m = 0.f;
#pragma unroll
                    for (int i = 64; i < 128; ++i) m = fmaxf(m, fabsf(acc[i]));
                    const uint32_t eb = max(__float_as_uint(m) >> 23, 15u);
                    xsc = __uint_as_float((268u - eb) << 23);
                    sts32(sbase + kScaleOff + tid * 4, (eb - 14u) << 23);
                }
                if (kb < 2) {
#pragma unroll
                    for (int i = 0; i < 4; ++i) {
                        const int v = 64 + 32 * kb + 8 * i;
                        sts128(xs + (it & 3) * kStageBytes + i * 2048, pack_f16(acc[v] * xsc, acc[v + 1] * xsc), pack_f16(acc[v + 2] * xsc, acc[v + 3] * xsc),
                               pack_f16(acc[v + 4] * xsc, acc[v + 5] * xsc), pack_f16(acc[v + 6] * xsc, acc[v + 7] * xsc));
                    }
                    asm volatile("fence.proxy.async.shared::cta;" ::: "memory");
                    __syncwarp();
                    if (lane == 0) mbar_arrive_local(bar_sent + 8 * kb);
                }
                if (kb == 3) { if (lane == 0) mbar_arrive_local(bar_sent + 16); }
                if (kb == kTail - 1) {
#pragma unroll
                    for (int j = 0; j < 2; ++j) {
                        mbar_wait(bar_recv + 8 * j, 0);
                        if (j == 0) xsc = lds32f(sbase + kScaleOff + 1024 + tid * 4);
#pragma unroll
                        for (int i = 0; i < 4; ++i) {
                            const uint4 rv = lds128(xs + ((64 + kNF + 2 + j) & 3) * kStageBytes + i * 2048);
                            const uint32_t rr[4] = {rv.x, rv.y, rv.z, rv.w};
#pragma unroll
                            for (int k = 0; k < 4; ++k) {
                                const int v = 32 * j + 8 * i + 2 * k;
                                const float2 f = __half22float2(*reinterpret_cast<const __half2*>(&rr[k]));
                                e[v] = fmaf(f.x, xsc, e[v]); e[v + 1] = fmaf(f.y, xsc, e[v + 1]);
                                PIN_F(e[v]); PIN_F(e[v + 1]);
                            }
                        }
                    }
                }
                KT(it, 2);
            }
        }
        wgmma_wait<0>();
        STAMP(tid == 0, 6);
        {
            const bool odd = q & 1;
            float* o0 = p.out + (size_t)(tb + r) * kD + colK + (odd ? 2 * q + 6 : 2 * q);
#pragma unroll
            for (int i = 0; i < 16; i += 2) {
#pragma unroll
                for (int h = 0; h < 2; ++h) {
                    const int va = 4 * i + 2 * h, vb = va + 4;
                    PIN_F(acc[va]); PIN_F(acc[va + 1]); PIN_F(acc[vb]); PIN_F(acc[vb + 1]);
                    const float a0 = acc[va] + e[va], a1 = acc[va + 1] + e[va + 1], b0 = acc[vb] + e[vb], b1 = acc[vb + 1] + e[vb + 1];
                    const float t0 = __shfl_xor_sync(0xffffffffu, odd ? a0 : b0, 1), t1 = __shfl_xor_sync(0xffffffffu, odd ? a1 : b1, 1);
                    stg128f(o0 + h * 64 * kD + 8 * i, odd ? t0 : a0, odd ? t1 : a1, odd ? b0 : t0, odd ? b1 : t1);
                }
            }
        }
        STAMP(tid == 0, 7);
    }
}

typedef CUresult (*EncodeFn)(CUtensorMap*, CUtensorMapDataType, cuuint32_t, void*, const cuuint64_t*, const cuuint64_t*,
                             const cuuint32_t*, const cuuint32_t*, CUtensorMapInterleave, CUtensorMapSwizzle,
                             CUtensorMapL2promotion, CUtensorMapFloatOOBfill);

bool encode(EncodeFn fn, CUtensorMap* m, const void* base, int rank, const cuuint64_t* dims, const cuuint64_t* strides,
            const cuuint32_t* box) {
    cuuint32_t es[5] = {1, 1, 1, 1, 1};
    return fn(m, CU_TENSOR_MAP_DATA_TYPE_BFLOAT16, rank, const_cast<void*>(base), dims, strides, box, es,
              CU_TENSOR_MAP_INTERLEAVE_NONE, CU_TENSOR_MAP_SWIZZLE_128B, CU_TENSOR_MAP_L2_PROMOTION_L2_256B,
              CU_TENSOR_MAP_FLOAT_OOB_FILL_NONE) == CUDA_SUCCESS;
}

}

extern "C" void kernel_launch(void* const* d_in, const int* in_sizes, int n_in, void* d_out, int out_size) {
    (void)in_sizes; (void)n_in; (void)out_size;
    typedef const __nv_bfloat16* bp;
    bp x = (bp)d_in[0], lam_re = (bp)d_in[1], lam_im = (bp)d_in[2], B_re = (bp)d_in[3], B_im = (bp)d_in[4];
    bp C_re = (bp)d_in[5], C_im = (bp)d_in[6], log_dt = (bp)d_in[7], dskip = (bp)d_in[8];
    bp w1 = (bp)d_in[10], b1 = (bp)d_in[11], w2 = (bp)d_in[12], b2 = (bp)d_in[13], gate_w = (bp)d_in[14];

    static EncodeFn fn = nullptr;
    static void *pHs = nullptr, *pHf = nullptr, *pBc = nullptr;
    if (!fn) {
        void* f = nullptr;
        cudaDriverEntryPointQueryResult qr;
        cudaGetDriverEntryPoint("cuTensorMapEncodeTiled", &f, cudaEnableDefault, &qr);
        fn = (EncodeFn)f;
        cudaGetSymbolAddress(&pHs, g_Hs);
        cudaGetSymbolAddress(&pHf, g_Hf);
        cudaGetSymbolAddress(&pBc, g_Bcopy);
        cudaFuncSetAttribute(fused_kernel, cudaFuncAttributeMaxDynamicSharedMemorySize, kSmemBytes);
    }
    cudaStream_t stream = cudaStreamPerThread;

    Params p;
    p.x = x; p.lam_re = lam_re; p.lam_im = lam_im; p.log_dt = log_dt; p.dskip = dskip; p.b1 = b1; p.b2 = b2;
    p.gate_w = gate_w; p.w1 = w1; p.w2 = w2; p.c_re = C_re; p.c_im = C_im; p.b_re = B_re; p.b_im = B_im; p.out = (float*)d_out;

    const char* lo = (const char*)B_re; const char* hi = (const char*)B_im;
    p.swap = 0;
    if (hi < lo) { const char* t = lo; lo = hi; hi = t; p.swap = 1; }
    unsigned long long diff = (unsigned long long)(hi - lo);
    if (diff >= (1ull << 40) || (diff & 15) || diff == 0) {
        cudaMemcpyAsync(pBc, B_re, 2u << 20, cudaMemcpyDeviceToDevice, stream);
        cudaMemcpyAsync((char*)pBc + (2u << 20), B_im, 2u << 20, cudaMemcpyDeviceToDevice, stream);
        lo = (const char*)pBc; diff = 2u << 20; p.swap = 0;
    }

    CUtensorMap mB, mXs, mXf, mW1a, mW1b, mHs, mHf, mCre, mCim, mW2;
    bool ok = true;
    { cuuint64_t d[4] = {1024, 8, 2, 128}, s[3] = {2048, diff, 16384}; cuuint32_t b[4] = {64, 8, 2, 8};
      ok &= encode(fn, &mB, lo, 4, d, s, b); }
    { cuuint64_t d[5] = {1024, 2, 4, 32, 8}, s[4] = {2048, 64 * 2048, 2 * 2048, 256 * 2048}; cuuint32_t b[5] = {64, 2, 4, 16, 1};
      ok &= encode(fn, &mXs, x, 5, d, s, b); }
    { cuuint64_t d[5] = {1024, 8, 4, 8, 8}, s[4] = {2048, 64 * 2048, 8 * 2048, 256 * 2048}; cuuint32_t b[5] = {64, 8, 4, 4, 1};
      ok &= encode(fn, &mXf, x, 5, d, s, b); }
    { cuuint64_t d[3] = {64, 1024, 56}, s[2] = {7168, 128}; cuuint32_t ba[3] = {64, 32, 4}, bb[3] = {64, 32, 3};
      ok &= encode(fn, &mW1a, w1, 3, d, s, ba); ok &= encode(fn, &mW1b, w1, 3, d, s, bb); }
    { cuuint64_t d[3] = {64, 2048, 32}, s[2] = {4096, 128}; cuuint32_t b[3] = {64, 64, 2};
      ok &= encode(fn, &mHs, pHs, 3, d, s, b); }
    { cuuint64_t d[2] = {3584, 2048}, s[1] = {7168}; cuuint32_t b[2] = {64, 128};
      ok &= encode(fn, &mHf, pHf, 2, d, s, b); }
    { cuuint64_t d[2] = {1024, 1024}, s[1] = {2048}; cuuint32_t b[2] = {64, 128};
      ok &= encode(fn, &mCre, C_re, 2, d, s, b); ok &= encode(fn, &mCim, C_im, 2, d, s, b); }
    { cuuint64_t d[5] = {64, 2, 448, 4, 16}, s[4] = {2048, 8 * 2048, 2 * 2048, 128}; cuuint32_t b[5] = {64, 2, 4, 4, 2};
      ok &= encode(fn, &mW2, w2, 5, d, s, b); }
    if (!ok) return;

    fused_kernel<<<128, 384, kSmemBytes, stream>>>(mB, mXs, mXf, mW1a, mW1b, mHs, mHf, mCre, mCim, mW2, p);
}
```

```cpp
#include <cuda_runtime.h>
#include <cuda_bf16.h>
#include <cuda_fp16.h>
#include <cuda.h>
#include <stdint.h>

#define MTAIL 8

#define XLDKB 8
#define XSND 0x01122233u
#define XLDK 0x44455566u
#define XUSE 0x66677777u

#define FIRSTN 1

#define PF0LINES 2

namespace {

constexpr int kD = 1024, kF = 3584;
constexpr int kStages = 4;
constexpr int kStageBytes = 49152;
constexpr int kABytes = 16384;
constexpr int kXOff = kStages * kStageBytes;
constexpr int kGateOff = kXOff + 32768;
constexpr int kBiasOff = kGateOff + 4 * 72 * 2;
constexpr int kBarOff = kBiasOff + 88 * 16;
constexpr int kSmemBytes = 232448;
static_assert(kBarOff + 128 <= kSmemBytes, "smem");
constexpr int kXBytes = 33792;
constexpr uint32_t kSmemOrg = 1024;
constexpr unsigned kSpinLimit = 1u << 22;
constexpr int kTail = MTAIL;
constexpr int kNA = (32 - kTail) / 2;
constexpr int kNF = 12 + kNA;
constexpr int kTotal = 64 + kNF + kTail;

__host__ __device__ constexpr int nib(unsigned v, int u) { return (int)((v >> (28 - 4 * u)) & 15u); }
__host__ __device__ constexpr int pass2_kb(int s) {
    return s < 4 ? 6 : s < 10 ? 7 : s < 18 ? 8 : s < 24 ? 9 : s < 30 ? 10 : s < 38 ? 11 : s < 44 ? 12 : s < 50 ? 13 : s < 58 ? 14 : 15;
}

__device__ __align__(1024) __nv_bfloat16 g_Hs[2048 * 2048];
__device__ __align__(1024) __nv_bfloat16 g_Hf[2048 * 3584];
__device__ __align__(1024) __nv_bfloat16 g_Bcopy[2 * 1024 * 1024];
__device__ uint4 g_agg[8 * 1024];
__device__ uint2 g_gate[2048];
__device__ unsigned g_cnt[40 * 32];
__device__ __align__(1024) uint8_t g_X[128 * kXBytes];
__device__ __align__(16) unsigned g_claim[64];
__device__ unsigned g_epoch;
__device__ unsigned g_done;

#define TRAP() break
#define PIN_F(x) asm volatile("" : "+f"(x))
#define PIN_R(x) asm volatile("" : "+r"(x))
__device__ __forceinline__ uint32_t smem_u32(const void* p) { return (uint32_t)__cvta_generic_to_shared(p); }
__device__ __forceinline__ void mbar_init(uint32_t bar, uint32_t count) {
    asm volatile("mbarrier.init.shared::cta.b64 [%0], %1;" ::"r"(bar), "r"(count) : "memory");
}
__device__ __forceinline__ void mbar_expect_tx(uint32_t bar, uint32_t bytes) {
    asm volatile("mbarrier.arrive.expect_tx.shared::cta.b64 _, [%0], %1;" ::"r"(bar), "r"(bytes) : "memory");
}
__device__ __forceinline__ void mbar_wait(uint32_t bar, uint32_t parity) {
    asm volatile(
        "{\n.reg .pred p;\n.reg .u32 n;\n"
        "mbarrier.try_wait.parity.shared::cta.b64 p, [%0], %1;\n"
        "@p bra DONE;\n"
        "mov.u32 n, 0;\n"
        "LOOP:\n"
        "mbarrier.try_wait.parity.shared::cta.b64 p, [%0], %1;\n"
        "@p bra DONE;\n"
        "add.u32 n, n, 1;\n"
        "setp.lt.u32 p, n, %2;\n"
        "@p bra LOOP;\n"
        "DONE:\n}\n"
        ::"r"(bar), "r"(parity), "n"(kSpinLimit) : "memory");
}
__device__ __forceinline__ void mbar_arrive_local(uint32_t bar) {
    asm volatile("mbarrier.arrive.shared::cta.b64 _, [%0];" ::"r"(bar) : "memory");
}
__device__ __forceinline__ void mbar_arrive_cluster(uint32_t cluster_addr) {
    asm volatile("mbarrier.arrive.shared::cluster.b64 _, [%0];" ::"r"(cluster_addr) : "memory");
}
__device__ __forceinline__ uint32_t mapa(uint32_t addr, uint32_t rank) {
    uint32_t r;
    asm("mapa.shared::cluster.u32 %0, %1, %2;" : "=r"(r) : "r"(addr), "r"(rank));
    return r;
}
__device__ __forceinline__ void cluster_arrive() { asm volatile("barrier.cluster.arrive.relaxed.aligned;" ::: "memory"); }
__device__ __forceinline__ void cluster_wait() { asm volatile("barrier.cluster.wait.acquire.aligned;" ::: "memory"); }
template <int ID, int N>
__device__ __forceinline__ void bar_sync() { asm volatile("bar.sync %0, %1;" ::"n"(ID), "n"(N) : "memory"); }
template <int ID, int N>
__device__ __forceinline__ void bar_arrive() { asm volatile("bar.arrive %0, %1;" ::"n"(ID), "n"(N) : "memory"); }

__device__ __forceinline__ void tma2(uint32_t dst, const CUtensorMap* m, uint32_t bar, int c0, int c1) {
    asm volatile("cp.async.bulk.tensor.2d.shared::cluster.global.mbarrier::complete_tx::bytes [%0], [%1, {%3, %4}], [%2];"
                 ::"r"(dst), "l"(m), "r"(bar), "r"(c0), "r"(c1) : "memory");
}
__device__ __forceinline__ void tma3(uint32_t dst, const CUtensorMap* m, uint32_t bar, int c0, int c1, int c2) {
    asm volatile("cp.async.bulk.tensor.3d.shared::cluster.global.mbarrier::complete_tx::bytes [%0], [%1, {%3, %4, %5}], [%2];"
                 ::"r"(dst), "l"(m), "r"(bar), "r"(c0), "r"(c1), "r"(c2) : "memory");
}
__device__ __forceinline__ void tma4(uint32_t dst, const CUtensorMap* m, uint32_t bar, int c0, int c1, int c2, int c3) {
    asm volatile("cp.async.bulk.tensor.4d.shared::cluster.global.mbarrier::complete_tx::bytes [%0], [%1, {%3, %4, %5, %6}], [%2];"
                 ::"r"(dst), "l"(m), "r"(bar), "r"(c0), "r"(c1), "r"(c2), "r"(c3) : "memory");
}
__device__ __forceinline__ void tma5(uint32_t dst, const CUtensorMap* m, uint32_t bar, int c0, int c1, int c2, int c3, int c4) {
    asm volatile("cp.async.bulk.tensor.5d.shared::cluster.global.mbarrier::complete_tx::bytes [%0], [%1, {%3, %4, %5, %6, %7}], [%2];"
                 ::"r"(dst), "l"(m), "r"(bar), "r"(c0), "r"(c1), "r"(c2), "r"(c3), "r"(c4) : "memory");
}
__device__ __forceinline__ void tma2_mc(uint32_t dst, const CUtensorMap* m, uint32_t bar, int c0, int c1) {
    asm volatile("cp.async.bulk.tensor.2d.shared::cluster.global.mbarrier::complete_tx::bytes.multicast::cluster [%0], [%1, {%3, %4}], [%2], %5;"
                 ::"r"(dst), "l"(m), "r"(bar), "r"(c0), "r"(c1), "h"((uint16_t)3) : "memory");
}
__device__ __forceinline__ void tma3_mc(uint32_t dst, const CUtensorMap* m, uint32_t bar, int c0, int c1, int c2) {
    asm volatile("cp.async.bulk.tensor.3d.shared::cluster.global.mbarrier::complete_tx::bytes.multicast::cluster [%0], [%1, {%3, %4, %5}], [%2], %6;"
                 ::"r"(dst), "l"(m), "r"(bar), "r"(c0), "r"(c1), "r"(c2), "h"((uint16_t)3) : "memory");
}
__device__ __forceinline__ void tma5_mc(uint32_t dst, const CUtensorMap* m, uint32_t bar, int c0, int c1, int c2, int c3, int c4) {
    asm volatile("cp.async.bulk.tensor.5d.shared::cluster.global.mbarrier::complete_tx::bytes.multicast::cluster [%0], [%1, {%3, %4, %5, %6, %7}], [%2], %8;"
                 ::"r"(dst), "l"(m), "r"(bar), "r"(c0), "r"(c1), "r"(c2), "r"(c3), "r"(c4), "h"((uint16_t)3) : "memory");
}
__device__ __forceinline__ void bulk_store(void* dst, uint32_t src, uint32_t bytes) {
    asm volatile("cp.async.bulk.global.shared::cta.bulk_group [%0], [%1], %2;" ::"l"(dst), "r"(src), "r"(bytes) : "memory");
}
__device__ __forceinline__ void bulk_load(uint32_t dst, const void* src, uint32_t bytes, uint32_t bar) {
    asm volatile("cp.async.bulk.shared::cluster.global.mbarrier::complete_tx::bytes [%0], [%1], %2, [%3];"
                 ::"r"(dst), "l"(src), "r"(bytes), "r"(bar) : "memory");
}
__device__ __forceinline__ unsigned atom_exch(unsigned* p, unsigned v) {
    unsigned r;
    asm volatile("atom.relaxed.gpu.global.exch.b32 %0, [%1], %2;" : "=r"(r) : "l"(p), "r"(v) : "memory");
    return r;
}
__device__ __forceinline__ uint32_t lds32_cluster(uint32_t a) {
    uint32_t v;
    asm volatile("ld.shared::cluster.u32 %0, [%1];" : "=r"(v) : "r"(a) : "memory");
    return v;
}
__device__ __forceinline__ void sts128f(uint32_t a, float x, float y, float z, float w) {
    asm volatile("st.shared.v4.f32 [%0], {%1, %2, %3, %4};" ::"r"(a), "f"(x), "f"(y), "f"(z), "f"(w) : "memory");
}
__device__ __forceinline__ void prefetch_map(const CUtensorMap* m) {
    asm volatile("prefetch.tensormap [%0];" ::"l"(m) : "memory");
}

__device__ __forceinline__ void prefetch_l2(const void* p, uint32_t bytes) {
    asm volatile("cp.async.bulk.prefetch.L2.global [%0], %1;" ::"l"(p), "r"(bytes) : "memory");
}

__device__ __forceinline__ void wgmma_fence() { asm volatile("wgmma.fence.sync.aligned;" ::: "memory"); }
__device__ __forceinline__ void wgmma_commit() { asm volatile("wgmma.commit_group.sync.aligned;" ::: "memory"); }
template <int N>
__device__ __forceinline__ void wgmma_wait() { asm volatile("wgmma.wait_group.sync.aligned %0;" ::"n"(N) : "memory"); }

__device__ __forceinline__ uint32_t pack_bf16(float lo, float hi) {
    uint32_t r;
    asm("cvt.rn.bf16x2.f32 %0, %1, %2;" : "=r"(r) : "f"(hi), "f"(lo));
    return r;
}
__device__ __forceinline__ uint32_t pack_f16(float lo, float hi) {
    uint32_t r;
    asm("cvt.rn.f16x2.f32 %0, %1, %2;" : "=r"(r) : "f"(hi), "f"(lo));
    return r;
}
__device__ __forceinline__ uint32_t pack_bf16_v(float lo, float hi) {
    uint32_t r;
    asm volatile("cvt.rn.bf16x2.f32 %0, %1, %2;" : "=r"(r) : "f"(hi), "f"(lo));
    return r;
}
__device__ __forceinline__ float bf_lo(uint32_t v) { return __uint_as_float(v << 16); }
__device__ __forceinline__ float bf_hi(uint32_t v) { return __uint_as_float(v & 0xffff0000u); }
__device__ __forceinline__ float bf16_round(float v) { return __bfloat162float(__float2bfloat16_rn(v)); }
__device__ __forceinline__ uint32_t bf2_mul(uint32_t a, uint32_t b) {
    uint32_t r;
    asm("mul.rn.bf16x2 %0, %1, %2;" : "=r"(r) : "r"(a), "r"(b));
    return r;
}
__device__ __forceinline__ uint32_t bf2_add_relu(uint32_t a, uint32_t b) {
    uint32_t r;
    asm("fma.rn.relu.bf16x2 %0, %1, %2, %3;" : "=r"(r) : "r"(a), "r"(0x3f803f80u), "r"(b));
    return r;
}
__device__ __forceinline__ uint4 ldg128(const void* p) {
    uint4 v;
    asm volatile("ld.global.nc.v4.u32 {%0, %1, %2, %3}, [%4];" : "=r"(v.x), "=r"(v.y), "=r"(v.z), "=r"(v.w) : "l"(p));
    return v;
}
__device__ __forceinline__ uint32_t ldg32(const void* p) {
    uint32_t v;
    asm volatile("ld.global.nc.u32 %0, [%1];" : "=r"(v) : "l"(p));
    return v;
}
__device__ __forceinline__ uint32_t ldg32na(const void* p) {
    uint32_t v;
    asm volatile("ld.global.nc.L1::no_allocate.u32 %0, [%1];" : "=r"(v) : "l"(p));
    return v;
}
__device__ __forceinline__ uint32_t ldg16(const __nv_bfloat16* p) {
    uint32_t v;
    asm volatile("ld.global.nc.u16 %0, [%1];" : "=r"(v) : "l"(p));
    return v;
}
__device__ __forceinline__ uint4 ld_relaxed128(const void* p) {
    uint4 v;
    asm volatile("ld.relaxed.gpu.global.v4.u32 {%0, %1, %2, %3}, [%4];" : "=r"(v.x), "=r"(v.y), "=r"(v.z), "=r"(v.w) : "l"(p) : "memory");
    return v;
}
__device__ __forceinline__ uint2 ld_relaxed64(const void* p) {
    unsigned long long v;
    asm volatile("ld.relaxed.gpu.global.u64 %0, [%1];" : "=l"(v) : "l"(p) : "memory");
    return make_uint2((uint32_t)v, (uint32_t)(v >> 32));
}
__device__ __forceinline__ void st_relaxed64(void* p, uint32_t lo, uint32_t hi) {
    unsigned long long v = ((unsigned long long)hi << 32) | lo;
    asm volatile("st.relaxed.gpu.global.u64 [%0], %1;" ::"l"(p), "l"(v) : "memory");
}
__device__ __forceinline__ void st_relaxed2x64(void* p, uint32_t a, uint32_t b, uint32_t c, uint32_t d) {
    unsigned long long v0 = ((unsigned long long)b << 32) | a, v1 = ((unsigned long long)d << 32) | c;
    asm volatile("st.relaxed.gpu.global.v2.u64 [%0], {%1, %2};" ::"l"(p), "l"(v0), "l"(v1) : "memory");
}
__device__ __forceinline__ uint4 ld_relaxed2x64(const void* p) {
    unsigned long long v0, v1;
    asm volatile("ld.relaxed.gpu.global.v2.u64 {%0, %1}, [%2];" : "=l"(v0), "=l"(v1) : "l"(p) : "memory");
    return make_uint4((uint32_t)v0, (uint32_t)(v0 >> 32), (uint32_t)v1, (uint32_t)(v1 >> 32));
}
__device__ __forceinline__ void stg128(void* p, uint32_t a, uint32_t b, uint32_t c, uint32_t d) {
    asm volatile("st.global.v4.u32 [%0], {%1, %2, %3, %4};" ::"l"(p), "r"(a), "r"(b), "r"(c), "r"(d) : "memory");
}
__device__ __forceinline__ void stg64f(void* p, float a, float b) {
    asm volatile("st.global.v2.f32 [%0], {%1, %2};" ::"l"(p), "f"(a), "f"(b) : "memory");
}
__device__ __forceinline__ uint4 lds128(uint32_t a) {
    uint4 v;
    asm volatile("ld.shared.v4.u32 {%0, %1, %2, %3}, [%4];" : "=r"(v.x), "=r"(v.y), "=r"(v.z), "=r"(v.w) : "r"(a) : "memory");
    return v;
}
__device__ __forceinline__ uint2 lds64(uint32_t a) {
    uint2 v;
    asm volatile("ld.shared.v2.u32 {%0, %1}, [%2];" : "=r"(v.x), "=r"(v.y) : "r"(a) : "memory");
    return v;
}
__device__ __forceinline__ uint4 ldsm4(uint32_t a) {
    uint4 v;
    asm volatile("ldmatrix.sync.aligned.m8n8.x4.shared.b16 {%0, %1, %2, %3}, [%4];" : "=r"(v.x), "=r"(v.y), "=r"(v.z), "=r"(v.w) : "r"(a) : "memory");
    return v;
}
__device__ __forceinline__ uint32_t lds16(uint32_t a) {
    uint32_t v;
    asm volatile("ld.shared.u16 %0, [%1];" : "=r"(v) : "r"(a) : "memory");
    return v;
}
__device__ __forceinline__ void sts16(uint32_t a, uint32_t x) {
    asm volatile("st.shared.u16 [%0], %1;" ::"r"(a), "h"((uint16_t)x) : "memory");
}
__device__ __forceinline__ void st_relaxed32(void* p, uint32_t v) {
    asm volatile("st.relaxed.gpu.global.u32 [%0], %1;" ::"l"(p), "r"(v) : "memory");
}
__device__ __forceinline__ float lds32f(uint32_t a) {
    float v;
    asm volatile("ld.shared.f32 %0, [%1];" : "=f"(v) : "r"(a) : "memory");
    return v;
}
__device__ __forceinline__ void sts128(uint32_t a, uint32_t x, uint32_t y, uint32_t z, uint32_t w) {
    asm volatile("st.shared.v4.u32 [%0], {%1, %2, %3, %4};" ::"r"(a), "r"(x), "r"(y), "r"(z), "r"(w) : "memory");
}
__device__ __forceinline__ void sts32(uint32_t a, uint32_t x) {
    asm volatile("st.shared.u32 [%0], %1;" ::"r"(a), "r"(x) : "memory");
}
__device__ __forceinline__ void stg128f(void* p, float a, float b, float c, float d) {
    asm volatile("st.global.v4.f32 [%0], {%1, %2, %3, %4};" ::"l"(p), "f"(a), "f"(b), "f"(c), "f"(d) : "memory");
}
__device__ __forceinline__ unsigned ld_relaxed32(const unsigned* p) {
    unsigned v;
    asm volatile("ld.relaxed.gpu.global.u32 %0, [%1];" : "=r"(v) : "l"(p) : "memory");
    return v;
}
__device__ __forceinline__ void wait_counter(const unsigned* p, unsigned target) {
    unsigned n = 0, v;
    while (true) {
        asm volatile("ld.acquire.gpu.global.u32 %0, [%1];" : "=r"(v) : "l"(p) : "memory");
        if ((int)(v - target) >= 0) break;
        if (++n > kSpinLimit) TRAP();
        __nanosleep(32);
    }
}
#define KT(IT, W) do { } while (0)
#define STAMP(cond, slot) do { } while (0)

template <int TA, int TB>
__device__ __forceinline__ void wgmma_n256(float (&d)[128], uint64_t da, uint64_t db) {
    asm volatile(
        "{\n.reg .pred p;\nsetp.ne.b32 p, 1, 0;\n"
        "wgmma.mma_async.sync.aligned.m64n256k16.f32.bf16.bf16 "
        "{%0, %1, %2, %3, %4, %5, %6, %7, %8, %9, %10, %11, %12, %13, %14, %15, "
        "%16, %17, %18, %19, %20, %21, %22, %23, %24, %25, %26, %27, %28, %29, %30, %31, "
        "%32, %33, %34, %35, %36, %37, %38, %39, %40, %41, %42, %43, %44, %45, %46, %47, "
        "%48, %49, %50, %51, %52, %53, %54, %55, %56, %57, %58, %59, %60, %61, %62, %63, "
        "%64, %65, %66, %67, %68, %69, %70, %71, %72, %73, %74, %75, %76, %77, %78, %79, "
        "%80, %81, %82, %83, %84, %85, %86, %87, %88, %89, %90, %91, %92, %93, %94, %95, "
        "%96, %97, %98, %99, %100, %101, %102, %103, %104, %105, %106, %107, %108, %109, %110, %111, "
        "%112, %113, %114, %115, %116, %117, %118, %119, %120, %121, %122, %123, %124, %125, %126, %127}, "
        "%128, %129, p, 1, 1, %130, %131;\n}\n"
        : "+f"(d[0]), "+f"(d[1]), "+f"(d[2]), "+f"(d[3]), "+f"(d[4]), "+f"(d[5]), "+f"(d[6]), "+f"(d[7]),
          "+f"(d[8]), "+f"(d[9]), "+f"(d[10]), "+f"(d[11]), "+f"(d[12]), "+f"(d[13]), "+f"(d[14]), "+f"(d[15]),
          "+f"(d[16]), "+f"(d[17]), "+f"(d[18]), "+f"(d[19]), "+f"(d[20]), "+f"(d[21]), "+f"(d[22]), "+f"(d[23]),
          "+f"(d[24]), "+f"(d[25]), "+f"(d[26]), "+f"(d[27]), "+f"(d[28]), "+f"(d[29]), "+f"(d[30]), "+f"(d[31]),
          "+f"(d[32]), "+f"(d[33]), "+f"(d[34]), "+f"(d[35]), "+f"(d[36]), "+f"(d[37]), "+f"(d[38]), "+f"(d[39]),
          "+f"(d[40]), "+f"(d[41]), "+f"(d[42]), "+f"(d[43]), "+f"(d[44]), "+f"(d[45]), "+f"(d[46]), "+f"(d[47]),
          "+f"(d[48]), "+f"(d[49]), "+f"(d[50]), "+f"(d[51]), "+f"(d[52]), "+f"(d[53]), "+f"(d[54]), "+f"(d[55]),
          "+f"(d[56]), "+f"(d[57]), "+f"(d[58]), "+f"(d[59]), "+f"(d[60]), "+f"(d[61]), "+f"(d[62]), "+f"(d[63]),
          "+f"(d[64]), "+f"(d[65]), "+f"(d[66]), "+f"(d[67]), "+f"(d[68]), "+f"(d[69]), "+f"(d[70]), "+f"(d[71]),
          "+f"(d[72]), "+f"(d[73]), "+f"(d[74]), "+f"(d[75]), "+f"(d[76]), "+f"(d[77]), "+f"(d[78]), "+f"(d[79]),
          "+f"(d[80]), "+f"(d[81]), "+f"(d[82]), "+f"(d[83]), "+f"(d[84]), "+f"(d[85]), "+f"(d[86]), "+f"(d[87]),
          "+f"(d[88]), "+f"(d[89]), "+f"(d[90]), "+f"(d[91]), "+f"(d[92]), "+f"(d[93]), "+f"(d[94]), "+f"(d[95]),
          "+f"(d[96]), "+f"(d[97]), "+f"(d[98]), "+f"(d[99]), "+f"(d[100]), "+f"(d[101]), "+f"(d[102]), "+f"(d[103]),
          "+f"(d[104]), "+f"(d[105]), "+f"(d[106]), "+f"(d[107]), "+f"(d[108]), "+f"(d[109]), "+f"(d[110]), "+f"(d[111]),
          "+f"(d[112]), "+f"(d[113]), "+f"(d[114]), "+f"(d[115]), "+f"(d[116]), "+f"(d[117]), "+f"(d[118]), "+f"(d[119]),
          "+f"(d[120]), "+f"(d[121]), "+f"(d[122]), "+f"(d[123]), "+f"(d[124]), "+f"(d[125]), "+f"(d[126]), "+f"(d[127])
        : "l"(da), "l"(db), "n"(TA), "n"(TB));
}
template <int TA, int TB>
__device__ __forceinline__ void wgmma_n256_first(float (&d)[128], uint64_t da, uint64_t db) {
    asm volatile(
        "{\n.reg .pred p;\nsetp.ne.b32 p, 0, 0;\n"
        "wgmma.mma_async.sync.aligned.m64n256k16.f32.bf16.bf16 "
        "{%0, %1, %2, %3, %4, %5, %6, %7, %8, %9, %10, %11, %12, %13, %14, %15, "
        "%16, %17, %18, %19, %20, %21, %22, %23, %24, %25, %26, %27, %28, %29, %30, %31, "
        "%32, %33, %34, %35, %36, %37, %38, %39, %40, %41, %42, %43, %44, %45, %46, %47, "
        "%48, %49, %50, %51, %52, %53, %54, %55, %56, %57, %58, %59, %60, %61, %62, %63, "
        "%64, %65, %66, %67, %68, %69, %70, %71, %72, %73, %74, %75, %76, %77, %78, %79, "
        "%80, %81, %82, %83, %84, %85, %86, %87, %88, %89, %90, %91, %92, %93, %94, %95, "
        "%96, %97, %98, %99, %100, %101, %102, %103, %104, %105, %106, %107, %108, %109, %110, %111, "
        "%112, %113, %114, %115, %116, %117, %118, %119, %120, %121, %122, %123, %124, %125, %126, %127}, "
        "%128, %129, p, 1, 1, %130, %131;\n}\n"
        : "=f"(d[0]), "=f"(d[1]), "=f"(d[2]), "=f"(d[3]), "=f"(d[4]), "=f"(d[5]), "=f"(d[6]), "=f"(d[7]),
          "=f"(d[8]), "=f"(d[9]), "=f"(d[10]), "=f"(d[11]), "=f"(d[12]), "=f"(d[13]), "=f"(d[14]), "=f"(d[15]),
          "=f"(d[16]), "=f"(d[17]), "=f"(d[18]), "=f"(d[19]), "=f"(d[20]), "=f"(d[21]), "=f"(d[22]), "=f"(d[23]),
          "=f"(d[24]), "=f"(d[25]), "=f"(d[26]), "=f"(d[27]), "=f"(d[28]), "=f"(d[29]), "=f"(d[30]), "=f"(d[31]),
          "=f"(d[32]), "=f"(d[33]), "=f"(d[34]), "=f"(d[35]), "=f"(d[36]), "=f"(d[37]), "=f"(d[38]), "=f"(d[39]),
          "=f"(d[40]), "=f"(d[41]), "=f"(d[42]), "=f"(d[43]), "=f"(d[44]), "=f"(d[45]), "=f"(d[46]), "=f"(d[47]),
          "=f"(d[48]), "=f"(d[49]), "=f"(d[50]), "=f"(d[51]), "=f"(d[52]), "=f"(d[53]), "=f"(d[54]), "=f"(d[55]),
          "=f"(d[56]), "=f"(d[57]), "=f"(d[58]), "=f"(d[59]), "=f"(d[60]), "=f"(d[61]), "=f"(d[62]), "=f"(d[63]),
          "=f"(d[64]), "=f"(d[65]), "=f"(d[66]), "=f"(d[67]), "=f"(d[68]), "=f"(d[69]), "=f"(d[70]), "=f"(d[71]),
          "=f"(d[72]), "=f"(d[73]), "=f"(d[74]), "=f"(d[75]), "=f"(d[76]), "=f"(d[77]), "=f"(d[78]), "=f"(d[79]),
          "=f"(d[80]), "=f"(d[81]), "=f"(d[82]), "=f"(d[83]), "=f"(d[84]), "=f"(d[85]), "=f"(d[86]), "=f"(d[87]),
          "=f"(d[88]), "=f"(d[89]), "=f"(d[90]), "=f"(d[91]), "=f"(d[92]), "=f"(d[93]), "=f"(d[94]), "=f"(d[95]),
          "=f"(d[96]), "=f"(d[97]), "=f"(d[98]), "=f"(d[99]), "=f"(d[100]), "=f"(d[101]), "=f"(d[102]), "=f"(d[103]),
          "=f"(d[104]), "=f"(d[105]), "=f"(d[106]), "=f"(d[107]), "=f"(d[108]), "=f"(d[109]), "=f"(d[110]), "=f"(d[111]),
          "=f"(d[112]), "=f"(d[113]), "=f"(d[114]), "=f"(d[115]), "=f"(d[116]), "=f"(d[117]), "=f"(d[118]), "=f"(d[119]),
          "=f"(d[120]), "=f"(d[121]), "=f"(d[122]), "=f"(d[123]), "=f"(d[124]), "=f"(d[125]), "=f"(d[126]), "=f"(d[127])
        : "l"(da), "l"(db), "n"(TA), "n"(TB));
}
template <int TA, int TB>
__device__ __forceinline__ void wgmma_n192(float (&d)[128], uint64_t da, uint64_t db) {
    asm volatile(
        "{\n.reg .pred p;\nsetp.ne.b32 p, 1, 0;\n"
        "wgmma.mma_async.sync.aligned.m64n192k16.f32.bf16.bf16 "
        "{%0, %1, %2, %3, %4, %5, %6, %7, %8, %9, %10, %11, %12, %13, %14, %15, "
        "%16, %17, %18, %19, %20, %21, %22, %23, %24, %25, %26, %27, %28, %29, %30, %31, "
        "%32, %33, %34, %35, %36, %37, %38, %39, %40, %41, %42, %43, %44, %45, %46, %47, "
        "%48, %49, %50, %51, %52, %53, %54, %55, %56, %57, %58, %59, %60, %61, %62, %63, "
        "%64, %65, %66, %67, %68, %69, %70, %71, %72, %73, %74, %75, %76, %77, %78, %79, "
        "%80, %81, %82, %83, %84, %85, %86, %87, %88, %89, %90, %91, %92, %93, %94, %95}, "
        "%96, %97, p, 1, 1, %98, %99;\n}\n"
        : "+f"(d[0]), "+f"(d[1]), "+f"(d[2]), "+f"(d[3]), "+f"(d[4]), "+f"(d[5]), "+f"(d[6]), "+f"(d[7]),
          "+f"(d[8]), "+f"(d[9]), "+f"(d[10]), "+f"(d[11]), "+f"(d[12]), "+f"(d[13]), "+f"(d[14]), "+f"(d[15]),
          "+f"(d[16]), "+f"(d[17]), "+f"(d[18]), "+f"(d[19]), "+f"(d[20]), "+f"(d[21]), "+f"(d[22]), "+f"(d[23]),
          "+f"(d[24]), "+f"(d[25]), "+f"(d[26]), "+f"(d[27]), "+f"(d[28]), "+f"(d[29]), "+f"(d[30]), "+f"(d[31]),
          "+f"(d[32]), "+f"(d[33]), "+f"(d[34]), "+f"(d[35]), "+f"(d[36]), "+f"(d[37]), "+f"(d[38]), "+f"(d[39]),
          "+f"(d[40]), "+f"(d[41]), "+f"(d[42]), "+f"(d[43]), "+f"(d[44]), "+f"(d[45]), "+f"(d[46]), "+f"(d[47]),
          "+f"(d[48]), "+f"(d[49]), "+f"(d[50]), "+f"(d[51]), "+f"(d[52]), "+f"(d[53]), "+f"(d[54]), "+f"(d[55]),
          "+f"(d[56]), "+f"(d[57]), "+f"(d[58]), "+f"(d[59]), "+f"(d[60]), "+f"(d[61]), "+f"(d[62]), "+f"(d[63]),
          "+f"(d[64]), "+f"(d[65]), "+f"(d[66]), "+f"(d[67]), "+f"(d[68]), "+f"(d[69]), "+f"(d[70]), "+f"(d[71]),
          "+f"(d[72]), "+f"(d[73]), "+f"(d[74]), "+f"(d[75]), "+f"(d[76]), "+f"(d[77]), "+f"(d[78]), "+f"(d[79]),
          "+f"(d[80]), "+f"(d[81]), "+f"(d[82]), "+f"(d[83]), "+f"(d[84]), "+f"(d[85]), "+f"(d[86]), "+f"(d[87]),
          "+f"(d[88]), "+f"(d[89]), "+f"(d[90]), "+f"(d[91]), "+f"(d[92]), "+f"(d[93]), "+f"(d[94]), "+f"(d[95])
        : "l"(da), "l"(db), "n"(TA), "n"(TB));
}
template <int TA, int TB>
__device__ __forceinline__ void wgmma_n192_first(float (&d)[128], uint64_t da, uint64_t db) {
    asm volatile(
        "{\n.reg .pred p;\nsetp.ne.b32 p, 0, 0;\n"
        "wgmma.mma_async.sync.aligned.m64n192k16.f32.bf16.bf16 "
        "{%0, %1, %2, %3, %4, %5, %6, %7, %8, %9, %10, %11, %12, %13, %14, %15, "
        "%16, %17, %18, %19, %20, %21, %22, %23, %24, %25, %26, %27, %28, %29, %30, %31, "
        "%32, %33, %34, %35, %36, %37, %38, %39, %40, %41, %42, %43, %44, %45, %46, %47, "
        "%48, %49, %50, %51, %52, %53, %54, %55, %56, %57, %58, %59, %60, %61, %62, %63, "
        "%64, %65, %66, %67, %68, %69, %70, %71, %72, %73, %74, %75, %76, %77, %78, %79, "
        "%80, %81, %82, %83, %84, %85, %86, %87, %88, %89, %90, %91, %92, %93, %94, %95}, "
        "%96, %97, p, 1, 1, %98, %99;\n}\n"
        : "=f"(d[0]), "=f"(d[1]), "=f"(d[2]), "=f"(d[3]), "=f"(d[4]), "=f"(d[5]), "=f"(d[6]), "=f"(d[7]),
          "=f"(d[8]), "=f"(d[9]), "=f"(d[10]), "=f"(d[11]), "=f"(d[12]), "=f"(d[13]), "=f"(d[14]), "=f"(d[15]),
          "=f"(d[16]), "=f"(d[17]), "=f"(d[18]), "=f"(d[19]), "=f"(d[20]), "=f"(d[21]), "=f"(d[22]), "=f"(d[23]),
          "=f"(d[24]), "=f"(d[25]), "=f"(d[26]), "=f"(d[27]), "=f"(d[28]), "=f"(d[29]), "=f"(d[30]), "=f"(d[31]),
          "=f"(d[32]), "=f"(d[33]), "=f"(d[34]), "=f"(d[35]), "=f"(d[36]), "=f"(d[37]), "=f"(d[38]), "=f"(d[39]),
          "=f"(d[40]), "=f"(d[41]), "=f"(d[42]), "=f"(d[43]), "=f"(d[44]), "=f"(d[45]), "=f"(d[46]), "=f"(d[47]),
          "=f"(d[48]), "=f"(d[49]), "=f"(d[50]), "=f"(d[51]), "=f"(d[52]), "=f"(d[53]), "=f"(d[54]), "=f"(d[55]),
          "=f"(d[56]), "=f"(d[57]), "=f"(d[58]), "=f"(d[59]), "=f"(d[60]), "=f"(d[61]), "=f"(d[62]), "=f"(d[63]),
          "=f"(d[64]), "=f"(d[65]), "=f"(d[66]), "=f"(d[67]), "=f"(d[68]), "=f"(d[69]), "=f"(d[70]), "=f"(d[71]),
          "=f"(d[72]), "=f"(d[73]), "=f"(d[74]), "=f"(d[75]), "=f"(d[76]), "=f"(d[77]), "=f"(d[78]), "=f"(d[79]),
          "=f"(d[80]), "=f"(d[81]), "=f"(d[82]), "=f"(d[83]), "=f"(d[84]), "=f"(d[85]), "=f"(d[86]), "=f"(d[87]),
          "=f"(d[88]), "=f"(d[89]), "=f"(d[90]), "=f"(d[91]), "=f"(d[92]), "=f"(d[93]), "=f"(d[94]), "=f"(d[95])
        : "l"(da), "l"(db), "n"(TA), "n"(TB));
}
template <int TA, int TB>
__device__ __forceinline__ void wgmma_n128(float (&d)[128], uint64_t da, uint64_t db) {
    asm volatile(
        "{\n.reg .pred p;\nsetp.ne.b32 p, 1, 0;\n"
        "wgmma.mma_async.sync.aligned.m64n128k16.f32.bf16.bf16 "
        "{%0, %1, %2, %3, %4, %5, %6, %7, %8, %9, %10, %11, %12, %13, %14, %15, "
        "%16, %17, %18, %19, %20, %21, %22, %23, %24, %25, %26, %27, %28, %29, %30, %31, "
        "%32, %33, %34, %35, %36, %37, %38, %39, %40, %41, %42, %43, %44, %45, %46, %47, "
        "%48, %49, %50, %51, %52, %53, %54, %55, %56, %57, %58, %59, %60, %61, %62, %63}, "
        "%64, %65, p, 1, 1, %66, %67;\n}\n"
        : "+f"(d[0]), "+f"(d[1]), "+f"(d[2]), "+f"(d[3]), "+f"(d[4]), "+f"(d[5]), "+f"(d[6]), "+f"(d[7]),
          "+f"(d[8]), "+f"(d[9]), "+f"(d[10]), "+f"(d[11]), "+f"(d[12]), "+f"(d[13]), "+f"(d[14]), "+f"(d[15]),
          "+f"(d[16]), "+f"(d[17]), "+f"(d[18]), "+f"(d[19]), "+f"(d[20]), "+f"(d[21]), "+f"(d[22]), "+f"(d[23]),
          "+f"(d[24]), "+f"(d[25]), "+f"(d[26]), "+f"(d[27]), "+f"(d[28]), "+f"(d[29]), "+f"(d[30]), "+f"(d[31]),
          "+f"(d[32]), "+f"(d[33]), "+f"(d[34]), "+f"(d[35]), "+f"(d[36]), "+f"(d[37]), "+f"(d[38]), "+f"(d[39]),
          "+f"(d[40]), "+f"(d[41]), "+f"(d[42]), "+f"(d[43]), "+f"(d[44]), "+f"(d[45]), "+f"(d[46]), "+f"(d[47]),
          "+f"(d[48]), "+f"(d[49]), "+f"(d[50]), "+f"(d[51]), "+f"(d[52]), "+f"(d[53]), "+f"(d[54]), "+f"(d[55]),
          "+f"(d[56]), "+f"(d[57]), "+f"(d[58]), "+f"(d[59]), "+f"(d[60]), "+f"(d[61]), "+f"(d[62]), "+f"(d[63])
        : "l"(da), "l"(db), "n"(TA), "n"(TB));
}

template <int MODE, bool FIRST>
__device__ __forceinline__ void mma_kblock(float (&acc)[128], uint32_t a_lo, uint32_t b_lo) {
    constexpr uint64_t HI = (uint64_t)(64u | 0x40000000u) << 32;
    constexpr uint32_t HALF = (MODE == 1) ? 12288u : 16384u;
    constexpr bool BN = (MODE == 1 || MODE == 2 || MODE == 4);
#pragma unroll
    for (int kk = 0; kk < 4; ++kk) {
        const uint32_t ao = (MODE == 3) ? kk * 2048u : kk * 32u;
        const uint32_t bo = BN ? ((kk >> 1) * HALF + (kk & 1) * 2048u) : kk * 32u;
        const uint64_t da = HI | (uint64_t)(a_lo + (ao >> 4) + (1u << 16));
        const uint64_t db = HI | (uint64_t)(b_lo + (bo >> 4) + (BN ? (256u << 16) : (1u << 16)));
        if (MODE == 1) {
            if (FIRST && kk == 0) wgmma_n192_first<0, 1>(acc, da, db); else wgmma_n192<0, 1>(acc, da, db);
        } else if (MODE == 4) {
            wgmma_n128<0, 1>(acc, da, db);
        } else {
            if (FIRST && kk == 0) wgmma_n256_first<(MODE == 3), BN>(acc, da, db);
            else wgmma_n256<(MODE == 3), BN>(acc, da, db);
        }
    }
}

struct Params {
    const __nv_bfloat16* x;
    const __nv_bfloat16* lam_re;
    const __nv_bfloat16* lam_im;
    const __nv_bfloat16* log_dt;
    const __nv_bfloat16* dskip;
    const __nv_bfloat16* b1;
    const __nv_bfloat16* b2;
    const __nv_bfloat16* gate_w;
    const __nv_bfloat16* w1;
    const __nv_bfloat16* w2;
    const __nv_bfloat16* c_re;
    const __nv_bfloat16* c_im;
    const __nv_bfloat16* b_re;
    const __nv_bfloat16* b_im;
    float* out;
    int swap;
};

#define CMUL(rr, ri, ar, ai, br, bi) do { float _r = (ar) * (br) - (ai) * (bi); float _i = (ar) * (bi) + (ai) * (br); rr = _r; ri = _i; } while (0)
#define CFMA(rr, ri, ar, ai, br, bi) do { float _r = fmaf(-(ai), (bi), fmaf((ar), (br), rr)); float _i = fmaf((ai), (br), fmaf((ar), (bi), ri)); rr = _r; ri = _i; } while (0)

#define KBLOCK_BEGIN(MODE, FIRST, IT)                                                            \
    KT(kt0 + (IT), 0);                                                                           \
    PIN_R(a_lo);                                                                                 \
    mbar_wait(bar_full + 8 * ((IT) & 3), ((IT) >> 2) & 1);                                       \
    KT(kt0 + (IT), 1);                                                                           \
    wgmma_fence();                                                                               \
    mma_kblock<MODE, FIRST>(acc, a_lo + ((IT) & 3) * (kStageBytes >> 4), b_lo + ((IT) & 3) * (kStageBytes >> 4)); \
    wgmma_commit();                                                                              \
    KBLOCK_EARLY(MODE, IT)
#define RELEASE_STAGE(S) do { if (lane < 2) mbar_arrive_cluster(rel_addr + 8 * (S)); } while (0)
#define KBLOCK_EARLY(MODE, IT) if ((MODE) != 4 && (IT) > 0) { wgmma_wait<1>(); RELEASE_STAGE(((IT) - 1) & 3); }
#define KBLOCK_END(IT) KT(kt0 + (IT), 2);

__global__ void __cluster_dims__(2, 1, 1) __launch_bounds__(384, 1)
fused_kernel(const __grid_constant__ CUtensorMap mB, const __grid_constant__ CUtensorMap mXs, const __grid_constant__ CUtensorMap mXf,
             const __grid_constant__ CUtensorMap mW1a, const __grid_constant__ CUtensorMap mW1b, const __grid_constant__ CUtensorMap mHs,
             const __grid_constant__ CUtensorMap mHf, const __grid_constant__ CUtensorMap mCre, const __grid_constant__ CUtensorMap mCim,
             const __grid_constant__ CUtensorMap mW2, const Params p) {
    extern __shared__ __align__(1024) uint8_t smem_raw[];
    const uint32_t sbase = smem_u32(smem_raw);
    if ((sbase & 0x3ffffu) != kSmemOrg) return;
    const uint32_t bar_full = sbase + kBarOff, bar_empty = bar_full + 32, bar_dep = bar_full + 64;
    const uint32_t bar_x = bar_full + 88, role_s = bar_full + 96;

    const int tid = threadIdx.x, lane = tid & 31;
    const int warp = __shfl_sync(0xffffffffu, tid >> 5, 0);
    const uint32_t rank = blockIdx.x & 1;

    int pref;
    {
        unsigned smid;
        asm("mov.u32 %0, %%smid;" : "=r"(smid));
        const int t = smid >> 1, u = t - 32, d = (u * 37) >> 8;
        pref = (t < 32) ? (t & 7) * 8 + (t >> 3) : (t < 60) ? (1 + u - 7 * d) * 8 + 4 + d : ((t - 58) & 7);
    }
#define FIRST_FILL(ROLE)                                                                     \
    _Pragma("unroll 1") for (int kb = 0; kb < FIRSTN; ++kb) {                                \
        const uint32_t st = sbase + kb * kStageBytes, fb = bar_full + 8 * kb;                \
        mbar_expect_tx(fb, 49152);                                                           \
        tma4(st, &mB, fb, kb * 64, 0, 0, (((ROLE) & 7) * 2 + (int)rank) * 8);                \
        tma5(st + kABytes, &mXs, fb, kb * 64, 0, 0, 0, (ROLE) >> 3);                         \
        tma5(st + kABytes + 16384, &mXs, fb, kb * 64, 0, 0, 16, (ROLE) >> 3);                \
    }
    STAMP(tid == 0, 0);
    if (tid == 0) {
        prefetch_map(&mB); prefetch_map(&mXs);
#pragma unroll
        for (int s = 0; s < kStages; ++s) {
            mbar_init(bar_full + 8 * s, 1);
            mbar_init(bar_empty + 8 * s, 16);
            mbar_init(bar_dep + 8 * s, 1);
        }
        asm volatile("fence.mbarrier_init.release.cluster;\nfence.proxy.async.shared::cta;" ::: "memory");
        FIRST_FILL(pref);
        mbar_expect_tx(bar_x, 2048);
        bulk_load(sbase + kXOff, p.gate_w, 2048, bar_x);
    } else if (tid == 32) {
        if (rank == 0) {
            int role = pref;
            unsigned taken = atom_exch(&g_claim[pref], 1u);
#pragma unroll 1
            for (int i = 0; taken != 0 && i < 64; ++i) { role = i; taken = atom_exch(&g_claim[i], 1u); }
            sts32(role_s, role);
            asm volatile("fence.acq_rel.cluster;" ::: "memory");
        }
    }
    else if (tid >= 128 && tid < 128 + 32 * PF0LINES) {
        const int row = blockIdx.x * 32 + lane;
        const __nv_bfloat16* src = (row < 2048) ? p.x + (size_t)row * kD : (row < 3072) ? p.b_re + (size_t)(row - 2048) * kD : p.b_im + (size_t)(row - 3072) * kD;
        asm volatile("prefetch.global.L2 [%0];" ::"l"(src + (warp - 4) * 64) : "memory");
    }
    __syncwarp();
    cluster_arrive();
#define TAKE_ROLE()                                                                          \
    cluster_wait();                                                                          \
    const int role = __shfl_sync(0xffffffffu, (int)lds32_cluster(mapa(role_s, 0)), 0);       \
    if (role != pref) {                                                                      \
        if (tid == 0) {                                                                      \
            _Pragma("unroll 1") for (int kb = 0; kb < FIRSTN; ++kb) {                        \
                mbar_wait(bar_full + 8 * kb, 0);                                             \
                asm volatile("mbarrier.inval.shared::cta.b64 [%0];" ::"r"(bar_full + 8 * kb) : "memory"); \
                mbar_init(bar_full + 8 * kb, 1);                                             \
            }                                                                                \
            asm volatile("fence.mbarrier_init.release.cluster;\nfence.proxy.async.shared::cta;" ::: "memory"); \
            FIRST_FILL(role);                                                                \
        }                                                                                    \
        __syncwarp();                                                                        \
        bar_sync<0, 384>();                                                                  \
    }                                                                                        \
    const int c = role >> 3;                                         \
    const int j8 = role & 7;                                    \
    const int cb = j8 * 2 + (int)rank;                         \
    const int rb = 2 * c + (int)rank;                           \
    const int kh = j8 >> 2;                \
    const int colK = (j8 & 3) * 256 + kh * 128, colS = colK ^ 128;    \
    (void)cb; (void)rb; (void)colS;

    if (warp >= 8) {
        asm volatile("setmaxnreg.dec.sync.aligned.u32 24;");
        TAKE_ROLE();
        if (warp == 8) {
            if (lane == 0) {
                int it = FIRSTN;
#define ACQUIRE(BYTES)                                                   \
    const uint32_t st = sbase + (it & 3) * kStageBytes, fb = bar_full + 8 * (it & 3); \
    mbar_wait(bar_empty + 8 * (it & 3), ((it >> 2) & 1) ^ 1);            \
    mbar_expect_tx(fb, BYTES);
                prefetch_map(&mXf); prefetch_map(&mW1b); prefetch_map(&mW1a);
#pragma unroll 1
                for (int kb = FIRSTN; kb < 16; ++kb, ++it) {
                    ACQUIRE(49152);
                    tma4(st, &mB, fb, kb * 64, 0, 0, cb * 8);
                    tma5_mc(st + kABytes + rank * 16384, &mXs, fb, kb * 64, 0, 0, rank * 16, c);
                }
#pragma unroll 1
                for (int kb = 0; kb < 16; ++kb, ++it) {
                    ACQUIRE(40960);
                    tma5(st, &mXf, fb, kb * 64, 0, 0, rank * 4, c);
                    tma3_mc(st + kABytes + rank * 12288, &mW1b, fb, 0, kb * 64 + rank * 32, 32 + 3 * j8);
                }
                const CUtensorMap* mC = kh ? &mCim : &mCre;
                prefetch_map(&mHs); prefetch_map(&mHf); prefetch_map(mC); prefetch_map(&mW2);
#pragma unroll 1
                for (int kb = 0; kb < 16; ++kb, ++it) {
                    ACQUIRE(49152);
                    tma5(st, &mXf, fb, kb * 64, 0, 0, rank * 4, c);
                    tma3_mc(st + kABytes + rank * 16384, &mW1a, fb, 0, kb * 64 + rank * 32, 4 * j8);
                    if (kb == XLDKB || kb == XLDKB + 2) {
                        const int h = (kb - XLDKB) >> 1;
                        if (h == 0) mbar_expect_tx(bar_x, 32768);
                        tma5(sbase + kXOff + h * 16384, &mXf, bar_x, colK + h * 64, 0, 0, rank * 4, c);
                    }
                }
                STAMP(true, 8);
                mbar_wait(bar_dep, 0);
                asm volatile("fence.proxy.async.global;" ::: "memory");
                STAMP(true, 9);
#pragma unroll 1
                for (int kb = 0; kb < 16; ++kb, ++it) {
                    ACQUIRE(49152);
                    tma3(st, &mHs, fb, 0, kh * 1024 + kb * 64, rb * 2);
                    tma2_mc(st + kABytes + rank * 16384, mC, fb, kb * 64, rank ? colS : colK);
                }
                mbar_wait(bar_dep + 8, 0);
                asm volatile("fence.proxy.async.global;" ::: "memory");
                STAMP(true, 10);
#pragma unroll 1
                for (int kb = 0; kb < kNF + kTail; ++kb, ++it) {
                    if (kb == 12) {
                        mbar_wait(bar_dep + 16, 0);
                        asm volatile("fence.proxy.async.global;" ::: "memory");
                    }
                    const int f0 = (kb < 12) ? 2048 + 768 * kh + 64 * kb : (kb < kNF ? 64 * (kNA * kh + kb - 12) : 64 * (kNA + kb - 12));
                    ACQUIRE(kb < kNF ? 49152 : 32768);
                    tma2(st, &mHf, fb, f0, rb * 128);
                    tma5_mc(st + kABytes + rank * 16384, &mW2, fb, 0, 0, (f0 >> 3) + 4 * rank, 0, colK >> 6);
                    if (kb < kNF) tma5_mc(st + kABytes + rank * 16384 + 8192, &mW2, fb, 0, 0, (f0 >> 3) + 4 * rank, 0, colS >> 6);
                }
            }
        } else if (warp == 9) {
#pragma unroll
            for (int ev = 0; ev < 3; ++ev) {
                if (ev == 0) bar_sync<3, 288>(); else if (ev == 1) bar_sync<4, 288>(); else bar_sync<5, 288>();
                if (lane == 0) {
                    unsigned* cnt = &g_cnt[(ev == 0 ? c : (ev == 1 ? 8 : 24) + rb) * 32];
                    asm volatile("fence.acq_rel.gpu;\nfence.proxy.async.global;" ::: "memory");
                    asm volatile("red.relaxed.gpu.global.add.u32 [%0], 1;" ::"l"(cnt) : "memory");
                }
            }
        } else if (warp == 10) {
            if (lane == 0) {
                const unsigned tag = ld_relaxed32(&g_epoch) + 1;
                wait_counter(&g_cnt[c * 32], tag * 16u);
                mbar_arrive_local(bar_dep);
                if (atomicInc(&g_done, 127u) == 127u) {
                    asm volatile("st.relaxed.gpu.global.u32 [%0], %1;" ::"l"(&g_epoch), "r"(tag) : "memory");
#pragma unroll 1
                    for (int i = 0; i < 64; i += 4) stg128(&g_claim[i], 0, 0, 0, 0);
                }
                wait_counter(&g_cnt[(8 + rb) * 32], tag * 8u);
                mbar_arrive_local(bar_dep + 8);
                wait_counter(&g_cnt[(24 + rb) * 32], tag * 8u);
                mbar_arrive_local(bar_dep + 16);
            }
        }
    } else {
        asm volatile("setmaxnreg.inc.sync.aligned.u32 240;");
        TAKE_ROLE();
        const int wg = warp >> 2, w = warp & 3, r = lane >> 2, q = lane & 3, tw = tid & 127;
        uint32_t a_lo = (kSmemOrg + wg * 8192) >> 4;
        constexpr uint32_t b_lo = (kSmemOrg + kABytes) >> 4;
        const uint32_t rel_addr = mapa(bar_empty, (uint32_t)(lane & 1));
        const uint32_t gate_s = sbase + kGateOff, bias_s = sbase + kBiasOff;
        float acc[128];
        int kt0 = 0; (void)kt0;
        uint32_t pk[64];
        unsigned tag = ld_relaxed32(&g_epoch);

        const int ch = cb * 64 + warp * 8 + r;
        float lr, li, m00, m01, m10, m11;
        float l64r, l64i, l128r, l128i, w0r, w0i, w1r, w1i;
        {
            uint32_t Lr_ = ldg16(p.lam_re + ch), Li_ = ldg16(p.lam_im + ch), Ldt_ = ldg16(p.log_dt + ch);
            uint32_t bz[4] = {0, 0, 0, 0};
            if (tw < 88) {
                const int J = tw >> 2;
                const __nv_bfloat16* src = (J < 6) ? p.b1 + 2048 + 192 * j8 + 32 * J
                                         : (J < 14) ? p.b1 + 256 * j8 + 32 * (J - 6)
                                         : (J < 18) ? p.dskip + colK + 32 * (J - 14) : p.b2 + colK + 32 * (J - 18);
#pragma unroll
                for (int jj = 0; jj < 4; ++jj) bz[jj] = ldg32(src + 8 * jj + 2 * (tw & 3));
            }
            const uint32_t gx_s = sbase + kABytes + (16 * cb + 2 * warp + (lane >> 4)) * 128 +
                                  ((((lane & 15) >> 1) ^ (2 * w + (lane >> 4))) << 4) + (lane & 1) * 8;
            const uint32_t gw_s = sbase + kXOff + (lane & 15) * 8;
            float gs = 0.f, dt, ea;
#pragma unroll
            for (int kb = 0; kb < 16; ++kb) {
                if (kb == 0) { KBLOCK_BEGIN(0, true, kb); STAMP(tid == 0, 1); mbar_wait(bar_x, 0); } else { KBLOCK_BEGIN(0, false, kb); }
                {
                    const uint2 xa = lds64(gx_s + (kb & 3) * kStageBytes), wa = lds64(gw_s + kb * 128);
                    const uint32_t pa = bf2_mul(xa.x, wa.x), pb = bf2_mul(xa.y, wa.y);
                    gs += (bf_lo(pa) + bf_hi(pa)) + (bf_lo(pb) + bf_hi(pb));
                    PIN_F(gs);
                }
                if (kb == 3) {
                    PIN_R(Lr_); PIN_R(Li_); PIN_R(Ldt_);
                    dt = bf16_round(expf(bf_lo(Ldt_)));
                    ea = expf(dt * bf_lo(Lr_));
                    PIN_F(dt); PIN_F(ea);
                }
                if (kb == 4) {
                    float sn, cs;
                    sincospif((dt * bf_lo(Li_)) * 0.31830988618379067f, &sn, &cs);
                    lr = ea * cs; li = ea * sn;
                    PIN_F(lr); PIN_F(li);
                }
                if (kb == 5) {
                    const float Lr = bf_lo(Lr_), Li = bf_lo(Li_);
                    const float nr = lr - 1.0f, ni = li;
                    float cr, ci;
                    if (fabsf(Lr) >= fabsf(Li)) {
                        const float t = Li / Lr, d = 1.0f / fmaf(Li, t, Lr);
                        cr = fmaf(ni, t, nr) * d; ci = fmaf(-nr, t, ni) * d;
                    } else {
                        const float t = Lr / Li, d = 1.0f / fmaf(Lr, t, Li);
                        cr = fmaf(nr, t, ni) * d; ci = fmaf(ni, t, -nr) * d;
                    }
                    if (p.swap) { li = -li; m00 = -2.f * ci; m01 = 2.f * cr; m10 = -2.f * cr; m11 = -2.f * ci; }
                    else { m00 = 2.f * cr; m01 = -2.f * ci; m10 = -2.f * ci; m11 = -2.f * cr; }
                    PIN_F(li); PIN_F(m00); PIN_F(m01); PIN_F(m10); PIN_F(m11);
                }
                if (kb == 6) {
                    PIN_R(tag); tag += 1;
                    if (tw < 88) sts128(bias_s + tw * 16, bz[0], bz[1], bz[2], bz[3]);
                    l64r = lr; l64i = li;
#pragma unroll
                    for (int i = 0; i < 6; ++i) CMUL(l64r, l64i, l64r, l64i, l64r, l64i);
                    CMUL(l128r, l128i, l64r, l64i, l64r, l64i);
                    PIN_F(l64r); PIN_F(l64i); PIN_F(l128r); PIN_F(l128i);
                }
                if (kb == 7) {
                    float l256r, l256i, l512r, l512i, l1kr, l1ki;
                    CMUL(l256r, l256i, l128r, l128i, l128r, l128i);
                    CMUL(l512r, l512i, l256r, l256i, l256r, l256i);
                    CMUL(l1kr, l1ki, l512r, l512i, l512r, l512i);
                    const int n2 = max(c - 1 - q, 0);
                    w1r = (n2 & 1) ? l256r : 1.f; w1i = (n2 & 1) ? l256i : 0.f;
                    if (n2 & 2) CMUL(w1r, w1i, w1r, w1i, l512r, l512i);
                    w0r = w1r; w0i = w1i;
                    if (n2 & 4) CMUL(w0r, w0i, w0r, w0i, l1kr, l1ki);
                    PIN_F(w0r); PIN_F(w0i); PIN_F(w1r); PIN_F(w1i);
                }
                if (kb == 15) {
#pragma unroll
                    for (int o = 8; o > 0; o >>= 1) gs += __shfl_xor_sync(0xffffffffu, gs, o);
                    if ((lane & 15) == 0) {
                        const float z = bf16_round(gs);
                        const float g = bf16_round(1.0f / (1.0f + expf(-z)));
                        st_relaxed64(&g_gate[c * 256 + (lane >> 4) + 64 * w + 4 * cb + 2 * wg], __float_as_uint(g), tag);
                    }
                    __syncwarp();
                }
                KBLOCK_END(kb);
            }
            wgmma_wait<0>();
            RELEASE_STAGE(3);
        }
        STAMP(tid == 0, 2); kt0 = 16;
#pragma unroll
        for (int s = 0; s < 64; ++s) pk[s] = pack_bf16_v(acc[4 * (s >> 1) + (s & 1)], acc[4 * (s >> 1) + 2 + (s & 1)]);

        {
            float hr = 0.f, hi = 0.f;
            uint4 av0, av1, gv;
            uint32_t gg[4], orr[4], oii[4];
            __nv_bfloat16* hs = g_Hs + (size_t)ch * 2048 + c * 256 + q * 8;
#pragma unroll
            for (int kb = 0; kb < 16; ++kb) {
                if (kb == 0) { KBLOCK_BEGIN(1, true, kb); } else { KBLOCK_BEGIN(1, false, kb); }
                if (kb < 4) {
#pragma unroll
                    for (int s = kb * 16; s < kb * 16 + 16; ++s) {
                        float nr = bf_lo(pk[s]), ni = bf_hi(pk[s]);
                        CFMA(nr, ni, lr, li, hr, hi);
                        hr = nr; hi = ni;
                    }
                    PIN_F(hr); PIN_F(hi);
                }
                if (kb == 2) gv = ld_relaxed2x64(&g_gate[c * 256 + 2 * tw]);
                if (kb == 3) {
                    float tr = __shfl_up_sync(0xffffffffu, hr, 1, 4), ti = __shfl_up_sync(0xffffffffu, hi, 1, 4);
                    if (q >= 1) CFMA(hr, hi, l64r, l64i, tr, ti);
                    tr = __shfl_up_sync(0xffffffffu, hr, 2, 4); ti = __shfl_up_sync(0xffffffffu, hi, 2, 4);
                    if (q >= 2) CFMA(hr, hi, l128r, l128i, tr, ti);
                    if (q == 3) st_relaxed2x64(&g_agg[c * 1024 + ch], __float_as_uint(hr), tag, __float_as_uint(hi), tag);
                    tr = __shfl_up_sync(0xffffffffu, hr, 1, 4); ti = __shfl_up_sync(0xffffffffu, hi, 1, 4);
                    hr = (q >= 1) ? tr : 0.f; hi = (q >= 1) ? ti : 0.f;
                }
                if (kb == 4) {
                    unsigned n = 0;
                    while (gv.y != tag || gv.w != tag) {
                        if (++n > kSpinLimit) TRAP();
                        gv = ld_relaxed2x64(&g_gate[c * 256 + 2 * tw]);
                    }
                    sts32(gate_s + ((tw >> 5) * 72 + 2 * lane) * 2, __byte_perm(gv.x, gv.z, 0x7632));
                    __syncwarp();
                    if (!(q & 1)) { l64r = 1.f; l64i = 0.f; }
                    if (q & 2) CMUL(l64r, l64i, l64r, l64i, l128r, l128i);
                    PIN_F(l64r); PIN_F(l64i);
                }
                if (kb == 5) {
                    av0 = make_uint4(0, tag, 0, tag); av1 = av0;
                    if (q < c) av0 = ld_relaxed2x64(&g_agg[q * 1024 + ch]);
                    if (q + 4 < c) av1 = ld_relaxed2x64(&g_agg[(q + 4) * 1024 + ch]);
                    if (wg == 0) bar_sync<1, 128>(); else bar_sync<2, 128>();
                }
                if (kb == 6) {
                    unsigned n = 0;
                    while (av0.y != tag || av0.w != tag || av1.y != tag || av1.w != tag) {
                        if (++n > kSpinLimit) TRAP();
                        if (q < c) av0 = ld_relaxed2x64(&g_agg[q * 1024 + ch]);
                        if (q + 4 < c) av1 = ld_relaxed2x64(&g_agg[(q + 4) * 1024 + ch]);
                    }
                    __syncwarp();
                    float vr, vi;
                    CMUL(vr, vi, w0r, w0i, __uint_as_float(av0.x), __uint_as_float(av0.z));
                    CFMA(vr, vi, w1r, w1i, __uint_as_float(av1.x), __uint_as_float(av1.z));
                    vr += __shfl_xor_sync(0xffffffffu, vr, 1); vi += __shfl_xor_sync(0xffffffffu, vi, 1);
                    vr += __shfl_xor_sync(0xffffffffu, vr, 2); vi += __shfl_xor_sync(0xffffffffu, vi, 2);
                    CFMA(hr, hi, l64r, l64i, vr, vi);
                }
                if (kb >= 6) {
#pragma unroll
                    for (int s = 0; s < 64; s += 2) {
                        if (pass2_kb(s) != kb) continue;
                        if ((s & 7) == 0) {
                            const uint4 ga = lds128(gate_s + (q * 72 + s) * 2);
                            gg[0] = ga.x; gg[1] = ga.y; gg[2] = ga.z; gg[3] = ga.w;
                        }
                        float o0[2], o1[2];
#pragma unroll
                        for (int k = 0; k < 2; ++k) {
                            PIN_R(pk[s + k]);
                            float nr = bf_lo(pk[s + k]), ni = bf_hi(pk[s + k]);
                            CFMA(nr, ni, lr, li, hr, hi);
                            hr = nr; hi = ni;
                            o0[k] = fmaf(m00, hr, m01 * hi);
                            o1[k] = fmaf(m10, hr, m11 * hi);
                        }
                        orr[(s >> 1) & 3] = bf2_mul(pack_bf16(o0[0], o0[1]), gg[(s >> 1) & 3]);
                        oii[(s >> 1) & 3] = bf2_mul(pack_bf16(o1[0], o1[1]), gg[(s >> 1) & 3]);
                        if ((s & 7) == 6) {
                            stg128(hs + 32 * (s >> 3), orr[0], orr[1], orr[2], orr[3]);
                            stg128(hs + 1024 * 2048 + 32 * (s >> 3), oii[0], oii[1], oii[2], oii[3]);
                        }
                    }
                    PIN_F(hr); PIN_F(hi);
                    if (kb == 15) bar_arrive<3, 288>();
                }
                KBLOCK_END(kb);
            }
            wgmma_wait<0>();
            RELEASE_STAGE(3);
        }
        STAMP(tid == 0, 3); kt0 = 32;
#pragma unroll
        for (int i = 0; i < 48; ++i) pk[i] = pack_bf16_v(acc[2 * i], acc[2 * i + 1]);

        const uint32_t gate_row = gate_s + ((2 * (w & 1)) * 72 + 8 * (4 * rank + 2 * wg + (w >> 1)) + r) * 2;
        uint32_t om0, om1;
        __nv_bfloat16* hf = g_Hf + (size_t)(rb * 128 + wg * 64 + w * 16 + r) * kF + q * 8;
#define FFN_SLICE(J, BIAS_ENTRY, F0)                                                                   \
    {                                                                                                  \
        const uint4 bv = lds128(bias_s + ((BIAS_ENTRY) * 4 + q) * 16);                                 \
        const uint32_t bb[4] = {bv.x, bv.y, bv.z, bv.w};                                               \
        uint32_t o0[4], o1[4];                                                                         \
        _Pragma("unroll") for (int jj = 0; jj < 4; ++jj) {                                             \
            const uint32_t r0 = bf2_add_relu(pk[8 * (J) + 2 * jj], bb[jj]), r1 = bf2_add_relu(pk[8 * (J) + 2 * jj + 1], bb[jj]); \
            o0[jj] = bf2_mul(bf2_mul(r0, r0), om0);                                                    \
            o1[jj] = bf2_mul(bf2_mul(r1, r1), om1);                                                    \
        }                                                                                              \
        stg128(hf + (F0) + 32 * (J), o0[0], o0[1], o0[2], o0[3]);                                      \
        stg128(hf + 8 * kF + (F0) + 32 * (J), o1[0], o1[1], o1[2], o1[3]);                             \
    }

        {
            const int f0 = 2048 + 192 * j8;
#pragma unroll
            for (int kb = 0; kb < 16; ++kb) {
                if (kb == 0) { KBLOCK_BEGIN(2, true, kb); } else { KBLOCK_BEGIN(2, false, kb); }
                if (kb == 0) {
                    const float a = 1.0f - bf_lo(lds16(gate_row)), b = 1.0f - bf_lo(lds16(gate_row + 72 * 2));
                    om0 = pack_bf16(a, a); om1 = pack_bf16(b, b);
                }
                if (kb < 6) FFN_SLICE(kb, kb, f0);
                if (kb == 5) bar_arrive<4, 288>();
                KBLOCK_END(kb);
            }
            wgmma_wait<0>();
            RELEASE_STAGE(3);
        }
        STAMP(tid == 0, 4); kt0 = 48;
#pragma unroll
        for (int i = 0; i < 64; ++i) pk[i] = pack_bf16_v(acc[2 * i], acc[2 * i + 1]);

        float e[64];
        {
            const int f0 = 256 * j8;
            const uint32_t x_s = sbase + kXOff + (wg * 64 + w * 16 + (lane & 15)) * 128 + (((lane >> 4) ^ (lane & 7)) << 4);
#pragma unroll
            for (int kb = 0; kb < 16; ++kb) {
                if (kb == 0) { KBLOCK_BEGIN(3, true, kb); } else { KBLOCK_BEGIN(3, false, kb); }
                if (kb < 8) FFN_SLICE(kb, 6 + kb, f0);
                if (kb == 7) bar_arrive<5, 288>();
                if (kb == 8) mbar_wait(bar_x, 1);
                if (kb >= 8 && kb < 12) {
                    const int jb = (kb - 8) * 4;
                    const float g0 = bf_lo(lds16(gate_row)), g1 = bf_lo(lds16(gate_row + 72 * 2));
                    const float o0f = bf_lo(om0), o1f = bf_lo(om1);
                    const uint4 dq = lds128(bias_s + ((14 + kb - 8) * 4 + q) * 16), bq = lds128(bias_s + ((18 + kb - 8) * 4 + q) * 16);
                    const uint4 xa = ldsm4((x_s ^ ((jb & 7) << 4)) + (jb >> 3) * 16384), xb = ldsm4((x_s ^ (((jb + 2) & 7) << 4)) + (jb >> 3) * 16384);
                    const uint32_t dv[4] = {dq.x, dq.y, dq.z, dq.w}, bv2[4] = {bq.x, bq.y, bq.z, bq.w};
                    const uint32_t xv[8] = {xa.x, xa.y, xa.z, xa.w, xb.x, xb.y, xb.z, xb.w};
#pragma unroll
                    for (int jj = 0; jj < 4; ++jj) {
                        const uint32_t x0 = bf2_mul(xv[2 * jj], dv[jj]), x1 = bf2_mul(xv[2 * jj + 1], dv[jj]);
                        const float bl = bf_lo(bv2[jj]), bh = bf_hi(bv2[jj]);
                        e[4 * (jb + jj) + 0] = fmaf(g0, bf_lo(x0), o0f * bl);
                        e[4 * (jb + jj) + 1] = fmaf(g0, bf_hi(x0), o0f * bh);
                        e[4 * (jb + jj) + 2] = fmaf(g1, bf_lo(x1), o1f * bl);
                        e[4 * (jb + jj) + 3] = fmaf(g1, bf_hi(x1), o1f * bh);
                        PIN_F(e[4 * (jb + jj)]); PIN_F(e[4 * (jb + jj) + 1]); PIN_F(e[4 * (jb + jj) + 2]); PIN_F(e[4 * (jb + jj) + 3]);
                    }
                }
                KBLOCK_END(kb);
            }
        }
        STAMP(tid == 0, 5);
#pragma unroll 1
        for (int k4 = 0; k4 < kNF / 4; ++k4) {
#pragma unroll
            for (int s = 0; s < 4; ++s) {
                KT(64 + k4 * 4 + s, 0);
                mbar_wait(bar_full + 8 * s, k4 & 1);
                KT(64 + k4 * 4 + s, 1);
                wgmma_fence();
                mma_kblock<2, false>(acc, a_lo + s * (kStageBytes >> 4), b_lo + s * (kStageBytes >> 4));
                wgmma_commit();
                wgmma_wait<1>();
                RELEASE_STAGE((s + 3) & 3);
            }
        }
        kt0 = 0;
#pragma unroll
        for (int it = 64 + (kNF & ~3); it < 64 + kNF; ++it) {
            KBLOCK_BEGIN(2, false, it);
            KBLOCK_END(it);
        }
        {
            uint8_t* xo = g_X + (size_t)(role * 2 + rank) * kXBytes + tid * 16;
            const uint8_t* xi = xo + (kh ? -8 * kXBytes : 8 * kXBytes);
            const uint32_t par = tag & 1;
            float xsc = 0.f;
            uint4 rx[8];
            uint32_t rs = 0;
#pragma unroll
            for (int kb = 0; kb < kTail; ++kb) {
                const int it = 64 + kNF + kb;
                KBLOCK_BEGIN(4, false, it);
                if (kb < kTail - 1) wgmma_wait<1>();
                if (it - 1 < kTotal - kStages) RELEASE_STAGE((it - 1) & 3);
                if (kb == 0) STAMP(tid == 0, 15);
                if (kb == 0) {
                    float m[4] = {0.f, 0.f, 0.f, 0.f};
#pragma unroll
                    for (int i = 64; i < 128; ++i) m[i & 3] = fmaxf(m[i & 3], fabsf(acc[i]));
                    const uint32_t eb = max(__float_as_uint(fmaxf(fmaxf(m[0], m[1]), fmaxf(m[2], m[3]))) >> 23, 15u);
                    xsc = __uint_as_float((268u - eb) << 23);
                    st_relaxed32(xo + 32768 - tid * 12, ((eb - 14u) << 23) | par);
                }
#pragma unroll
                for (int u = 0; u < 8; ++u) {
                    if (nib(XSND, u) == kb) {
                        const int v = 64 + 8 * u;
                        st_relaxed2x64(xo + u * 4096, (pack_f16(acc[v] * xsc, acc[v + 1] * xsc) & ~1u) | par, pack_f16(acc[v + 2] * xsc, acc[v + 3] * xsc),
                                       (pack_f16(acc[v + 4] * xsc, acc[v + 5] * xsc) & ~1u) | par, pack_f16(acc[v + 6] * xsc, acc[v + 7] * xsc));
                        if (u == 7) STAMP(tid == 0, 12);
                    }
                }
#pragma unroll
                for (int u = 0; u < 8; ++u) {
                    if (nib(XLDK, u) == kb) {
                        if (u == 0) rs = ld_relaxed32((const unsigned*)(xi + 32768 - tid * 12));
                        rx[u] = ld_relaxed2x64(xi + u * 4096);
                    }
                }
#pragma unroll
                for (int u = 0; u < 8; ++u) {
                    if (nib(XUSE, u) == kb) {
                        unsigned n = 0;
                        if (u == 0) {
                            while ((rs ^ par) & 1) {
                                if (++n > kSpinLimit) TRAP();
                                rs = ld_relaxed32((const unsigned*)(xi + 32768 - tid * 12));
                            }
                            xsc = __uint_as_float(rs & ~1u);
                        }
                        while (((rx[u].x ^ par) | (rx[u].z ^ par)) & 1) {
                            if (++n > kSpinLimit) TRAP();
                            rx[u] = ld_relaxed2x64(xi + u * 4096);
                        }
                        __syncwarp();
                        const uint32_t rr[4] = {rx[u].x, rx[u].y, rx[u].z, rx[u].w};
#pragma unroll
                        for (int k = 0; k < 4; ++k) {
                            const int v = 8 * u + 2 * k;
                            const float2 f = __half22float2(*reinterpret_cast<const __half2*>(&rr[k]));
                            e[v] = fmaf(f.x, xsc, e[v]); e[v + 1] = fmaf(f.y, xsc, e[v + 1]);
                            PIN_F(e[v]); PIN_F(e[v + 1]);
                        }
                        if (u == 0) STAMP(tid == 0, 13);
                        if (u == 7) STAMP(tid == 0, 14);
                    }
                }
            }
        }
        wgmma_wait<0>();
        STAMP(tid == 0, 6);
        {
            const bool odd = q & 1;
            const int tb = c * 256 + 128 * (w & 1) + 8 * (4 * rank + 2 * wg + (w >> 1));
            float* o0 = p.out + (size_t)(tb + r) * kD + colK + (odd ? 2 * q + 6 : 2 * q);
#pragma unroll
            for (int i = 0; i < 16; i += 2) {
#pragma unroll
                for (int h = 0; h < 2; ++h) {
                    const int va = 4 * i + 2 * h, vb = va + 4;
                    PIN_F(acc[va]); PIN_F(acc[va + 1]); PIN_F(acc[vb]); PIN_F(acc[vb + 1]);
                    const float a0 = acc[va] + e[va], a1 = acc[va + 1] + e[va + 1], b0 = acc[vb] + e[vb], b1 = acc[vb + 1] + e[vb + 1];
                    const float t0 = __shfl_xor_sync(0xffffffffu, odd ? a0 : b0, 1), t1 = __shfl_xor_sync(0xffffffffu, odd ? a1 : b1, 1);
                    stg128f(o0 + h * 64 * kD + 8 * i, odd ? t0 : a0, odd ? t1 : a1, odd ? b0 : t0, odd ? b1 : t1);
                }
            }
        }
        STAMP(tid == 0, 7);
    }
}

typedef CUresult (*EncodeFn)(CUtensorMap*, CUtensorMapDataType, cuuint32_t, void*, const cuuint64_t*, const cuuint64_t*,
                             const cuuint32_t*, const cuuint32_t*, CUtensorMapInterleave, CUtensorMapSwizzle,
                             CUtensorMapL2promotion, CUtensorMapFloatOOBfill);

bool encode(EncodeFn fn, CUtensorMap* m, const void* base, int rank, const cuuint64_t* dims, const cuuint64_t* strides,
            const cuuint32_t* box) {
    cuuint32_t es[5] = {1, 1, 1, 1, 1};
    return fn(m, CU_TENSOR_MAP_DATA_TYPE_BFLOAT16, rank, const_cast<void*>(base), dims, strides, box, es,
              CU_TENSOR_MAP_INTERLEAVE_NONE, CU_TENSOR_MAP_SWIZZLE_128B, CU_TENSOR_MAP_L2_PROMOTION_L2_256B,
              CU_TENSOR_MAP_FLOAT_OOB_FILL_NONE) == CUDA_SUCCESS;
}

}

extern "C" void kernel_launch(void* const* d_in, const int* in_sizes, int n_in, void* d_out, int out_size) {
    (void)in_sizes; (void)n_in; (void)out_size;
    typedef const __nv_bfloat16* bp;
    bp x = (bp)d_in[0], lam_re = (bp)d_in[1], lam_im = (bp)d_in[2], B_re = (bp)d_in[3], B_im = (bp)d_in[4];
    bp C_re = (bp)d_in[5], C_im = (bp)d_in[6], log_dt = (bp)d_in[7], dskip = (bp)d_in[8];
    bp w1 = (bp)d_in[10], b1 = (bp)d_in[11], w2 = (bp)d_in[12], b2 = (bp)d_in[13], gate_w = (bp)d_in[14];

    static EncodeFn fn = nullptr;
    static void *pHs = nullptr, *pHf = nullptr, *pBc = nullptr;
    if (!fn) {
        void* f = nullptr;
        cudaDriverEntryPointQueryResult qr;
        cudaGetDriverEntryPoint("cuTensorMapEncodeTiled", &f, cudaEnableDefault, &qr);
        fn = (EncodeFn)f;
        cudaGetSymbolAddress(&pHs, g_Hs);
        cudaGetSymbolAddress(&pHf, g_Hf);
        cudaGetSymbolAddress(&pBc, g_Bcopy);
        cudaFuncSetAttribute(fused_kernel, cudaFuncAttributeMaxDynamicSharedMemorySize, kSmemBytes);
    }
    cudaStream_t stream = cudaStreamPerThread;

    Params p;
    p.x = x; p.lam_re = lam_re; p.lam_im = lam_im; p.log_dt = log_dt; p.dskip = dskip; p.b1 = b1; p.b2 = b2;
    p.gate_w = gate_w; p.w1 = w1; p.w2 = w2; p.c_re = C_re; p.c_im = C_im; p.b_re = B_re; p.b_im = B_im; p.out = (float*)d_out;

    const char* lo = (const char*)B_re; const char* hi = (const char*)B_im;
    p.swap = 0;
    if (hi < lo) { const char* t = lo; lo = hi; hi = t; p.swap = 1; }
    unsigned long long diff = (unsigned long long)(hi - lo);
    if (diff >= (1ull << 40) || (diff & 15) || diff == 0) {
        cudaMemcpyAsync(pBc, B_re, 2u << 20, cudaMemcpyDeviceToDevice, stream);
        cudaMemcpyAsync((char*)pBc + (2u << 20), B_im, 2u << 20, cudaMemcpyDeviceToDevice, stream);
        lo = (const char*)pBc; diff = 2u << 20; p.swap = 0;
    }

    CUtensorMap mB, mXs, mXf, mW1a, mW1b, mHs, mHf, mCre, mCim, mW2;
    bool ok = true;
    { cuuint64_t d[4] = {1024, 8, 2, 128}, s[3] = {2048, diff, 16384}; cuuint32_t b[4] = {64, 8, 2, 8};
      ok &= encode(fn, &mB, lo, 4, d, s, b); }
    { cuuint64_t d[5] = {1024, 2, 4, 32, 8}, s[4] = {2048, 64 * 2048, 2 * 2048, 256 * 2048}; cuuint32_t b[5] = {64, 2, 4, 16, 1};
      ok &= encode(fn, &mXs, x, 5, d, s, b); }
    { cuuint64_t d[5] = {1024, 8, 4, 8, 8}, s[4] = {2048, 64 * 2048, 8 * 2048, 256 * 2048}; cuuint32_t b[5] = {64, 8, 4, 4, 1};
      ok &= encode(fn, &mXf, x, 5, d, s, b); }
    { cuuint64_t d[3] = {64, 1024, 56}, s[2] = {7168, 128}; cuuint32_t ba[3] = {64, 32, 4}, bb[3] = {64, 32, 3};
      ok &= encode(fn, &mW1a, w1, 3, d, s, ba); ok &= encode(fn, &mW1b, w1, 3, d, s, bb); }
    { cuuint64_t d[3] = {64, 2048, 32}, s[2] = {4096, 128}; cuuint32_t b[3] = {64, 64, 2};
      ok &= encode(fn, &mHs, pHs, 3, d, s, b); }
    { cuuint64_t d[2] = {3584, 2048}, s[1] = {7168}; cuuint32_t b[2] = {64, 128};
      ok &= encode(fn, &mHf, pHf, 2, d, s, b); }
    { cuuint64_t d[2] = {1024, 1024}, s[1] = {2048}; cuuint32_t b[2] = {64, 128};
      ok &= encode(fn, &mCre, C_re, 2, d, s, b); ok &= encode(fn, &mCim, C_im, 2, d, s, b); }
    { cuuint64_t d[5] = {64, 2, 448, 4, 16}, s[4] = {2048, 8 * 2048, 2 * 2048, 128}; cuuint32_t b[5] = {64, 2, 4, 4, 2};
      ok &= encode(fn, &mW2, w2, 5, d, s, b); }
    if (!ok) return;

    fused_kernel<<<128, 384, kSmemBytes, stream>>>(mB, mXs, mXf, mW1a, mW1b, mHs, mHf, mCre, mCim, mW2, p);
}
```

```cpp
#include <cuda_runtime.h>
#include <cuda_bf16.h>
#include <cuda_fp16.h>
#include <cuda.h>
#include <stdint.h>

#define MTAIL 8

#define XLDKB 8
#define XSND 0x01122233u
#define XLDK 0x44455566u
#define XUSE 0x66677777u

#define PF0LINES 2

namespace {

constexpr int kD = 1024, kF = 3584;
constexpr int kStages = 4;
constexpr int kStageBytes = 49152;
constexpr int kABytes = 16384;
constexpr int kXOff = kStages * kStageBytes;
constexpr int kGateOff = kXOff + 32768;
constexpr int kBiasOff = kGateOff + 4 * 72 * 2;
constexpr int kBarOff = kBiasOff + 88 * 16;
constexpr int kSmemBytes = 232448;
static_assert(kBarOff + 128 <= kSmemBytes, "smem");
constexpr int kXBytes = 33792;
constexpr uint32_t kSmemOrg = 1024;
constexpr unsigned kSpinLimit = 1u << 22;
constexpr int kTail = MTAIL;
constexpr int kNA = (32 - kTail) / 2;
constexpr int kNF = 12 + kNA;
constexpr int kTotal = 64 + kNF + kTail;

__host__ __device__ constexpr int nib(unsigned v, int u) { return (int)((v >> (28 - 4 * u)) & 15u); }
__host__ __device__ constexpr bool any_nib(unsigned v, int k) {
    for (int u = 0; u < 8; ++u) if (nib(v, u) == k) return true;
    return false;
}
__host__ __device__ constexpr int pass2_kb(int s) {
    return s < 4 ? 6 : s < 10 ? 7 : s < 18 ? 8 : s < 24 ? 9 : s < 30 ? 10 : s < 38 ? 11 : s < 44 ? 12 : s < 50 ? 13 : s < 58 ? 14 : 15;
}

__device__ __align__(1024) __nv_bfloat16 g_Hs[2048 * 2048];
__device__ __align__(1024) __nv_bfloat16 g_Hf[2048 * 3584];
__device__ __align__(1024) __nv_bfloat16 g_Bcopy[2 * 1024 * 1024];
__device__ uint4 g_agg[8 * 1024];
__device__ uint2 g_gate[2048];
__device__ unsigned g_cnt[40 * 32];
__device__ __align__(1024) uint8_t g_X[128 * kXBytes];
__device__ __align__(16) unsigned g_claim[64];
__device__ unsigned g_epoch;
__device__ unsigned g_done;

#define TRAP() break
#define PIN_F(x) asm volatile("" : "+f"(x))
#define PIN_R(x) asm volatile("" : "+r"(x))
#define UNDEF_F(x) asm volatile("" : "=f"(x))
#define UNDEF_R(x) asm volatile("" : "=r"(x))
#define NEXT_IT() do { it = it_next; } while (0)
#define RESPIN()
__device__ __forceinline__ uint32_t smem_u32(const void* p) { return (uint32_t)__cvta_generic_to_shared(p); }
__device__ __forceinline__ void mbar_init(uint32_t bar, uint32_t count) {
    asm volatile("mbarrier.init.shared::cta.b64 [%0], %1;" ::"r"(bar), "r"(count) : "memory");
}
__device__ __forceinline__ void mbar_expect_tx(uint32_t bar, uint32_t bytes) {
    asm volatile("mbarrier.arrive.expect_tx.shared::cta.b64 _, [%0], %1;" ::"r"(bar), "r"(bytes) : "memory");
}
__device__ __forceinline__ void mbar_wait(uint32_t bar, uint32_t parity) {
    asm volatile(
        "{\n.reg .pred p;\n.reg .u32 n;\n"
        "mbarrier.try_wait.parity.shared::cta.b64 p, [%0], %1;\n"
        "@p bra DONE;\n"
        "mov.u32 n, 0;\n"
        "LOOP:\n"
        "mbarrier.try_wait.parity.shared::cta.b64 p, [%0], %1;\n"
        "@p bra DONE;\n"
        "add.u32 n, n, 1;\n"
        "setp.lt.u32 p, n, %2;\n"
        "@p bra LOOP;\n"
        "DONE:\n}\n"
        ::"r"(bar), "r"(parity), "n"(kSpinLimit) : "memory");
}
__device__ __forceinline__ void mbar_arrive_local(uint32_t bar) {
    asm volatile("mbarrier.arrive.shared::cta.b64 _, [%0];" ::"r"(bar) : "memory");
}
__device__ __forceinline__ void mbar_arrive_cluster(uint32_t cluster_addr) {
    asm volatile("mbarrier.arrive.shared::cluster.b64 _, [%0];" ::"r"(cluster_addr) : "memory");
}
__device__ __forceinline__ uint32_t mapa(uint32_t addr, uint32_t rank) {
    uint32_t r;
    asm("mapa.shared::cluster.u32 %0, %1, %2;" : "=r"(r) : "r"(addr), "r"(rank));
    return r;
}
__device__ __forceinline__ void cluster_arrive() { asm volatile("barrier.cluster.arrive.relaxed.aligned;" ::: "memory"); }
__device__ __forceinline__ void cluster_wait() { asm volatile("barrier.cluster.wait.acquire.aligned;" ::: "memory"); }
__device__ __forceinline__ void bar_sync(int id, int n) { asm volatile("bar.sync %0, %1;" ::"r"(id), "r"(n) : "memory"); }
__device__ __forceinline__ void bar_arrive(int id, int n) { asm volatile("bar.arrive %0, %1;" ::"r"(id), "r"(n) : "memory"); }
__device__ __forceinline__ bool elect_one() {
    uint32_t p;
    asm volatile("{\n.reg .pred P;\nelect.sync _|P, 0xffffffff;\nselp.u32 %0, 1, 0, P;\n}\n" : "=r"(p));
    return p != 0;
}

__device__ __forceinline__ void tma2(uint32_t dst, const CUtensorMap* m, uint32_t bar, int c0, int c1) {
    asm volatile("cp.async.bulk.tensor.2d.shared::cluster.global.mbarrier::complete_tx::bytes [%0], [%1, {%3, %4}], [%2];"
                 ::"r"(dst), "l"(m), "r"(bar), "r"(c0), "r"(c1) : "memory");
}
__device__ __forceinline__ void tma3(uint32_t dst, const CUtensorMap* m, uint32_t bar, int c0, int c1, int c2) {
    asm volatile("cp.async.bulk.tensor.3d.shared::cluster.global.mbarrier::complete_tx::bytes [%0], [%1, {%3, %4, %5}], [%2];"
                 ::"r"(dst), "l"(m), "r"(bar), "r"(c0), "r"(c1), "r"(c2) : "memory");
}
__device__ __forceinline__ void tma4(uint32_t dst, const CUtensorMap* m, uint32_t bar, int c0, int c1, int c2, int c3) {
    asm volatile("cp.async.bulk.tensor.4d.shared::cluster.global.mbarrier::complete_tx::bytes [%0], [%1, {%3, %4, %5, %6}], [%2];"
                 ::"r"(dst), "l"(m), "r"(bar), "r"(c0), "r"(c1), "r"(c2), "r"(c3) : "memory");
}
__device__ __forceinline__ void tma5(uint32_t dst, const CUtensorMap* m, uint32_t bar, int c0, int c1, int c2, int c3, int c4) {
    asm volatile("cp.async.bulk.tensor.5d.shared::cluster.global.mbarrier::complete_tx::bytes [%0], [%1, {%3, %4, %5, %6, %7}], [%2];"
                 ::"r"(dst), "l"(m), "r"(bar), "r"(c0), "r"(c1), "r"(c2), "r"(c3), "r"(c4) : "memory");
}
__device__ __forceinline__ void tma2_mc(uint32_t dst, const CUtensorMap* m, uint32_t bar, int c0, int c1) {
    asm volatile("cp.async.bulk.tensor.2d.shared::cluster.global.mbarrier::complete_tx::bytes.multicast::cluster [%0], [%1, {%3, %4}], [%2], %5;"
                 ::"r"(dst), "l"(m), "r"(bar), "r"(c0), "r"(c1), "h"((uint16_t)3) : "memory");
}
__device__ __forceinline__ void tma3_mc(uint32_t dst, const CUtensorMap* m, uint32_t bar, int c0, int c1, int c2) {
    asm volatile("cp.async.bulk.tensor.3d.shared::cluster.global.mbarrier::complete_tx::bytes.multicast::cluster [%0], [%1, {%3, %4, %5}], [%2], %6;"
                 ::"r"(dst), "l"(m), "r"(bar), "r"(c0), "r"(c1), "r"(c2), "h"((uint16_t)3) : "memory");
}
__device__ __forceinline__ void tma5_mc(uint32_t dst, const CUtensorMap* m, uint32_t bar, int c0, int c1, int c2, int c3, int c4) {
    asm volatile("cp.async.bulk.tensor.5d.shared::cluster.global.mbarrier::complete_tx::bytes.multicast::cluster [%0], [%1, {%3, %4, %5, %6, %7}], [%2], %8;"
                 ::"r"(dst), "l"(m), "r"(bar), "r"(c0), "r"(c1), "r"(c2), "r"(c3), "r"(c4), "h"((uint16_t)3) : "memory");
}
__device__ __forceinline__ void bulk_store(void* dst, uint32_t src, uint32_t bytes) {
    asm volatile("cp.async.bulk.global.shared::cta.bulk_group [%0], [%1], %2;" ::"l"(dst), "r"(src), "r"(bytes) : "memory");
}
__device__ __forceinline__ void bulk_load(uint32_t dst, const void* src, uint32_t bytes, uint32_t bar) {
    asm volatile("cp.async.bulk.shared::cluster.global.mbarrier::complete_tx::bytes [%0], [%1], %2, [%3];"
                 ::"r"(dst), "l"(src), "r"(bytes), "r"(bar) : "memory");
}
__device__ __forceinline__ unsigned atom_exch(unsigned* p, unsigned v) {
    unsigned r;
    asm volatile("atom.relaxed.gpu.global.exch.b32 %0, [%1], %2;" : "=r"(r) : "l"(p), "r"(v) : "memory");
    return r;
}
__device__ __forceinline__ uint32_t lds32_cluster(uint32_t a) {
    uint32_t v;
    asm volatile("ld.shared::cluster.u32 %0, [%1];" : "=r"(v) : "r"(a) : "memory");
    return v;
}
__device__ __forceinline__ void sts128f(uint32_t a, float x, float y, float z, float w) {
    asm volatile("st.shared.v4.f32 [%0], {%1, %2, %3, %4};" ::"r"(a), "f"(x), "f"(y), "f"(z), "f"(w) : "memory");
}
__device__ __forceinline__ void prefetch_map(const CUtensorMap* m) {
    asm volatile("prefetch.tensormap [%0];" ::"l"(m) : "memory");
}

__device__ __forceinline__ void prefetch_l2(const void* p, uint32_t bytes) {
    asm volatile("cp.async.bulk.prefetch.L2.global [%0], %1;" ::"l"(p), "r"(bytes) : "memory");
}

__device__ __forceinline__ void wgmma_fence() { asm volatile("wgmma.fence.sync.aligned;" ::: "memory"); }
__device__ __forceinline__ void wgmma_commit() { asm volatile("wgmma.commit_group.sync.aligned;" ::: "memory"); }
template <int N>
__device__ __forceinline__ void wgmma_wait() { asm volatile("wgmma.wait_group.sync.aligned %0;" ::"n"(N) : "memory"); }

__device__ __forceinline__ uint32_t pack_bf16(float lo, float hi) {
    uint32_t r;
    asm("cvt.rn.bf16x2.f32 %0, %1, %2;" : "=r"(r) : "f"(hi), "f"(lo));
    return r;
}
__device__ __forceinline__ uint32_t pack_f16(float lo, float hi) {
    uint32_t r;
    asm("cvt.rn.f16x2.f32 %0, %1, %2;" : "=r"(r) : "f"(hi), "f"(lo));
    return r;
}
__device__ __forceinline__ uint32_t pack_bf16_v(float lo, float hi) {
    uint32_t r;
    asm volatile("cvt.rn.bf16x2.f32 %0, %1, %2;" : "=r"(r) : "f"(hi), "f"(lo));
    return r;
}
__device__ __forceinline__ float bf_lo(uint32_t v) { return __uint_as_float(v << 16); }
__device__ __forceinline__ float bf_hi(uint32_t v) { return __uint_as_float(v & 0xffff0000u); }
__device__ __forceinline__ float bf16_round(float v) { return __bfloat162float(__float2bfloat16_rn(v)); }
__device__ __forceinline__ uint32_t bf2_mul(uint32_t a, uint32_t b) {
    uint32_t r;
    asm("mul.rn.bf16x2 %0, %1, %2;" : "=r"(r) : "r"(a), "r"(b));
    return r;
}
__device__ __forceinline__ uint32_t bf2_add_relu(uint32_t a, uint32_t b) {
    uint32_t r;
    asm("fma.rn.relu.bf16x2 %0, %1, %2, %3;" : "=r"(r) : "r"(a), "r"(0x3f803f80u), "r"(b));
    return r;
}
__device__ __forceinline__ uint4 ldg128(const void* p) {
    uint4 v;
    asm volatile("ld.global.nc.v4.u32 {%0, %1, %2, %3}, [%4];" : "=r"(v.x), "=r"(v.y), "=r"(v.z), "=r"(v.w) : "l"(p));
    return v;
}
__device__ __forceinline__ uint32_t ldg32(const void* p) {
    uint32_t v;
    asm volatile("ld.global.nc.u32 %0, [%1];" : "=r"(v) : "l"(p));
    return v;
}
__device__ __forceinline__ uint32_t ldg32na(const void* p) {
    uint32_t v;
    asm volatile("ld.global.nc.L1::no_allocate.u32 %0, [%1];" : "=r"(v) : "l"(p));
    return v;
}
__device__ __forceinline__ uint32_t ldg16(const __nv_bfloat16* p) {
    uint32_t v;
    asm volatile("ld.global.nc.u16 %0, [%1];" : "=r"(v) : "l"(p));
    return v;
}
__device__ __forceinline__ uint4 ld_relaxed128(const void* p) {
    uint4 v;
    asm volatile("ld.relaxed.gpu.global.v4.u32 {%0, %1, %2, %3}, [%4];" : "=r"(v.x), "=r"(v.y), "=r"(v.z), "=r"(v.w) : "l"(p) : "memory");
    return v;
}
__device__ __forceinline__ uint2 ld_relaxed64(const void* p) {
    unsigned long long v;
    asm volatile("ld.relaxed.gpu.global.u64 %0, [%1];" : "=l"(v) : "l"(p) : "memory");
    return make_uint2((uint32_t)v, (uint32_t)(v >> 32));
}
__device__ __forceinline__ void st_relaxed64(void* p, uint32_t lo, uint32_t hi) {
    unsigned long long v = ((unsigned long long)hi << 32) | lo;
    asm volatile("st.relaxed.gpu.global.u64 [%0], %1;" ::"l"(p), "l"(v) : "memory");
}
__device__ __forceinline__ void st_relaxed2x64(void* p, uint32_t a, uint32_t b, uint32_t c, uint32_t d) {
    unsigned long long v0 = ((unsigned long long)b << 32) | a, v1 = ((unsigned long long)d << 32) | c;
    asm volatile("st.relaxed.gpu.global.v2.u64 [%0], {%1, %2};" ::"l"(p), "l"(v0), "l"(v1) : "memory");
}
__device__ __forceinline__ uint4 ld_relaxed2x64(const void* p) {
    unsigned long long v0, v1;
    asm volatile("ld.relaxed.gpu.global.v2.u64 {%0, %1}, [%2];" : "=l"(v0), "=l"(v1) : "l"(p) : "memory");
    return make_uint4((uint32_t)v0, (uint32_t)(v0 >> 32), (uint32_t)v1, (uint32_t)(v1 >> 32));
}
__device__ __forceinline__ void stg128(void* p, uint32_t a, uint32_t b, uint32_t c, uint32_t d) {
    asm volatile("st.global.v4.u32 [%0], {%1, %2, %3, %4};" ::"l"(p), "r"(a), "r"(b), "r"(c), "r"(d) : "memory");
}
__device__ __forceinline__ void stg64f(void* p, float a, float b) {
    asm volatile("st.global.v2.f32 [%0], {%1, %2};" ::"l"(p), "f"(a), "f"(b) : "memory");
}
__device__ __forceinline__ uint4 lds128(uint32_t a) {
    uint4 v;
    asm volatile("ld.shared.v4.u32 {%0, %1, %2, %3}, [%4];" : "=r"(v.x), "=r"(v.y), "=r"(v.z), "=r"(v.w) : "r"(a) : "memory");
    return v;
}
__device__ __forceinline__ uint2 lds64(uint32_t a) {
    uint2 v;
    asm volatile("ld.shared.v2.u32 {%0, %1}, [%2];" : "=r"(v.x), "=r"(v.y) : "r"(a) : "memory");
    return v;
}
__device__ __forceinline__ uint4 ldsm4(uint32_t a) {
    uint4 v;
    asm volatile("ldmatrix.sync.aligned.m8n8.x4.shared.b16 {%0, %1, %2, %3}, [%4];" : "=r"(v.x), "=r"(v.y), "=r"(v.z), "=r"(v.w) : "r"(a) : "memory");
    return v;
}
__device__ __forceinline__ uint32_t lds16(uint32_t a) {
    uint32_t v;
    asm volatile("ld.shared.u16 %0, [%1];" : "=r"(v) : "r"(a) : "memory");
    return v;
}
__device__ __forceinline__ void sts16(uint32_t a, uint32_t x) {
    asm volatile("st.shared.u16 [%0], %1;" ::"r"(a), "h"((uint16_t)x) : "memory");
}
__device__ __forceinline__ void st_relaxed32(void* p, uint32_t v) {
    asm volatile("st.relaxed.gpu.global.u32 [%0], %1;" ::"l"(p), "r"(v) : "memory");
}
__device__ __forceinline__ float lds32f(uint32_t a) {
    float v;
    asm volatile("ld.shared.f32 %0, [%1];" : "=f"(v) : "r"(a) : "memory");
    return v;
}
__device__ __forceinline__ void sts128(uint32_t a, uint32_t x, uint32_t y, uint32_t z, uint32_t w) {
    asm volatile("st.shared.v4.u32 [%0], {%1, %2, %3, %4};" ::"r"(a), "r"(x), "r"(y), "r"(z), "r"(w) : "memory");
}
__device__ __forceinline__ void sts32(uint32_t a, uint32_t x) {
    asm volatile("st.shared.u32 [%0], %1;" ::"r"(a), "r"(x) : "memory");
}
__device__ __forceinline__ void stg128f(void* p, float a, float b, float c, float d) {
    asm volatile("st.global.v4.f32 [%0], {%1, %2, %3, %4};" ::"l"(p), "f"(a), "f"(b), "f"(c), "f"(d) : "memory");
}
__device__ __forceinline__ unsigned ld_relaxed32(const unsigned* p) {
    unsigned v;
    asm volatile("ld.relaxed.gpu.global.u32 %0, [%1];" : "=r"(v) : "l"(p) : "memory");
    return v;
}
__device__ __forceinline__ void wait_counter(const unsigned* p, unsigned target) {
    unsigned n = 0, v;
    while (true) {
        asm volatile("ld.acquire.gpu.global.u32 %0, [%1];" : "=r"(v) : "l"(p) : "memory");
        if ((int)(v - target) >= 0) break;
        if (++n > kSpinLimit) TRAP();
        __nanosleep(32);
    }
}
#define KT(IT, W) do { } while (0)
#define STAMP(cond, slot) do { } while (0)

template <int TA, int TB>
__device__ __forceinline__ void wgmma_n256(float (&d)[128], uint64_t da, uint64_t db, int keep) {
    asm volatile(
        "{\n.reg .pred p;\nsetp.ne.b32 p, %132, 0;\n"
        "wgmma.mma_async.sync.aligned.m64n256k16.f32.bf16.bf16 "
        "{%0, %1, %2, %3, %4, %5, %6, %7, %8, %9, %10, %11, %12, %13, %14, %15, "
        "%16, %17, %18, %19, %20, %21, %22, %23, %24, %25, %26, %27, %28, %29, %30, %31, "
        "%32, %33, %34, %35, %36, %37, %38, %39, %40, %41, %42, %43, %44, %45, %46, %47, "
        "%48, %49, %50, %51, %52, %53, %54, %55, %56, %57, %58, %59, %60, %61, %62, %63, "
        "%64, %65, %66, %67, %68, %69, %70, %71, %72, %73, %74, %75, %76, %77, %78, %79, "
        "%80, %81, %82, %83, %84, %85, %86, %87, %88, %89, %90, %91, %92, %93, %94, %95, "
        "%96, %97, %98, %99, %100, %101, %102, %103, %104, %105, %106, %107, %108, %109, %110, %111, "
        "%112, %113, %114, %115, %116, %117, %118, %119, %120, %121, %122, %123, %124, %125, %126, %127}, "
        "%128, %129, p, 1, 1, %130, %131;\n}\n"
        : "+f"(d[0]), "+f"(d[1]), "+f"(d[2]), "+f"(d[3]), "+f"(d[4]), "+f"(d[5]), "+f"(d[6]), "+f"(d[7]),
          "+f"(d[8]), "+f"(d[9]), "+f"(d[10]), "+f"(d[11]), "+f"(d[12]), "+f"(d[13]), "+f"(d[14]), "+f"(d[15]),
          "+f"(d[16]), "+f"(d[17]), "+f"(d[18]), "+f"(d[19]), "+f"(d[20]), "+f"(d[21]), "+f"(d[22]), "+f"(d[23]),
          "+f"(d[24]), "+f"(d[25]), "+f"(d[26]), "+f"(d[27]), "+f"(d[28]), "+f"(d[29]), "+f"(d[30]), "+f"(d[31]),
          "+f"(d[32]), "+f"(d[33]), "+f"(d[34]), "+f"(d[35]), "+f"(d[36]), "+f"(d[37]), "+f"(d[38]), "+f"(d[39]),
          "+f"(d[40]), "+f"(d[41]), "+f"(d[42]), "+f"(d[43]), "+f"(d[44]), "+f"(d[45]), "+f"(d[46]), "+f"(d[47]),
          "+f"(d[48]), "+f"(d[49]), "+f"(d[50]), "+f"(d[51]), "+f"(d[52]), "+f"(d[53]), "+f"(d[54]), "+f"(d[55]),
          "+f"(d[56]), "+f"(d[57]), "+f"(d[58]), "+f"(d[59]), "+f"(d[60]), "+f"(d[61]), "+f"(d[62]), "+f"(d[63]),
          "+f"(d[64]), "+f"(d[65]), "+f"(d[66]), "+f"(d[67]), "+f"(d[68]), "+f"(d[69]), "+f"(d[70]), "+f"(d[71]),
          "+f"(d[72]), "+f"(d[73]), "+f"(d[74]), "+f"(d[75]), "+f"(d[76]), "+f"(d[77]), "+f"(d[78]), "+f"(d[79]),
          "+f"(d[80]), "+f"(d[81]), "+f"(d[82]), "+f"(d[83]), "+f"(d[84]), "+f"(d[85]), "+f"(d[86]), "+f"(d[87]),
          "+f"(d[88]), "+f"(d[89]), "+f"(d[90]), "+f"(d[91]), "+f"(d[92]), "+f"(d[93]), "+f"(d[94]), "+f"(d[95]),
          "+f"(d[96]), "+f"(d[97]), "+f"(d[98]), "+f"(d[99]), "+f"(d[100]), "+f"(d[101]), "+f"(d[102]), "+f"(d[103]),
          "+f"(d[104]), "+f"(d[105]), "+f"(d[106]), "+f"(d[107]), "+f"(d[108]), "+f"(d[109]), "+f"(d[110]), "+f"(d[111]),
          "+f"(d[112]), "+f"(d[113]), "+f"(d[114]), "+f"(d[115]), "+f"(d[116]), "+f"(d[117]), "+f"(d[118]), "+f"(d[119]),
          "+f"(d[120]), "+f"(d[121]), "+f"(d[122]), "+f"(d[123]), "+f"(d[124]), "+f"(d[125]), "+f"(d[126]), "+f"(d[127])
        : "l"(da), "l"(db), "n"(TA), "n"(TB), "r"(keep));
}
template <int TA, int TB>
__device__ __forceinline__ void wgmma_n192(float (&d)[128], uint64_t da, uint64_t db, int keep) {
    asm volatile(
        "{\n.reg .pred p;\nsetp.ne.b32 p, %100, 0;\n"
        "wgmma.mma_async.sync.aligned.m64n192k16.f32.bf16.bf16 "
        "{%0, %1, %2, %3, %4, %5, %6, %7, %8, %9, %10, %11, %12, %13, %14, %15, "
        "%16, %17, %18, %19, %20, %21, %22, %23, %24, %25, %26, %27, %28, %29, %30, %31, "
        "%32, %33, %34, %35, %36, %37, %38, %39, %40, %41, %42, %43, %44, %45, %46, %47, "
        "%48, %49, %50, %51, %52, %53, %54, %55, %56, %57, %58, %59, %60, %61, %62, %63, "
        "%64, %65, %66, %67, %68, %69, %70, %71, %72, %73, %74, %75, %76, %77, %78, %79, "
        "%80, %81, %82, %83, %84, %85, %86, %87, %88, %89, %90, %91, %92, %93, %94, %95}, "
        "%96, %97, p, 1, 1, %98, %99;\n}\n"
        : "+f"(d[0]), "+f"(d[1]), "+f"(d[2]), "+f"(d[3]), "+f"(d[4]), "+f"(d[5]), "+f"(d[6]), "+f"(d[7]),
          "+f"(d[8]), "+f"(d[9]), "+f"(d[10]), "+f"(d[11]), "+f"(d[12]), "+f"(d[13]), "+f"(d[14]), "+f"(d[15]),
          "+f"(d[16]), "+f"(d[17]), "+f"(d[18]), "+f"(d[19]), "+f"(d[20]), "+f"(d[21]), "+f"(d[22]), "+f"(d[23]),
          "+f"(d[24]), "+f"(d[25]), "+f"(d[26]), "+f"(d[27]), "+f"(d[28]), "+f"(d[29]), "+f"(d[30]), "+f"(d[31]),
          "+f"(d[32]), "+f"(d[33]), "+f"(d[34]), "+f"(d[35]), "+f"(d[36]), "+f"(d[37]), "+f"(d[38]), "+f"(d[39]),
          "+f"(d[40]), "+f"(d[41]), "+f"(d[42]), "+f"(d[43]), "+f"(d[44]), "+f"(d[45]), "+f"(d[46]), "+f"(d[47]),
          "+f"(d[48]), "+f"(d[49]), "+f"(d[50]), "+f"(d[51]), "+f"(d[52]), "+f"(d[53]), "+f"(d[54]), "+f"(d[55]),
          "+f"(d[56]), "+f"(d[57]), "+f"(d[58]), "+f"(d[59]), "+f"(d[60]), "+f"(d[61]), "+f"(d[62]), "+f"(d[63]),
          "+f"(d[64]), "+f"(d[65]), "+f"(d[66]), "+f"(d[67]), "+f"(d[68]), "+f"(d[69]), "+f"(d[70]), "+f"(d[71]),
          "+f"(d[72]), "+f"(d[73]), "+f"(d[74]), "+f"(d[75]), "+f"(d[76]), "+f"(d[77]), "+f"(d[78]), "+f"(d[79]),
          "+f"(d[80]), "+f"(d[81]), "+f"(d[82]), "+f"(d[83]), "+f"(d[84]), "+f"(d[85]), "+f"(d[86]), "+f"(d[87]),
          "+f"(d[88]), "+f"(d[89]), "+f"(d[90]), "+f"(d[91]), "+f"(d[92]), "+f"(d[93]), "+f"(d[94]), "+f"(d[95])
        : "l"(da), "l"(db), "n"(TA), "n"(TB), "r"(keep));
}
template <int TA, int TB>
__device__ __forceinline__ void wgmma_n128(float (&d)[128], uint64_t da, uint64_t db, int keep) {
    asm volatile(
        "{\n.reg .pred p;\nsetp.ne.b32 p, %68, 0;\n"
        "wgmma.mma_async.sync.aligned.m64n128k16.f32.bf16.bf16 "
        "{%0, %1, %2, %3, %4, %5, %6, %7, %8, %9, %10, %11, %12, %13, %14, %15, "
        "%16, %17, %18, %19, %20, %21, %22, %23, %24, %25, %26, %27, %28, %29, %30, %31, "
        "%32, %33, %34, %35, %36, %37, %38, %39, %40, %41, %42, %43, %44, %45, %46, %47, "
        "%48, %49, %50, %51, %52, %53, %54, %55, %56, %57, %58, %59, %60, %61, %62, %63}, "
        "%64, %65, p, 1, 1, %66, %67;\n}\n"
        : "+f"(d[0]), "+f"(d[1]), "+f"(d[2]), "+f"(d[3]), "+f"(d[4]), "+f"(d[5]), "+f"(d[6]), "+f"(d[7]),
          "+f"(d[8]), "+f"(d[9]), "+f"(d[10]), "+f"(d[11]), "+f"(d[12]), "+f"(d[13]), "+f"(d[14]), "+f"(d[15]),
          "+f"(d[16]), "+f"(d[17]), "+f"(d[18]), "+f"(d[19]), "+f"(d[20]), "+f"(d[21]), "+f"(d[22]), "+f"(d[23]),
          "+f"(d[24]), "+f"(d[25]), "+f"(d[26]), "+f"(d[27]), "+f"(d[28]), "+f"(d[29]), "+f"(d[30]), "+f"(d[31]),
          "+f"(d[32]), "+f"(d[33]), "+f"(d[34]), "+f"(d[35]), "+f"(d[36]), "+f"(d[37]), "+f"(d[38]), "+f"(d[39]),
          "+f"(d[40]), "+f"(d[41]), "+f"(d[42]), "+f"(d[43]), "+f"(d[44]), "+f"(d[45]), "+f"(d[46]), "+f"(d[47]),
          "+f"(d[48]), "+f"(d[49]), "+f"(d[50]), "+f"(d[51]), "+f"(d[52]), "+f"(d[53]), "+f"(d[54]), "+f"(d[55]),
          "+f"(d[56]), "+f"(d[57]), "+f"(d[58]), "+f"(d[59]), "+f"(d[60]), "+f"(d[61]), "+f"(d[62]), "+f"(d[63])
        : "l"(da), "l"(db), "n"(TA), "n"(TB), "r"(keep));
}

template <int MODE>
__device__ __forceinline__ void mma_kblock(float (&acc)[128], uint32_t a_lo, uint32_t b_lo, int keep) {
    constexpr uint64_t HI = (uint64_t)(64u | 0x40000000u) << 32;
    constexpr uint32_t HALF = (MODE == 1) ? 12288u : 16384u;
    constexpr bool BN = (MODE == 1 || MODE == 2 || MODE == 4);
#pragma unroll
    for (int kk = 0; kk < 4; ++kk) {
        const uint32_t ao = (MODE == 3) ? kk * 2048u : kk * 32u;
        const uint32_t bo = BN ? ((kk >> 1) * HALF + (kk & 1) * 2048u) : kk * 32u;
        const uint64_t da = HI | (uint64_t)(a_lo + (ao >> 4) + (1u << 16));
        const uint64_t db = HI | (uint64_t)(b_lo + (bo >> 4) + (BN ? (256u << 16) : (1u << 16)));
        if (MODE == 1) wgmma_n192<0, 1>(acc, da, db, kk == 0 ? keep : 1);
        else if (MODE == 4) wgmma_n128<0, 1>(acc, da, db, 1);
        else wgmma_n256<(MODE == 3), BN>(acc, da, db, kk == 0 ? keep : 1);
    }
}

struct Params {
    const __nv_bfloat16* x;
    const __nv_bfloat16* lam_re;
    const __nv_bfloat16* lam_im;
    const __nv_bfloat16* log_dt;
    const __nv_bfloat16* dskip;
    const __nv_bfloat16* b1;
    const __nv_bfloat16* b2;
    const __nv_bfloat16* gate_w;
    const __nv_bfloat16* w1;
    const __nv_bfloat16* w2;
    const __nv_bfloat16* c_re;
    const __nv_bfloat16* c_im;
    const __nv_bfloat16* b_re;
    const __nv_bfloat16* b_im;
    float* out;
    int swap;
};

#define CMUL(rr, ri, ar, ai, br, bi) do { float _r = (ar) * (br) - (ai) * (bi); float _i = (ar) * (bi) + (ai) * (br); rr = _r; ri = _i; } while (0)
#define CFMA(rr, ri, ar, ai, br, bi) do { float _r = fmaf(-(ai), (bi), fmaf((ar), (br), rr)); float _i = fmaf((ai), (br), fmaf((ar), (bi), ri)); rr = _r; ri = _i; } while (0)

#define KBLOCK(MODE, KEEP, REL)                                                                  \
    {                                                                                            \
        const uint32_t so = (it & 3) * (kStageBytes >> 4);                                       \
        KT(it, 0);                                                                               \
        mbar_wait(bar_full + 8 * (it & 3), (it >> 2) & 1);                                       \
        KT(it, 1);                                                                               \
        wgmma_fence();                                                                           \
        mma_kblock<MODE>(acc, a_lo + so, b_lo + so, KEEP);                                       \
        wgmma_commit();                                                                          \
        it_next = __shfl_sync(0xffffffffu, it + 1, 0);                                           \
        wgmma_wait<1>();                                                                         \
        if (lane < 2 && (REL)) mbar_arrive_cluster(rel_addr + 8 * ((it - 1) & 3));               \
    }
#define TILE_END() do { wgmma_wait<0>(); if (lane < 2) mbar_arrive_cluster(rel_addr + 24); } while (0)

__global__ void __cluster_dims__(2, 1, 1) __launch_bounds__(384, 1)
fused_kernel(const __grid_constant__ CUtensorMap mB, const __grid_constant__ CUtensorMap mXs, const __grid_constant__ CUtensorMap mXf,
             const __grid_constant__ CUtensorMap mW1a, const __grid_constant__ CUtensorMap mW1b, const __grid_constant__ CUtensorMap mHs,
             const __grid_constant__ CUtensorMap mHf, const __grid_constant__ CUtensorMap mCre, const __grid_constant__ CUtensorMap mCim,
             const __grid_constant__ CUtensorMap mW2, const Params p) {
    extern __shared__ __align__(1024) uint8_t smem_raw[];
    const uint32_t sbase = smem_u32(smem_raw);
    if ((sbase & 0x3ffffu) != kSmemOrg) return;
    const uint32_t bar_full = sbase + kBarOff, bar_empty = bar_full + 32, bar_dep = bar_full + 64;
    const uint32_t bar_x = bar_full + 88, role_s = bar_full + 96;

    const int tid = threadIdx.x, lane = tid & 31;
    const int warp = __shfl_sync(0xffffffffu, tid >> 5, 0);
    const uint32_t rank = blockIdx.x & 1;

    int pref;
    {
        unsigned smid;
        asm("mov.u32 %0, %%smid;" : "=r"(smid));
        const int t = smid >> 1, u = t - 32, d = (u * 37) >> 8;
        pref = (t < 32) ? (t & 7) * 8 + (t >> 3) : (t < 60) ? (1 + u - 7 * d) * 8 + 4 + d : ((t - 58) & 7);
    }
#define FIRST_FILL(ROLE)                                                                     \
    {                                                                                        \
        mbar_expect_tx(bar_full, 49152);                                                     \
        tma4(sbase, &mB, bar_full, 0, 0, 0, (((ROLE) & 7) * 2 + (int)rank) * 8);             \
        tma5(sbase + kABytes, &mXs, bar_full, 0, 0, 0, 0, (ROLE) >> 3);                      \
        tma5(sbase + kABytes + 16384, &mXs, bar_full, 0, 0, 0, 16, (ROLE) >> 3);             \
    }
    STAMP(tid == 0, 0);
    if (warp == 0) {
        if (elect_one()) {
            prefetch_map(&mB); prefetch_map(&mXs);
#pragma unroll
            for (int s = 0; s < kStages; ++s) {
                mbar_init(bar_full + 8 * s, 1);
                mbar_init(bar_empty + 8 * s, 16);
                mbar_init(bar_dep + 8 * s, 1);
            }
            asm volatile("fence.mbarrier_init.release.cluster;\nfence.proxy.async.shared::cta;" ::: "memory");
            FIRST_FILL(pref);
            mbar_expect_tx(bar_x, 2048);
            bulk_load(sbase + kXOff, p.gate_w, 2048, bar_x);
        }
    } else if (warp == 1) {
        if (rank == 0 && elect_one()) {
            int role = pref;
            unsigned taken = atom_exch(&g_claim[pref], 1u);
#pragma unroll 1
            for (int i = 0; taken != 0 && i < 64; ++i) { role = i; taken = atom_exch(&g_claim[i], 1u); }
            sts32(role_s, role);
            asm volatile("fence.acq_rel.cluster;" ::: "memory");
        }
    } else if (warp >= 4 && warp < 4 + PF0LINES) {
        const int row = blockIdx.x * 32 + lane;
        const __nv_bfloat16* src = (row < 2048) ? p.x + (size_t)row * kD : (row < 3072) ? p.b_re + (size_t)(row - 2048) * kD : p.b_im + (size_t)(row - 3072) * kD;
        asm volatile("prefetch.global.L2 [%0];" ::"l"(src + (warp - 4) * 64) : "memory");
    }
    __syncwarp();
    cluster_arrive();
    cluster_wait();
    const int role = __shfl_sync(0xffffffffu, (int)lds32_cluster(mapa(role_s, 0)), 0);
    if (__builtin_expect(role != pref, 0)) {
        if (warp == 0 && elect_one()) {
            mbar_wait(bar_full, 0);
            asm volatile("mbarrier.inval.shared::cta.b64 [%0];" ::"r"(bar_full) : "memory");
            mbar_init(bar_full, 1);
            asm volatile("fence.mbarrier_init.release.cluster;\nfence.proxy.async.shared::cta;" ::: "memory");
            FIRST_FILL(role);
        }
        __syncwarp();
        bar_sync(0, 384);
    }
    const int c = role >> 3;
    const int j8 = role & 7;
    const int cb = j8 * 2 + (int)rank;
    const int rb = 2 * c + (int)rank;
    const int kh = j8 >> 2;
    const int colK = (j8 & 3) * 256 + kh * 128, colS = colK ^ 128;

    if (warp >= 8) {
        asm volatile("setmaxnreg.dec.sync.aligned.u32 24;");
        if (warp == 8) {
            if (elect_one()) {
                int it = 1;
#define ACQUIRE(BYTES)                                                   \
    const uint32_t st = sbase + (it & 3) * kStageBytes, fb = bar_full + 8 * (it & 3); \
    mbar_wait(bar_empty + 8 * (it & 3), ((it >> 2) & 1) ^ 1);            \
    mbar_expect_tx(fb, BYTES);
#pragma unroll 1
                for (; it < 16; ++it) {
                    ACQUIRE(49152);
                    tma4(st, &mB, fb, it * 64, 0, 0, cb * 8);
                    tma5_mc(st + kABytes + rank * 16384, &mXs, fb, it * 64, 0, 0, rank * 16, c);
                }
#pragma unroll 1
                for (; it < 48; ++it) {
                    const bool t1 = it < 32;
                    const int k0 = (it & 15) * 64;
                    ACQUIRE(t1 ? 40960 : 49152);
                    tma5(st, &mXf, fb, k0, 0, 0, rank * 4, c);
                    tma3_mc(st + kABytes + rank * (t1 ? 12288 : 16384), t1 ? &mW1b : &mW1a, fb, 0, k0 + rank * 32, t1 ? 32 + 3 * j8 : 4 * j8);
                    if ((it & ~2) == 32 + XLDKB) {
                        const int h = (it >> 1) & 1;
                        if (h == 0) mbar_expect_tx(bar_x, 32768);
                        tma5(sbase + kXOff + h * 16384, &mXf, bar_x, colK + h * 64, 0, 0, rank * 4, c);
                    }
                }
                STAMP(true, 8);
                mbar_wait(bar_dep, 0);
                asm volatile("fence.proxy.async.global;" ::: "memory");
                STAMP(true, 9);
#pragma unroll 1
                for (; it < 64; ++it) {
                    const int k0 = (it & 15) * 64;
                    ACQUIRE(49152);
                    tma3(st, &mHs, fb, 0, kh * 1024 + k0, rb * 2);
                    tma2_mc(st + kABytes + rank * 16384, kh ? &mCim : &mCre, fb, k0, rank ? colS : colK);
                }
                int f0 = 2048 + 768 * kh;
#pragma unroll 1
                for (; it < kTotal; ++it, f0 += 64) {
                    if (it == 64 || it == 76) {
                        mbar_wait(bar_dep + (it == 64 ? 8 : 16), 0);
                        asm volatile("fence.proxy.async.global;" ::: "memory");
                        if (it == 76) f0 = 64 * kNA * kh;
                    }
                    if (it == 64 + kNF) f0 = 128 * kNA;
                    const bool full = it < 64 + kNF;
                    ACQUIRE(full ? 49152 : 32768);
                    tma2(st, &mHf, fb, f0, rb * 128);
                    tma5_mc(st + kABytes + rank * 16384, &mW2, fb, 0, 0, (f0 >> 3) + 4 * rank, 0, colK >> 6);
                    if (full) tma5_mc(st + kABytes + rank * 16384 + 8192, &mW2, fb, 0, 0, (f0 >> 3) + 4 * rank, 0, colS >> 6);
                }
            }
        } else if (warp == 9) {
#pragma unroll 1
            for (int ev = 0; ev < 3; ++ev) {
                bar_sync(3 + ev, 288);
                if (lane == 0) {
                    unsigned* cnt = &g_cnt[(ev == 0 ? c : 16 * ev - 8 + rb) * 32];
                    asm volatile("fence.acq_rel.gpu;\nfence.proxy.async.global;" ::: "memory");
                    asm volatile("red.relaxed.gpu.global.add.u32 [%0], 1;" ::"l"(cnt) : "memory");
                }
                __syncwarp();
            }
        } else if (warp == 10) {
            if (lane == 0) {
                const unsigned tag = ld_relaxed32(&g_epoch) + 1;
#pragma unroll 1
                for (int ev = 0; ev < 3; ++ev) {
                    wait_counter(&g_cnt[(ev == 0 ? c : 16 * ev - 8 + rb) * 32], tag * (ev == 0 ? 16u : 8u));
                    mbar_arrive_local(bar_dep + 8 * ev);
                    if (ev == 0 && atomicInc(&g_done, 127u) == 127u) {
                        asm volatile("st.relaxed.gpu.global.u32 [%0], %1;" ::"l"(&g_epoch), "r"(tag) : "memory");
#pragma unroll 1
                        for (int i = 0; i < 64; i += 4) stg128(&g_claim[i], 0, 0, 0, 0);
                    }
                }
            }
        } else {
            if (lane < 8) {
                const CUtensorMap* m = lane == 0 ? &mXf : lane == 1 ? &mW1b : lane == 2 ? &mW1a : lane == 3 ? &mHs : lane == 4 ? &mHf : lane == 5 ? &mCre : lane == 6 ? &mCim : &mW2;
                prefetch_map(m);
            }
        }
    } else {
        asm volatile("setmaxnreg.inc.sync.aligned.u32 240;");
        const int wg = warp >> 2, w = warp & 3, r = lane >> 2, q = lane & 3, tw = tid & 127;
        const uint32_t a_lo = (kSmemOrg + wg * 8192) >> 4;
        constexpr uint32_t b_lo = (kSmemOrg + kABytes) >> 4;
        const uint32_t rel_addr = mapa(bar_empty, (uint32_t)(lane & 1));
        const uint32_t gate_s = sbase + kGateOff, bias_s = sbase + kBiasOff;
        float acc[128];
        uint32_t pk[64];
        unsigned tag = ld_relaxed32(&g_epoch);
        uint32_t it = 0, it_next;

        const int ch = cb * 64 + warp * 8 + r;
        float lr, li, m00, m01, m10, m11;
        float l64r, l64i, l128r, l128i, w0r, w0i, w1r, w1i;
        UNDEF_F(lr); UNDEF_F(li); UNDEF_F(m00); UNDEF_F(m01); UNDEF_F(m10); UNDEF_F(m11); UNDEF_F(l64r); UNDEF_F(l64i);
        UNDEF_F(l128r); UNDEF_F(l128i); UNDEF_F(w0r); UNDEF_F(w0i); UNDEF_F(w1r); UNDEF_F(w1i);
#pragma unroll
        for (int i = 0; i < 128; ++i) UNDEF_F(acc[i]);
        {
            uint32_t Lr_ = ldg16(p.lam_re + ch), Li_ = ldg16(p.lam_im + ch), Ldt_ = ldg16(p.log_dt + ch);
            uint32_t bz[4] = {0, 0, 0, 0};
            if (tw < 88) {
                const int J = tw >> 2;
                const __nv_bfloat16* src = (J < 6) ? p.b1 + 2048 + 192 * j8 + 32 * J
                                         : (J < 14) ? p.b1 + 256 * j8 + 32 * (J - 6)
                                         : (J < 18) ? p.dskip + colK + 32 * (J - 14) : p.b2 + colK + 32 * (J - 18);
#pragma unroll
                for (int jj = 0; jj < 4; ++jj) bz[jj] = ldg32(src + 8 * jj + 2 * (tw & 3));
            }
            const uint32_t gx_s = sbase + kABytes + (16 * cb + 2 * warp + (lane >> 4)) * 128 +
                                  ((((lane & 15) >> 1) ^ (2 * w + (lane >> 4))) << 4) + (lane & 1) * 8;
            const uint32_t gw_s = sbase + kXOff + (lane & 15) * 8;
            float gs = 0.f;
            mbar_wait(bar_x, 0);
#pragma unroll 1
            do {
                KBLOCK(0, it, it != 0);
                {
                    const uint2 xa = lds64(gx_s + (it & 3) * kStageBytes), wa = lds64(gw_s + it * 128);
                    const uint32_t pa = bf2_mul(xa.x, wa.x), pb = bf2_mul(xa.y, wa.y);
                    gs += (bf_lo(pa) + bf_hi(pa)) + (bf_lo(pb) + bf_hi(pb));
                }
                switch (it) {
                case 3: {
                    PIN_R(Lr_); PIN_R(Ldt_);
                    m00 = bf16_round(expf(bf_lo(Ldt_)));
                    m01 = expf(m00 * bf_lo(Lr_));
                } break;
                case 4: {
                    float sn, cs;
                    PIN_R(Li_);
                    sincospif((m00 * bf_lo(Li_)) * 0.31830988618379067f, &sn, &cs);
                    lr = m01 * cs; li = m01 * sn;
                } break;
                case 5: {
                    PIN_R(Lr_); PIN_R(Li_);
                    const float Lr = bf_lo(Lr_), Li = bf_lo(Li_);
                    const float nr = lr - 1.0f, ni = li;
                    const bool big = fabsf(Lr) >= fabsf(Li);
                    const float u = big ? Lr : Li, v = big ? Li : Lr;
                    const float t = v / u, d = 1.0f / fmaf(v, t, u);
                    const float cr = (big ? fmaf(ni, t, nr) : fmaf(nr, t, ni)) * d, ci = (big ? fmaf(-nr, t, ni) : fmaf(ni, t, -nr)) * d;
                    if (p.swap) { li = -li; m00 = -2.f * ci; m01 = 2.f * cr; m10 = -2.f * cr; m11 = -2.f * ci; }
                    else { m00 = 2.f * cr; m01 = -2.f * ci; m10 = -2.f * ci; m11 = -2.f * cr; }
                } break;
                case 6: {
                    PIN_R(tag); tag += 1;
                    if (tw < 88) sts128(bias_s + tw * 16, bz[0], bz[1], bz[2], bz[3]);
                    l64r = lr; l64i = li;
#pragma unroll
                    for (int i = 0; i < 6; ++i) CMUL(l64r, l64i, l64r, l64i, l64r, l64i);
                    CMUL(l128r, l128i, l64r, l64i, l64r, l64i);
                } break;
                case 7: {
                    float l256r, l256i, l512r, l512i, l1kr, l1ki;
                    CMUL(l256r, l256i, l128r, l128i, l128r, l128i);
                    CMUL(l512r, l512i, l256r, l256i, l256r, l256i);
                    CMUL(l1kr, l1ki, l512r, l512i, l512r, l512i);
                    const int n2 = max(c - 1 - q, 0);
                    w1r = (n2 & 1) ? l256r : 1.f; w1i = (n2 & 1) ? l256i : 0.f;
                    if (n2 & 2) CMUL(w1r, w1i, w1r, w1i, l512r, l512i);
                    w0r = w1r; w0i = w1i;
                    if (n2 & 4) CMUL(w0r, w0i, w0r, w0i, l1kr, l1ki);
                } break;
                case 15: {
#pragma unroll
                    for (int o = 8; o > 0; o >>= 1) gs += __shfl_xor_sync(0xffffffffu, gs, o);
                    if ((lane & 15) == 0) {
                        const float z = bf16_round(gs);
                        const float g = bf16_round(1.0f / (1.0f + expf(-z)));
                        st_relaxed64(&g_gate[c * 256 + (lane >> 4) + 64 * w + 4 * cb + 2 * wg], __float_as_uint(g), tag);
                    }
                    __syncwarp();
                } break;
                default: break;
                }
                NEXT_IT();
            } while (it < 16);
            TILE_END();
        }
        STAMP(tid == 0, 2);
#pragma unroll
        for (int s = 0; s < 64; ++s) pk[s] = pack_bf16_v(acc[4 * (s >> 1) + (s & 1)], acc[4 * (s >> 1) + 2 + (s & 1)]);
#pragma unroll
        for (int i = 0; i < 96; ++i) UNDEF_F(acc[i]);

        {
            float hr = 0.f, hi = 0.f;
            uint4 av0, av1, gv;
            uint32_t gg[4], orr[4], oii[4];
            UNDEF_R(av0.x); UNDEF_R(av0.y); UNDEF_R(av0.z); UNDEF_R(av0.w); UNDEF_R(av1.x); UNDEF_R(av1.y); UNDEF_R(av1.z); UNDEF_R(av1.w);
            UNDEF_R(gv.x); UNDEF_R(gv.y); UNDEF_R(gv.z); UNDEF_R(gv.w);
#pragma unroll
            for (int i = 0; i < 4; ++i) { UNDEF_R(gg[i]); UNDEF_R(orr[i]); UNDEF_R(oii[i]); }
            __nv_bfloat16* hs = g_Hs + (size_t)ch * 2048 + c * 256 + q * 8;
#define PASS1(KB)                                                                                      \
    _Pragma("unroll") for (int s = (KB) * 16; s < (KB) * 16 + 16; ++s) {                               \
        PIN_R(pk[s]);                                                                                  \
        float nr = bf_lo(pk[s]), ni = bf_hi(pk[s]);                                                    \
        CFMA(nr, ni, lr, li, hr, hi);                                                                  \
        hr = nr; hi = ni;                                                                              \
    }
#define PASS2(KB)                                                                                      \
    _Pragma("unroll") for (int s = 0; s < 64; s += 2) {                                                \
        if (pass2_kb(s) != (KB)) continue;                                                             \
        if ((s & 7) == 0) {                                                                            \
            const uint4 ga = lds128(gate_s + (q * 72 + s) * 2);                                        \
            gg[0] = ga.x; gg[1] = ga.y; gg[2] = ga.z; gg[3] = ga.w;                                    \
        }                                                                                              \
        float o0[2], o1[2];                                                                            \
        _Pragma("unroll") for (int k = 0; k < 2; ++k) {                                                \
            PIN_R(pk[s + k]);                                                                          \
            float nr = bf_lo(pk[s + k]), ni = bf_hi(pk[s + k]);                                        \
            CFMA(nr, ni, lr, li, hr, hi);                                                              \
            hr = nr; hi = ni;                                                                          \
            o0[k] = fmaf(m00, hr, m01 * hi);                                                           \
            o1[k] = fmaf(m10, hr, m11 * hi);                                                           \
        }                                                                                              \
        orr[(s >> 1) & 3] = bf2_mul(pack_bf16(o0[0], o0[1]), gg[(s >> 1) & 3]);                        \
        oii[(s >> 1) & 3] = bf2_mul(pack_bf16(o1[0], o1[1]), gg[(s >> 1) & 3]);                        \
        if ((s & 7) == 6) {                                                                            \
            stg128(hs + 32 * (s >> 3), orr[0], orr[1], orr[2], orr[3]);                                \
            stg128(hs + 1024 * 2048 + 32 * (s >> 3), oii[0], oii[1], oii[2], oii[3]);                  \
        }                                                                                              \
    }
#pragma unroll 1
            do {
                KBLOCK(1, it - 16, it != 16);
                switch (it - 16) {
                case 0: PASS1(0); break;
                case 1: PASS1(1); break;
                case 2: PASS1(2); gv = ld_relaxed2x64(&g_gate[c * 256 + 2 * tw]); break;
                case 3: {
                    PASS1(3);
                    float tr = __shfl_up_sync(0xffffffffu, hr, 1, 4), ti = __shfl_up_sync(0xffffffffu, hi, 1, 4);
                    if (q >= 1) CFMA(hr, hi, l64r, l64i, tr, ti);
                    tr = __shfl_up_sync(0xffffffffu, hr, 2, 4); ti = __shfl_up_sync(0xffffffffu, hi, 2, 4);
                    if (q >= 2) CFMA(hr, hi, l128r, l128i, tr, ti);
                    if (q == 3) st_relaxed2x64(&g_agg[c * 1024 + ch], __float_as_uint(hr), tag, __float_as_uint(hi), tag);
                    tr = __shfl_up_sync(0xffffffffu, hr, 1, 4); ti = __shfl_up_sync(0xffffffffu, hi, 1, 4);
                    hr = (q >= 1) ? tr : 0.f; hi = (q >= 1) ? ti : 0.f;
                } break;
                case 4: {
                    unsigned n = 0;
                    while (__any_sync(0xffffffffu, gv.y != tag || gv.w != tag)) {
                        if (++n > kSpinLimit) TRAP();
                        gv = ld_relaxed2x64(&g_gate[c * 256 + 2 * tw]);
                    }
                    sts32(gate_s + ((tw >> 5) * 72 + 2 * lane) * 2, __byte_perm(gv.x, gv.z, 0x7632));
                    if (!(q & 1)) { l64r = 1.f; l64i = 0.f; }
                    if (q & 2) CMUL(l64r, l64i, l64r, l64i, l128r, l128i);
                } break;
                case 5: {
                    av0 = make_uint4(0, tag, 0, tag); av1 = av0;
                    if (q < c) av0 = ld_relaxed2x64(&g_agg[q * 1024 + ch]);
                    if (q + 4 < c) av1 = ld_relaxed2x64(&g_agg[(q + 4) * 1024 + ch]);
                    bar_sync(1 + wg, 128);
                } break;
                case 6: {
                    unsigned n = 0;
                    while (__any_sync(0xffffffffu, av0.y != tag || av0.w != tag || av1.y != tag || av1.w != tag)) {
                        if (++n > kSpinLimit) TRAP();
                        if (q < c) av0 = ld_relaxed2x64(&g_agg[q * 1024 + ch]);
                        if (q + 4 < c) av1 = ld_relaxed2x64(&g_agg[(q + 4) * 1024 + ch]);
                    }
                    float vr, vi;
                    CMUL(vr, vi, w0r, w0i, __uint_as_float(av0.x), __uint_as_float(av0.z));
                    CFMA(vr, vi, w1r, w1i, __uint_as_float(av1.x), __uint_as_float(av1.z));
                    vr += __shfl_xor_sync(0xffffffffu, vr, 1); vi += __shfl_xor_sync(0xffffffffu, vi, 1);
                    vr += __shfl_xor_sync(0xffffffffu, vr, 2); vi += __shfl_xor_sync(0xffffffffu, vi, 2);
                    CFMA(hr, hi, l64r, l64i, vr, vi);
                    PASS2(6);
                } break;
                case 7: PASS2(7); break;
                case 8: PASS2(8); break;
                case 9: PASS2(9); break;
                case 10: PASS2(10); break;
                case 11: PASS2(11); break;
                case 12: PASS2(12); break;
                case 13: PASS2(13); break;
                case 14: PASS2(14); break;
                default: PASS2(15); bar_arrive(3, 288); break;
                }
                NEXT_IT();
            } while (it < 32);
            TILE_END();
        }
        STAMP(tid == 0, 3);
#pragma unroll
        for (int i = 0; i < 48; ++i) pk[i] = pack_bf16_v(acc[2 * i], acc[2 * i + 1]);
#pragma unroll
        for (int i = 0; i < 128; ++i) UNDEF_F(acc[i]);

        const uint32_t gate_row = gate_s + ((2 * (w & 1)) * 72 + 8 * (4 * rank + 2 * wg + (w >> 1)) + r) * 2;
        uint32_t om0, om1;
        UNDEF_R(om0); UNDEF_R(om1);
        __nv_bfloat16* hf = g_Hf + (size_t)(rb * 128 + wg * 64 + w * 16 + r) * kF + q * 8;
#define FFN_SLICE(J, BIAS_ENTRY, F0)                                                                   \
    {                                                                                                  \
        const uint4 bv = lds128(bias_s + ((BIAS_ENTRY) * 4 + q) * 16);                                 \
        const uint32_t bb[4] = {bv.x, bv.y, bv.z, bv.w};                                               \
        uint32_t o0[4], o1[4];                                                                         \
        _Pragma("unroll") for (int jj = 0; jj < 4; ++jj) {                                             \
            const uint32_t r0 = bf2_add_relu(pk[8 * (J) + 2 * jj], bb[jj]), r1 = bf2_add_relu(pk[8 * (J) + 2 * jj + 1], bb[jj]); \
            o0[jj] = bf2_mul(bf2_mul(r0, r0), om0);                                                    \
            o1[jj] = bf2_mul(bf2_mul(r1, r1), om1);                                                    \
        }                                                                                              \
        stg128(hf + (F0) + 32 * (J), o0[0], o0[1], o0[2], o0[3]);                                      \
        stg128(hf + 8 * kF + (F0) + 32 * (J), o1[0], o1[1], o1[2], o1[3]);                             \
    }

        {
            const int f0 = 2048 + 192 * j8;
#pragma unroll 1
            do {
                KBLOCK(2, it - 32, it != 32);
                switch (it - 32) {
                case 0: {
                    const float a = 1.0f - bf_lo(lds16(gate_row)), b = 1.0f - bf_lo(lds16(gate_row + 72 * 2));
                    om0 = pack_bf16(a, a); om1 = pack_bf16(b, b);
                    FFN_SLICE(0, 0, f0);
                } break;
                case 1: FFN_SLICE(1, 1, f0); break;
                case 2: FFN_SLICE(2, 2, f0); break;
                case 3: FFN_SLICE(3, 3, f0); break;
                case 4: FFN_SLICE(4, 4, f0); break;
                case 5: FFN_SLICE(5, 5, f0); bar_arrive(4, 288); break;
                default: break;
                }
                NEXT_IT();
            } while (it < 48);
            TILE_END();
        }
        STAMP(tid == 0, 4);
#pragma unroll
        for (int i = 0; i < 64; ++i) pk[i] = pack_bf16_v(acc[2 * i], acc[2 * i + 1]);
#pragma unroll
        for (int i = 0; i < 128; ++i) UNDEF_F(acc[i]);

        {
            const int f0 = 256 * j8;
            const uint32_t x_s = sbase + kXOff + (wg * 64 + w * 16 + (lane & 15)) * 128 + (((lane >> 4) ^ (lane & 7)) << 4);
#define ETERM(K)                                                                                       \
    {                                                                                                  \
        const int jb = (K) * 4;                                                                        \
        const float g0 = bf_lo(lds16(gate_row)), g1 = bf_lo(lds16(gate_row + 72 * 2));                 \
        const float o0f = bf_lo(om0), o1f = bf_lo(om1);                                                \
        const uint4 dq = lds128(bias_s + ((14 + (K)) * 4 + q) * 16), bq = lds128(bias_s + ((18 + (K)) * 4 + q) * 16); \
        const uint4 xa = ldsm4((x_s ^ ((jb & 7) << 4)) + (jb >> 3) * 16384), xb = ldsm4((x_s ^ (((jb + 2) & 7) << 4)) + (jb >> 3) * 16384); \
        const uint32_t dv[4] = {dq.x, dq.y, dq.z, dq.w}, bv2[4] = {bq.x, bq.y, bq.z, bq.w};            \
        const uint32_t xv[8] = {xa.x, xa.y, xa.z, xa.w, xb.x, xb.y, xb.z, xb.w};                       \
        _Pragma("unroll") for (int jj = 0; jj < 4; ++jj) {                                             \
            const uint32_t x0 = bf2_mul(xv[2 * jj], dv[jj]), x1 = bf2_mul(xv[2 * jj + 1], dv[jj]);     \
            const float bl = bf_lo(bv2[jj]), bh = bf_hi(bv2[jj]);                                      \
            pk[4 * (jb + jj) + 0] = __float_as_uint(fmaf(g0, bf_lo(x0), o0f * bl));                    \
            pk[4 * (jb + jj) + 1] = __float_as_uint(fmaf(g0, bf_hi(x0), o0f * bh));                    \
            pk[4 * (jb + jj) + 2] = __float_as_uint(fmaf(g1, bf_lo(x1), o1f * bl));                    \
            pk[4 * (jb + jj) + 3] = __float_as_uint(fmaf(g1, bf_hi(x1), o1f * bh));                    \
        }                                                                                              \
    }
#pragma unroll 1
            do {
                KBLOCK(3, it - 48, it != 48);
                switch (it - 48) {
                case 0: FFN_SLICE(0, 6, f0); break;
                case 1: FFN_SLICE(1, 7, f0); break;
                case 2: FFN_SLICE(2, 8, f0); break;
                case 3: FFN_SLICE(3, 9, f0); break;
                case 4: FFN_SLICE(4, 10, f0); break;
                case 5: FFN_SLICE(5, 11, f0); break;
                case 6: FFN_SLICE(6, 12, f0); break;
                case 7: FFN_SLICE(7, 13, f0); bar_arrive(5, 288); break;
                case 8: mbar_wait(bar_x, 1); ETERM(0); break;
                case 9: ETERM(1); break;
                case 10: ETERM(2); break;
                case 11: ETERM(3); break;
                default: break;
                }
                NEXT_IT();
            } while (it < 64);
        }
        STAMP(tid == 0, 5);
#pragma unroll 1
        do {
            KBLOCK(2, 1, true);
            NEXT_IT();
        } while (it < 64 + kNF);
        {
            uint8_t* xo = g_X + (size_t)(role * 2 + rank) * kXBytes + tid * 16;
            const uint8_t* xi = xo + (kh ? -8 * kXBytes : 8 * kXBytes);
            const uint32_t par = tag & 1;
            float xsc;
            uint32_t rs;
            UNDEF_F(xsc); UNDEF_R(rs);
#define RX(U, K) acc[64 + 8 * (U) + (K)]
#define RXLOAD(U) { const uint4 t_ = ld_relaxed2x64(xi + (U) * 4096); RX(U, 0) = __uint_as_float(t_.x); RX(U, 1) = __uint_as_float(t_.y); RX(U, 2) = __uint_as_float(t_.z); RX(U, 3) = __uint_as_float(t_.w); }
#define TAILWORK(KB)                                                                                   \
    {                                                                                                  \
        if ((KB) == 0) {    \
            float m[4] = {0.f, 0.f, 0.f, 0.f};                                                         \
            _Pragma("unroll") for (int i = 64; i < 128; ++i) m[i & 3] = fmaxf(m[i & 3], fabsf(acc[i])); \
            const uint32_t eb = max(__float_as_uint(fmaxf(fmaxf(m[0], m[1]), fmaxf(m[2], m[3]))) >> 23, 15u); \
            xsc = __uint_as_float((268u - eb) << 23);                                                  \
            st_relaxed32(xo + 32768 - tid * 12, ((eb - 14u) << 23) | par);                             \
        }                                                                                              \
        _Pragma("unroll") for (int u = 0; u < 8; ++u) {                                                \
            if (nib(XSND, u) == (KB)) {                                                                \
                const int v = 64 + 8 * u;                                                              \
                st_relaxed2x64(xo + u * 4096, (pack_f16(acc[v] * xsc, acc[v + 1] * xsc) & ~1u) | par, pack_f16(acc[v + 2] * xsc, acc[v + 3] * xsc), \
                               (pack_f16(acc[v + 4] * xsc, acc[v + 5] * xsc) & ~1u) | par, pack_f16(acc[v + 6] * xsc, acc[v + 7] * xsc)); \
                if (u == 7) STAMP(tid == 0, 12);                                                       \
            }                                                                                          \
        }                                                                                              \
        _Pragma("unroll") for (int u = 0; u < 8; ++u) {                                                \
            if (nib(XLDK, u) == (KB)) {                                                                \
                if (u == 0) rs = ld_relaxed32((const unsigned*)(xi + 32768 - tid * 12));               \
                RXLOAD(u);                                                                             \
            }                                                                                          \
        }                                                                                              \
        if (any_nib(XUSE, KB)) {                                                                       \
            unsigned n = 0;                                                                            \
            _Pragma("unroll 1") while (true) {                                                         \
                uint32_t bad = (nib(XUSE, 0) == (KB)) ? rs ^ par : 0u;                                 \
                _Pragma("unroll") for (int u = 0; u < 8; ++u)                                          \
                    if (nib(XUSE, u) == (KB)) bad |= (__float_as_uint(RX(u, 0)) ^ par) | (__float_as_uint(RX(u, 2)) ^ par); \
                if (!__any_sync(0xffffffffu, bad & 1) || ++n > kSpinLimit) break;                      \
                if (nib(XUSE, 0) == (KB)) rs = ld_relaxed32((const unsigned*)(xi + 32768 - tid * 12)); \
                _Pragma("unroll") for (int u = 0; u < 8; ++u) if (nib(XUSE, u) == (KB)) RXLOAD(u);     \
                RESPIN();                                                                              \
            }                                                                                          \
            if (nib(XUSE, 0) == (KB)) xsc = __uint_as_float(rs & ~1u);                                 \
            _Pragma("unroll") for (int u = 0; u < 8; ++u) {                                            \
                if (nib(XUSE, u) == (KB)) {                                                            \
                    _Pragma("unroll") for (int k = 0; k < 4; ++k) {                                    \
                        const int v = 8 * u + 2 * k;                                                   \
                        const uint32_t rr = __float_as_uint(RX(u, k));                                 \
                        const float2 f = __half22float2(*reinterpret_cast<const __half2*>(&rr));       \
                        pk[v] = __float_as_uint(fmaf(f.x, xsc, __uint_as_float(pk[v])));               \
                        pk[v + 1] = __float_as_uint(fmaf(f.y, xsc, __uint_as_float(pk[v + 1])));       \
                    }                                                                                  \
                    if (u == 0) STAMP(tid == 0, 13);                                                   \
                    if (u == 7) STAMP(tid == 0, 14);                                                   \
                }                                                                                      \
            }                                                                                          \
        }                                                                                              \
    }
            KBLOCK(4, 1, true);
            STAMP(tid == 0, 15);
            TAILWORK(0);
            NEXT_IT();
#pragma unroll 1
            do {
                KBLOCK(4, 1, it <= kTotal - kStages);
                switch (it - (64 + kNF)) {
                case 1: TAILWORK(1); break;
                case 2: TAILWORK(2); break;
                case 3: TAILWORK(3); break;
                case 4: TAILWORK(4); break;
                case 5: TAILWORK(5); break;
                case 6: TAILWORK(6); break;
                case 7: TAILWORK(7); break;
                default: break;
                }
                NEXT_IT();
            } while (it < kTotal);
        }
        wgmma_wait<0>();
        STAMP(tid == 0, 6);
        {
            const bool odd = q & 1;
            const int tb = c * 256 + 128 * (w & 1) + 8 * (4 * rank + 2 * wg + (w >> 1));
            float* o0 = p.out + (size_t)(tb + r) * kD + colK + (odd ? 2 * q + 6 : 2 * q);
#pragma unroll
            for (int i = 0; i < 16; i += 2) {
#pragma unroll
                for (int h = 0; h < 2; ++h) {
                    const int va = 4 * i + 2 * h, vb = va + 4;
                    PIN_F(acc[va]); PIN_F(acc[va + 1]); PIN_F(acc[vb]); PIN_F(acc[vb + 1]);
                    const float a0 = acc[va] + __uint_as_float(pk[va]), a1 = acc[va + 1] + __uint_as_float(pk[va + 1]);
                    const float b0 = acc[vb] + __uint_as_float(pk[vb]), b1 = acc[vb + 1] + __uint_as_float(pk[vb + 1]);
                    const float t0 = __shfl_xor_sync(0xffffffffu, odd ? a0 : b0, 1), t1 = __shfl_xor_sync(0xffffffffu, odd ? a1 : b1, 1);
                    stg128f(o0 + h * 64 * kD + 8 * i, odd ? t0 : a0, odd ? t1 : a1, odd ? b0 : t0, odd ? b1 : t1);
                }
            }
        }
        STAMP(tid == 0, 7);
    }
}

typedef CUresult (*EncodeFn)(CUtensorMap*, CUtensorMapDataType, cuuint32_t, void*, const cuuint64_t*, const cuuint64_t*,
                             const cuuint32_t*, const cuuint32_t*, CUtensorMapInterleave, CUtensorMapSwizzle,
                             CUtensorMapL2promotion, CUtensorMapFloatOOBfill);

bool encode(EncodeFn fn, CUtensorMap* m, const void* base, int rank, const cuuint64_t* dims, const cuuint64_t* strides,
            const cuuint32_t* box) {
    cuuint32_t es[5] = {1, 1, 1, 1, 1};
    return fn(m, CU_TENSOR_MAP_DATA_TYPE_BFLOAT16, rank, const_cast<void*>(base), dims, strides, box, es,
              CU_TENSOR_MAP_INTERLEAVE_NONE, CU_TENSOR_MAP_SWIZZLE_128B, CU_TENSOR_MAP_L2_PROMOTION_L2_256B,
              CU_TENSOR_MAP_FLOAT_OOB_FILL_NONE) == CUDA_SUCCESS;
}

}

extern "C" void kernel_launch(void* const* d_in, const int* in_sizes, int n_in, void* d_out, int out_size) {
    (void)in_sizes; (void)n_in; (void)out_size;
    typedef const __nv_bfloat16* bp;
    bp x = (bp)d_in[0], lam_re = (bp)d_in[1], lam_im = (bp)d_in[2], B_re = (bp)d_in[3], B_im = (bp)d_in[4];
    bp C_re = (bp)d_in[5], C_im = (bp)d_in[6], log_dt = (bp)d_in[7], dskip = (bp)d_in[8];
    bp w1 = (bp)d_in[10], b1 = (bp)d_in[11], w2 = (bp)d_in[12], b2 = (bp)d_in[13], gate_w = (bp)d_in[14];

    static EncodeFn fn = nullptr;
    static void *pHs = nullptr, *pHf = nullptr, *pBc = nullptr;
    if (!fn) {
        void* f = nullptr;
        cudaDriverEntryPointQueryResult qr;
        cudaGetDriverEntryPoint("cuTensorMapEncodeTiled", &f, cudaEnableDefault, &qr);
        fn = (EncodeFn)f;
        cudaGetSymbolAddress(&pHs, g_Hs);
        cudaGetSymbolAddress(&pHf, g_Hf);
        cudaGetSymbolAddress(&pBc, g_Bcopy);
        cudaFuncSetAttribute(fused_kernel, cudaFuncAttributeMaxDynamicSharedMemorySize, kSmemBytes);
    }
    cudaStream_t stream = cudaStreamPerThread;

    Params p;
    p.x = x; p.lam_re = lam_re; p.lam_im = lam_im; p.log_dt = log_dt; p.dskip = dskip; p.b1 = b1; p.b2 = b2;
    p.gate_w = gate_w; p.w1 = w1; p.w2 = w2; p.c_re = C_re; p.c_im = C_im; p.b_re = B_re; p.b_im = B_im; p.out = (float*)d_out;

    const char* lo = (const char*)B_re; const char* hi = (const char*)B_im;
    p.swap = 0;
    if (hi < lo) { const char* t = lo; lo = hi; hi = t; p.swap = 1; }
    unsigned long long diff = (unsigned long long)(hi - lo);
    if (diff >= (1ull << 40) || (diff & 15) || diff == 0) {
        cudaMemcpyAsync(pBc, B_re, 2u << 20, cudaMemcpyDeviceToDevice, stream);
        cudaMemcpyAsync((char*)pBc + (2u << 20), B_im, 2u << 20, cudaMemcpyDeviceToDevice, stream);
        lo = (const char*)pBc; diff = 2u << 20; p.swap = 0;
    }

    CUtensorMap mB, mXs, mXf, mW1a, mW1b, mHs, mHf, mCre, mCim, mW2;
    bool ok = true;
    { cuuint64_t d[4] = {1024, 8, 2, 128}, s[3] = {2048, diff, 16384}; cuuint32_t b[4] = {64, 8, 2, 8};
      ok &= encode(fn, &mB, lo, 4, d, s, b); }
    { cuuint64_t d[5] = {1024, 2, 4, 32, 8}, s[4] = {2048, 64 * 2048, 2 * 2048, 256 * 2048}; cuuint32_t b[5] = {64, 2, 4, 16, 1};
      ok &= encode(fn, &mXs, x, 5, d, s, b); }
    { cuuint64_t d[5] = {1024, 8, 4, 8, 8}, s[4] = {2048, 64 * 2048, 8 * 2048, 256 * 2048}; cuuint32_t b[5] = {64, 8, 4, 4, 1};
      ok &= encode(fn, &mXf, x, 5, d, s, b); }
    { cuuint64_t d[3] = {64, 1024, 56}, s[2] = {7168, 128}; cuuint32_t ba[3] = {64, 32, 4}, bb[3] = {64, 32, 3};
      ok &= encode(fn, &mW1a, w1, 3, d, s, ba); ok &= encode(fn, &mW1b, w1, 3, d, s, bb); }
    { cuuint64_t d[3] = {64, 2048, 32}, s[2] = {4096, 128}; cuuint32_t b[3] = {64, 64, 2};
      ok &= encode(fn, &mHs, pHs, 3, d, s, b); }
    { cuuint64_t d[2] = {3584, 2048}, s[1] = {7168}; cuuint32_t b[2] = {64, 128};
      ok &= encode(fn, &mHf, pHf, 2, d, s, b); }
    { cuuint64_t d[2] = {1024, 1024}, s[1] = {2048}; cuuint32_t b[2] = {64, 128};
      ok &= encode(fn, &mCre, C_re, 2, d, s, b); ok &= encode(fn, &mCim, C_im, 2, d, s, b); }
    { cuuint64_t d[5] = {64, 2, 448, 4, 16}, s[4] = {2048, 8 * 2048, 2 * 2048, 128}; cuuint32_t b[5] = {64, 2, 4, 4, 2};
      ok &= encode(fn, &mW2, w2, 5, d, s, b); }
    if (!ok) return;

    fused_kernel<<<128, 384, kSmemBytes, stream>>>(mB, mXs, mXf, mW1a, mW1b, mHs, mHf, mCre, mCim, mW2, p);
}
```

```cpp
#include <cuda_runtime.h>
#include <cuda_bf16.h>
#include <cuda_fp16.h>
#include <cuda.h>
#include <stdint.h>
#include <stddef.h>

#define XLDKB 40
#define PF0LINES 2
#define ORDER 0

namespace {

constexpr int kD = 1024, kF = 3584;
constexpr int kStages = 4;
constexpr int kStageBytes = 49152;
constexpr int kABytes = 16384;
constexpr int kXOff = kStages * kStageBytes;
constexpr int kTabOff = kXOff + 2048;
constexpr int kGateOff = kXOff + 32768;
constexpr int kBiasOff = kGateOff + 4 * 72 * 2;
constexpr int kBarOff = kBiasOff + 88 * 16;
constexpr int kSmemBytes = 232448;
static_assert(kBarOff + 128 <= kSmemBytes, "smem");
constexpr int kXBytes = 33792;
constexpr uint32_t kSmemOrg = 1024;
constexpr unsigned kSpinLimit = 1u << 22;
constexpr int kTotal = 92;

__host__ __device__ constexpr int pass2_kb(int s) {
    return s < 2 ? 6 : s < 8 ? 7 : s < 12 ? 8 : s < 18 ? 9 : s < 22 ? 10 : s < 28 ? 11 : s < 32 ? 12 : s < 38 ? 13 : s < 42 ? 14 : s < 48 ? 15 : s < 56 ? 16 : 17;
}

struct Scratch {
    unsigned claim[64];
    unsigned epoch, pad0[31];
    unsigned done, pad1[31];
    unsigned cnt[40 * 32];
    uint2 gate[2048];
    uint4 agg[8 * 1024];
    __align__(1024) uint8_t X[128 * kXBytes];
    __align__(1024) __nv_bfloat16 Hs[2048 * 2048];
    __align__(1024) __nv_bfloat16 Hf[2048 * 3584];
    __align__(1024) __nv_bfloat16 Bcopy[2 * 1024 * 1024];
};
__device__ Scratch g_s;

#define TRAP() break
#define PIN_F(x) asm volatile("" : "+f"(x))
#define PIN_R(x) asm volatile("" : "+r"(x))
#define UNDEF_F(x) asm volatile("" : "=f"(x))
#define UNDEF_R(x) asm volatile("" : "=r"(x))
#define RESPIN()
__device__ __forceinline__ uint32_t smem_u32(const void* p) { return (uint32_t)__cvta_generic_to_shared(p); }
__device__ __forceinline__ void mbar_init(uint32_t bar, uint32_t count) {
    asm volatile("mbarrier.init.shared::cta.b64 [%0], %1;" ::"r"(bar), "r"(count) : "memory");
}
__device__ __forceinline__ void mbar_expect_tx(uint32_t bar, uint32_t bytes) {
    asm volatile("mbarrier.arrive.expect_tx.shared::cta.b64 _, [%0], %1;" ::"r"(bar), "r"(bytes) : "memory");
}
__device__ __forceinline__ void mbar_wait(uint32_t bar, uint32_t parity) {
    asm volatile(
        "{\n.reg .pred p;\n.reg .u32 n;\n"
        "mbarrier.try_wait.parity.shared::cta.b64 p, [%0], %1;\n"
        "@p bra DONE;\n"
        "mov.u32 n, 0;\n"
        "LOOP:\n"
        "mbarrier.try_wait.parity.shared::cta.b64 p, [%0], %1;\n"
        "@p bra DONE;\n"
        "add.u32 n, n, 1;\n"
        "setp.lt.u32 p, n, %2;\n"
        "@p bra LOOP;\n"
        "DONE:\n}\n"
        ::"r"(bar), "r"(parity), "n"(kSpinLimit) : "memory");
}
__device__ __forceinline__ void mbar_arrive_local(uint32_t bar) {
    asm volatile("mbarrier.arrive.shared::cta.b64 _, [%0];" ::"r"(bar) : "memory");
}
__device__ __forceinline__ void mbar_arrive_cluster(uint32_t cluster_addr) {
    asm volatile("mbarrier.arrive.shared::cluster.b64 _, [%0];" ::"r"(cluster_addr) : "memory");
}
__device__ __forceinline__ uint32_t mapa(uint32_t addr, uint32_t rank) {
    uint32_t r;
    asm("mapa.shared::cluster.u32 %0, %1, %2;" : "=r"(r) : "r"(addr), "r"(rank));
    return r;
}
__device__ __forceinline__ void cluster_arrive() { asm volatile("barrier.cluster.arrive.relaxed.aligned;" ::: "memory"); }
__device__ __forceinline__ void cluster_wait() { asm volatile("barrier.cluster.wait.acquire.aligned;" ::: "memory"); }
__device__ __forceinline__ void bar_sync(int id, int n) { asm volatile("bar.sync %0, %1;" ::"r"(id), "r"(n) : "memory"); }
__device__ __forceinline__ void bar_arrive(int id, int n) { asm volatile("bar.arrive %0, %1;" ::"r"(id), "r"(n) : "memory"); }
__device__ __forceinline__ bool elect_one() {
    uint32_t p;
    asm volatile("{\n.reg .pred P;\nelect.sync _|P, 0xffffffff;\nselp.u32 %0, 1, 0, P;\n}\n" : "=r"(p));
    return p != 0;
}

__device__ __forceinline__ void tma2(uint32_t dst, const CUtensorMap* m, uint32_t bar, int c0, int c1) {
    asm volatile("cp.async.bulk.tensor.2d.shared::cluster.global.mbarrier::complete_tx::bytes [%0], [%1, {%3, %4}], [%2];"
                 ::"r"(dst), "l"(m), "r"(bar), "r"(c0), "r"(c1) : "memory");
}
__device__ __forceinline__ void tma3(uint32_t dst, const CUtensorMap* m, uint32_t bar, int c0, int c1, int c2) {
    asm volatile("cp.async.bulk.tensor.3d.shared::cluster.global.mbarrier::complete_tx::bytes [%0], [%1, {%3, %4, %5}], [%2];"
                 ::"r"(dst), "l"(m), "r"(bar), "r"(c0), "r"(c1), "r"(c2) : "memory");
}
__device__ __forceinline__ void tma4(uint32_t dst, const CUtensorMap* m, uint32_t bar, int c0, int c1, int c2, int c3) {
    asm volatile("cp.async.bulk.tensor.4d.shared::cluster.global.mbarrier::complete_tx::bytes [%0], [%1, {%3, %4, %5, %6}], [%2];"
                 ::"r"(dst), "l"(m), "r"(bar), "r"(c0), "r"(c1), "r"(c2), "r"(c3) : "memory");
}
__device__ __forceinline__ void tma5(uint32_t dst, const CUtensorMap* m, uint32_t bar, int c0, int c1, int c2, int c3, int c4) {
    asm volatile("cp.async.bulk.tensor.5d.shared::cluster.global.mbarrier::complete_tx::bytes [%0], [%1, {%3, %4, %5, %6, %7}], [%2];"
                 ::"r"(dst), "l"(m), "r"(bar), "r"(c0), "r"(c1), "r"(c2), "r"(c3), "r"(c4) : "memory");
}
__device__ __forceinline__ void tma2_mc(uint32_t dst, const CUtensorMap* m, uint32_t bar, int c0, int c1) {
    asm volatile("cp.async.bulk.tensor.2d.shared::cluster.global.mbarrier::complete_tx::bytes.multicast::cluster [%0], [%1, {%3, %4}], [%2], %5;"
                 ::"r"(dst), "l"(m), "r"(bar), "r"(c0), "r"(c1), "h"((uint16_t)3) : "memory");
}
__device__ __forceinline__ void tma3_mc(uint32_t dst, const CUtensorMap* m, uint32_t bar, int c0, int c1, int c2) {
    asm volatile("cp.async.bulk.tensor.3d.shared::cluster.global.mbarrier::complete_tx::bytes.multicast::cluster [%0], [%1, {%3, %4, %5}], [%2], %6;"
                 ::"r"(dst), "l"(m), "r"(bar), "r"(c0), "r"(c1), "r"(c2), "h"((uint16_t)3) : "memory");
}
__device__ __forceinline__ void tma5_mc(uint32_t dst, const CUtensorMap* m, uint32_t bar, int c0, int c1, int c2, int c3, int c4) {
    asm volatile("cp.async.bulk.tensor.5d.shared::cluster.global.mbarrier::complete_tx::bytes.multicast::cluster [%0], [%1, {%3, %4, %5, %6, %7}], [%2], %8;"
                 ::"r"(dst), "l"(m), "r"(bar), "r"(c0), "r"(c1), "r"(c2), "r"(c3), "r"(c4), "h"((uint16_t)3) : "memory");
}
__device__ __forceinline__ void bulk_store(void* dst, uint32_t src, uint32_t bytes) {
    asm volatile("cp.async.bulk.global.shared::cta.bulk_group [%0], [%1], %2;" ::"l"(dst), "r"(src), "r"(bytes) : "memory");
}
__device__ __forceinline__ void bulk_load(uint32_t dst, const void* src, uint32_t bytes, uint32_t bar) {
    asm volatile("cp.async.bulk.shared::cluster.global.mbarrier::complete_tx::bytes [%0], [%1], %2, [%3];"
                 ::"r"(dst), "l"(src), "r"(bytes), "r"(bar) : "memory");
}
__device__ __forceinline__ unsigned atom_exch(unsigned* p, unsigned v) {
    unsigned r;
    asm volatile("atom.relaxed.gpu.global.exch.b32 %0, [%1], %2;" : "=r"(r) : "l"(p), "r"(v) : "memory");
    return r;
}
__device__ __forceinline__ uint32_t lds32_cluster(uint32_t a) {
    uint32_t v;
    asm volatile("ld.shared::cluster.u32 %0, [%1];" : "=r"(v) : "r"(a) : "memory");
    return v;
}
__device__ __forceinline__ void sts128f(uint32_t a, float x, float y, float z, float w) {
    asm volatile("st.shared.v4.f32 [%0], {%1, %2, %3, %4};" ::"r"(a), "f"(x), "f"(y), "f"(z), "f"(w) : "memory");
}
__device__ __forceinline__ void prefetch_map(const CUtensorMap* m) {
    asm volatile("prefetch.tensormap [%0];" ::"l"(m) : "memory");
}

__device__ __forceinline__ void prefetch_l2(const void* p, uint32_t bytes) {
    asm volatile("cp.async.bulk.prefetch.L2.global [%0], %1;" ::"l"(p), "r"(bytes) : "memory");
}

__device__ __forceinline__ void wgmma_fence() { asm volatile("wgmma.fence.sync.aligned;" ::: "memory"); }
__device__ __forceinline__ void wgmma_commit() { asm volatile("wgmma.commit_group.sync.aligned;" ::: "memory"); }
template <int N>
__device__ __forceinline__ void wgmma_wait() { asm volatile("wgmma.wait_group.sync.aligned %0;" ::"n"(N) : "memory"); }

__device__ __forceinline__ uint32_t pack_bf16(float lo, float hi) {
    uint32_t r;
    asm("cvt.rn.bf16x2.f32 %0, %1, %2;" : "=r"(r) : "f"(hi), "f"(lo));
    return r;
}
__device__ __forceinline__ uint32_t pack_f16(float lo, float hi) {
    uint32_t r;
    asm("cvt.rn.f16x2.f32 %0, %1, %2;" : "=r"(r) : "f"(hi), "f"(lo));
    return r;
}
__device__ __forceinline__ uint32_t pack_bf16_v(float lo, float hi) {
    uint32_t r;
    asm volatile("cvt.rn.bf16x2.f32 %0, %1, %2;" : "=r"(r) : "f"(hi), "f"(lo));
    return r;
}
template <int LUT>
__device__ __forceinline__ uint32_t lop3(uint32_t a, uint32_t b, uint32_t c) {
    uint32_t r;
    asm("lop3.b32 %0, %1, %2, %3, %4;" : "=r"(r) : "r"(a), "r"(b), "r"(c), "n"(LUT));
    return r;
}
__device__ __forceinline__ float bf_lo(uint32_t v) { return __uint_as_float(v << 16); }
__device__ __forceinline__ float bf_hi(uint32_t v) { return __uint_as_float(v & 0xffff0000u); }
__device__ __forceinline__ float bf16_round(float v) { return __bfloat162float(__float2bfloat16_rn(v)); }
__device__ __forceinline__ uint32_t bf2_mul(uint32_t a, uint32_t b) {
    uint32_t r;
    asm("mul.rn.bf16x2 %0, %1, %2;" : "=r"(r) : "r"(a), "r"(b));
    return r;
}
__device__ __forceinline__ uint32_t bf2_add_relu(uint32_t a, uint32_t b) {
    uint32_t r;
    asm("fma.rn.relu.bf16x2 %0, %1, %2, %3;" : "=r"(r) : "r"(a), "r"(0x3f803f80u), "r"(b));
    return r;
}
__device__ __forceinline__ uint4 ldg128(const void* p) {
    uint4 v;
    asm volatile("ld.global.nc.v4.u32 {%0, %1, %2, %3}, [%4];" : "=r"(v.x), "=r"(v.y), "=r"(v.z), "=r"(v.w) : "l"(p));
    return v;
}
__device__ __forceinline__ uint32_t ldg32(const void* p) {
    uint32_t v;
    asm volatile("ld.global.nc.u32 %0, [%1];" : "=r"(v) : "l"(p));
    return v;
}
__device__ __forceinline__ uint32_t ldg32na(const void* p) {
    uint32_t v;
    asm volatile("ld.global.nc.L1::no_allocate.u32 %0, [%1];" : "=r"(v) : "l"(p));
    return v;
}
__device__ __forceinline__ uint32_t ldg16(const __nv_bfloat16* p) {
    uint32_t v;
    asm volatile("ld.global.nc.u16 %0, [%1];" : "=r"(v) : "l"(p));
    return v;
}
__device__ __forceinline__ uint4 ld_relaxed128(const void* p) {
    uint4 v;
    asm volatile("ld.relaxed.gpu.global.v4.u32 {%0, %1, %2, %3}, [%4];" : "=r"(v.x), "=r"(v.y), "=r"(v.z), "=r"(v.w) : "l"(p) : "memory");
    return v;
}
__device__ __forceinline__ uint2 ld_relaxed64(const void* p) {
    unsigned long long v;
    asm volatile("ld.relaxed.gpu.global.u64 %0, [%1];" : "=l"(v) : "l"(p) : "memory");
    return make_uint2((uint32_t)v, (uint32_t)(v >> 32));
}
__device__ __forceinline__ void st_relaxed64(void* p, uint32_t lo, uint32_t hi) {
    unsigned long long v = ((unsigned long long)hi << 32) | lo;
    asm volatile("st.relaxed.gpu.global.u64 [%0], %1;" ::"l"(p), "l"(v) : "memory");
}
__device__ __forceinline__ void st_relaxed2x64(void* p, uint32_t a, uint32_t b, uint32_t c, uint32_t d) {
    unsigned long long v0 = ((unsigned long long)b << 32) | a, v1 = ((unsigned long long)d << 32) | c;
    asm volatile("st.relaxed.gpu.global.v2.u64 [%0], {%1, %2};" ::"l"(p), "l"(v0), "l"(v1) : "memory");
}
__device__ __forceinline__ uint4 ld_relaxed2x64(const void* p) {
    unsigned long long v0, v1;
    asm volatile("ld.relaxed.gpu.global.v2.u64 {%0, %1}, [%2];" : "=l"(v0), "=l"(v1) : "l"(p) : "memory");
    return make_uint4((uint32_t)v0, (uint32_t)(v0 >> 32), (uint32_t)v1, (uint32_t)(v1 >> 32));
}
__device__ __forceinline__ void stg128(void* p, uint32_t a, uint32_t b, uint32_t c, uint32_t d) {
    asm volatile("st.global.v4.u32 [%0], {%1, %2, %3, %4};" ::"l"(p), "r"(a), "r"(b), "r"(c), "r"(d) : "memory");
}
__device__ __forceinline__ void stg64f(void* p, float a, float b) {
    asm volatile("st.global.v2.f32 [%0], {%1, %2};" ::"l"(p), "f"(a), "f"(b) : "memory");
}
__device__ __forceinline__ uint4 lds128(uint32_t a) {
    uint4 v;
    asm volatile("ld.shared.v4.u32 {%0, %1, %2, %3}, [%4];" : "=r"(v.x), "=r"(v.y), "=r"(v.z), "=r"(v.w) : "r"(a) : "memory");
    return v;
}
__device__ __forceinline__ uint2 lds64(uint32_t a) {
    uint2 v;
    asm volatile("ld.shared.v2.u32 {%0, %1}, [%2];" : "=r"(v.x), "=r"(v.y) : "r"(a) : "memory");
    return v;
}
__device__ __forceinline__ uint4 ldsm4(uint32_t a) {
    uint4 v;
    asm volatile("ldmatrix.sync.aligned.m8n8.x4.shared.b16 {%0, %1, %2, %3}, [%4];" : "=r"(v.x), "=r"(v.y), "=r"(v.z), "=r"(v.w) : "r"(a) : "memory");
    return v;
}
__device__ __forceinline__ uint32_t lds16(uint32_t a) {
    uint32_t v;
    asm volatile("ld.shared.u16 %0, [%1];" : "=r"(v) : "r"(a) : "memory");
    return v;
}
__device__ __forceinline__ void sts16(uint32_t a, uint32_t x) {
    asm volatile("st.shared.u16 [%0], %1;" ::"r"(a), "h"((uint16_t)x) : "memory");
}
__device__ __forceinline__ void st_relaxed32(void* p, uint32_t v) {
    asm volatile("st.relaxed.gpu.global.u32 [%0], %1;" ::"l"(p), "r"(v) : "memory");
}
__device__ __forceinline__ float lds32f(uint32_t a) {
    float v;
    asm volatile("ld.shared.f32 %0, [%1];" : "=f"(v) : "r"(a) : "memory");
    return v;
}
__device__ __forceinline__ void sts128(uint32_t a, uint32_t x, uint32_t y, uint32_t z, uint32_t w) {
    asm volatile("st.shared.v4.u32 [%0], {%1, %2, %3, %4};" ::"r"(a), "r"(x), "r"(y), "r"(z), "r"(w) : "memory");
}
__device__ __forceinline__ void sts64f(uint32_t a, float x, float y) {
    asm volatile("st.shared.v2.f32 [%0], {%1, %2};" ::"r"(a), "f"(x), "f"(y) : "memory");
}
__device__ __forceinline__ float4 lds128f(uint32_t a) {
    float4 v;
    asm volatile("ld.shared.v4.f32 {%0, %1, %2, %3}, [%4];" : "=f"(v.x), "=f"(v.y), "=f"(v.z), "=f"(v.w) : "r"(a) : "memory");
    return v;
}
__device__ __forceinline__ uint32_t lds32(uint32_t a) {
    uint32_t v;
    asm volatile("ld.shared.u32 %0, [%1];" : "=r"(v) : "r"(a) : "memory");
    return v;
}
__device__ __forceinline__ void sts32(uint32_t a, uint32_t x) {
    asm volatile("st.shared.u32 [%0], %1;" ::"r"(a), "r"(x) : "memory");
}
__device__ __forceinline__ void stg128f(void* p, float a, float b, float c, float d) {
    asm volatile("st.global.v4.f32 [%0], {%1, %2, %3, %4};" ::"l"(p), "f"(a), "f"(b), "f"(c), "f"(d) : "memory");
}
__device__ __forceinline__ unsigned ld_relaxed32(const unsigned* p) {
    unsigned v;
    asm volatile("ld.relaxed.gpu.global.u32 %0, [%1];" : "=r"(v) : "l"(p) : "memory");
    return v;
}
__device__ __forceinline__ void wait_counter(const unsigned* p, unsigned target) {
    unsigned n = 0, v;
    while (true) {
        asm volatile("ld.acquire.gpu.global.u32 %0, [%1];" : "=r"(v) : "l"(p) : "memory");
        if ((int)(v - target) >= 0) break;
        if (++n > kSpinLimit) TRAP();
        __nanosleep(32);
    }
}
#define KT(IT, W) do { } while (0)
#define STAMP(cond, slot) do { } while (0)

template <int TA, int TB>
__device__ __forceinline__ void wgmma_n256(float (&d)[128], uint64_t da, uint64_t db, int keep) {
    asm volatile(
        "{\n.reg .pred p;\nsetp.ne.b32 p, %132, 0;\n"
        "wgmma.mma_async.sync.aligned.m64n256k16.f32.bf16.bf16 "
        "{%0, %1, %2, %3, %4, %5, %6, %7, %8, %9, %10, %11, %12, %13, %14, %15, "
        "%16, %17, %18, %19, %20, %21, %22, %23, %24, %25, %26, %27, %28, %29, %30, %31, "
        "%32, %33, %34, %35, %36, %37, %38, %39, %40, %41, %42, %43, %44, %45, %46, %47, "
        "%48, %49, %50, %51, %52, %53, %54, %55, %56, %57, %58, %59, %60, %61, %62, %63, "
        "%64, %65, %66, %67, %68, %69, %70, %71, %72, %73, %74, %75, %76, %77, %78, %79, "
        "%80, %81, %82, %83, %84, %85, %86, %87, %88, %89, %90, %91, %92, %93, %94, %95, "
        "%96, %97, %98, %99, %100, %101, %102, %103, %104, %105, %106, %107, %108, %109, %110, %111, "
        "%112, %113, %114, %115, %116, %117, %118, %119, %120, %121, %122, %123, %124, %125, %126, %127}, "
        "%128, %129, p, 1, 1, %130, %131;\n}\n"
        : "+f"(d[0]), "+f"(d[1]), "+f"(d[2]), "+f"(d[3]), "+f"(d[4]), "+f"(d[5]), "+f"(d[6]), "+f"(d[7]),
          "+f"(d[8]), "+f"(d[9]), "+f"(d[10]), "+f"(d[11]), "+f"(d[12]), "+f"(d[13]), "+f"(d[14]), "+f"(d[15]),
          "+f"(d[16]), "+f"(d[17]), "+f"(d[18]), "+f"(d[19]), "+f"(d[20]), "+f"(d[21]), "+f"(d[22]), "+f"(d[23]),
          "+f"(d[24]), "+f"(d[25]), "+f"(d[26]), "+f"(d[27]), "+f"(d[28]), "+f"(d[29]), "+f"(d[30]), "+f"(d[31]),
          "+f"(d[32]), "+f"(d[33]), "+f"(d[34]), "+f"(d[35]), "+f"(d[36]), "+f"(d[37]), "+f"(d[38]), "+f"(d[39]),
          "+f"(d[40]), "+f"(d[41]), "+f"(d[42]), "+f"(d[43]), "+f"(d[44]), "+f"(d[45]), "+f"(d[46]), "+f"(d[47]),
          "+f"(d[48]), "+f"(d[49]), "+f"(d[50]), "+f"(d[51]), "+f"(d[52]), "+f"(d[53]), "+f"(d[54]), "+f"(d[55]),
          "+f"(d[56]), "+f"(d[57]), "+f"(d[58]), "+f"(d[59]), "+f"(d[60]), "+f"(d[61]), "+f"(d[62]), "+f"(d[63]),
          "+f"(d[64]), "+f"(d[65]), "+f"(d[66]), "+f"(d[67]), "+f"(d[68]), "+f"(d[69]), "+f"(d[70]), "+f"(d[71]),
          "+f"(d[72]), "+f"(d[73]), "+f"(d[74]), "+f"(d[75]), "+f"(d[76]), "+f"(d[77]), "+f"(d[78]), "+f"(d[79]),
          "+f"(d[80]), "+f"(d[81]), "+f"(d[82]), "+f"(d[83]), "+f"(d[84]), "+f"(d[85]), "+f"(d[86]), "+f"(d[87]),
          "+f"(d[88]), "+f"(d[89]), "+f"(d[90]), "+f"(d[91]), "+f"(d[92]), "+f"(d[93]), "+f"(d[94]), "+f"(d[95]),
          "+f"(d[96]), "+f"(d[97]), "+f"(d[98]), "+f"(d[99]), "+f"(d[100]), "+f"(d[101]), "+f"(d[102]), "+f"(d[103]),
          "+f"(d[104]), "+f"(d[105]), "+f"(d[106]), "+f"(d[107]), "+f"(d[108]), "+f"(d[109]), "+f"(d[110]), "+f"(d[111]),
          "+f"(d[112]), "+f"(d[113]), "+f"(d[114]), "+f"(d[115]), "+f"(d[116]), "+f"(d[117]), "+f"(d[118]), "+f"(d[119]),
          "+f"(d[120]), "+f"(d[121]), "+f"(d[122]), "+f"(d[123]), "+f"(d[124]), "+f"(d[125]), "+f"(d[126]), "+f"(d[127])
        : "l"(da), "l"(db), "n"(TA), "n"(TB), "r"(keep));
}
template <int TA, int TB>
__device__ __forceinline__ void wgmma_n192(float (&d)[128], uint64_t da, uint64_t db, int keep) {
    asm volatile(
        "{\n.reg .pred p;\nsetp.ne.b32 p, %100, 0;\n"
        "wgmma.mma_async.sync.aligned.m64n192k16.f32.bf16.bf16 "
        "{%0, %1, %2, %3, %4, %5, %6, %7, %8, %9, %10, %11, %12, %13, %14, %15, "
        "%16, %17, %18, %19, %20, %21, %22, %23, %24, %25, %26, %27, %28, %29, %30, %31, "
        "%32, %33, %34, %35, %36, %37, %38, %39, %40, %41, %42, %43, %44, %45, %46, %47, "
        "%48, %49, %50, %51, %52, %53, %54, %55, %56, %57, %58, %59, %60, %61, %62, %63, "
        "%64, %65, %66, %67, %68, %69, %70, %71, %72, %73, %74, %75, %76, %77, %78, %79, "
        "%80, %81, %82, %83, %84, %85, %86, %87, %88, %89, %90, %91, %92, %93, %94, %95}, "
        "%96, %97, p, 1, 1, %98, %99;\n}\n"
        : "+f"(d[0]), "+f"(d[1]), "+f"(d[2]), "+f"(d[3]), "+f"(d[4]), "+f"(d[5]), "+f"(d[6]), "+f"(d[7]),
          "+f"(d[8]), "+f"(d[9]), "+f"(d[10]), "+f"(d[11]), "+f"(d[12]), "+f"(d[13]), "+f"(d[14]), "+f"(d[15]),
          "+f"(d[16]), "+f"(d[17]), "+f"(d[18]), "+f"(d[19]), "+f"(d[20]), "+f"(d[21]), "+f"(d[22]), "+f"(d[23]),
          "+f"(d[24]), "+f"(d[25]), "+f"(d[26]), "+f"(d[27]), "+f"(d[28]), "+f"(d[29]), "+f"(d[30]), "+f"(d[31]),
          "+f"(d[32]), "+f"(d[33]), "+f"(d[34]), "+f"(d[35]), "+f"(d[36]), "+f"(d[37]), "+f"(d[38]), "+f"(d[39]),
          "+f"(d[40]), "+f"(d[41]), "+f"(d[42]), "+f"(d[43]), "+f"(d[44]), "+f"(d[45]), "+f"(d[46]), "+f"(d[47]),
          "+f"(d[48]), "+f"(d[49]), "+f"(d[50]), "+f"(d[51]), "+f"(d[52]), "+f"(d[53]), "+f"(d[54]), "+f"(d[55]),
          "+f"(d[56]), "+f"(d[57]), "+f"(d[58]), "+f"(d[59]), "+f"(d[60]), "+f"(d[61]), "+f"(d[62]), "+f"(d[63]),
          "+f"(d[64]), "+f"(d[65]), "+f"(d[66]), "+f"(d[67]), "+f"(d[68]), "+f"(d[69]), "+f"(d[70]), "+f"(d[71]),
          "+f"(d[72]), "+f"(d[73]), "+f"(d[74]), "+f"(d[75]), "+f"(d[76]), "+f"(d[77]), "+f"(d[78]), "+f"(d[79]),
          "+f"(d[80]), "+f"(d[81]), "+f"(d[82]), "+f"(d[83]), "+f"(d[84]), "+f"(d[85]), "+f"(d[86]), "+f"(d[87]),
          "+f"(d[88]), "+f"(d[89]), "+f"(d[90]), "+f"(d[91]), "+f"(d[92]), "+f"(d[93]), "+f"(d[94]), "+f"(d[95])
        : "l"(da), "l"(db), "n"(TA), "n"(TB), "r"(keep));
}
template <int TA, int TB>
__device__ __forceinline__ void wgmma_n128(float (&d)[128], uint64_t da, uint64_t db, int keep) {
    asm volatile(
        "{\n.reg .pred p;\nsetp.ne.b32 p, %68, 0;\n"
        "wgmma.mma_async.sync.aligned.m64n128k16.f32.bf16.bf16 "
        "{%0, %1, %2, %3, %4, %5, %6, %7, %8, %9, %10, %11, %12, %13, %14, %15, "
        "%16, %17, %18, %19, %20, %21, %22, %23, %24, %25, %26, %27, %28, %29, %30, %31, "
        "%32, %33, %34, %35, %36, %37, %38, %39, %40, %41, %42, %43, %44, %45, %46, %47, "
        "%48, %49, %50, %51, %52, %53, %54, %55, %56, %57, %58, %59, %60, %61, %62, %63}, "
        "%64, %65, p, 1, 1, %66, %67;\n}\n"
        : "+f"(d[0]), "+f"(d[1]), "+f"(d[2]), "+f"(d[3]), "+f"(d[4]), "+f"(d[5]), "+f"(d[6]), "+f"(d[7]),
          "+f"(d[8]), "+f"(d[9]), "+f"(d[10]), "+f"(d[11]), "+f"(d[12]), "+f"(d[13]), "+f"(d[14]), "+f"(d[15]),
          "+f"(d[16]), "+f"(d[17]), "+f"(d[18]), "+f"(d[19]), "+f"(d[20]), "+f"(d[21]), "+f"(d[22]), "+f"(d[23]),
          "+f"(d[24]), "+f"(d[25]), "+f"(d[26]), "+f"(d[27]), "+f"(d[28]), "+f"(d[29]), "+f"(d[30]), "+f"(d[31]),
          "+f"(d[32]), "+f"(d[33]), "+f"(d[34]), "+f"(d[35]), "+f"(d[36]), "+f"(d[37]), "+f"(d[38]), "+f"(d[39]),
          "+f"(d[40]), "+f"(d[41]), "+f"(d[42]), "+f"(d[43]), "+f"(d[44]), "+f"(d[45]), "+f"(d[46]), "+f"(d[47]),
          "+f"(d[48]), "+f"(d[49]), "+f"(d[50]), "+f"(d[51]), "+f"(d[52]), "+f"(d[53]), "+f"(d[54]), "+f"(d[55]),
          "+f"(d[56]), "+f"(d[57]), "+f"(d[58]), "+f"(d[59]), "+f"(d[60]), "+f"(d[61]), "+f"(d[62]), "+f"(d[63])
        : "l"(da), "l"(db), "n"(TA), "n"(TB), "r"(keep));
}
__device__ __forceinline__ void wgmma_n128_rs(float (&d)[128], uint32_t a0, uint32_t a1, uint32_t a2, uint32_t a3, uint64_t db) {
    asm volatile(
        "{\n.reg .pred p;\nsetp.ne.b32 p, 1, 0;\n"
        "wgmma.mma_async.sync.aligned.m64n128k16.f32.bf16.bf16 "
        "{%0, %1, %2, %3, %4, %5, %6, %7, %8, %9, %10, %11, %12, %13, %14, %15, "
        "%16, %17, %18, %19, %20, %21, %22, %23, %24, %25, %26, %27, %28, %29, %30, %31, "
        "%32, %33, %34, %35, %36, %37, %38, %39, %40, %41, %42, %43, %44, %45, %46, %47, "
        "%48, %49, %50, %51, %52, %53, %54, %55, %56, %57, %58, %59, %60, %61, %62, %63}, "
        "{%64, %65, %66, %67}, %68, p, 1, 1, 1;\n}\n"
        : "+f"(d[0]), "+f"(d[1]), "+f"(d[2]), "+f"(d[3]), "+f"(d[4]), "+f"(d[5]), "+f"(d[6]), "+f"(d[7]),
          "+f"(d[8]), "+f"(d[9]), "+f"(d[10]), "+f"(d[11]), "+f"(d[12]), "+f"(d[13]), "+f"(d[14]), "+f"(d[15]),
          "+f"(d[16]), "+f"(d[17]), "+f"(d[18]), "+f"(d[19]), "+f"(d[20]), "+f"(d[21]), "+f"(d[22]), "+f"(d[23]),
          "+f"(d[24]), "+f"(d[25]), "+f"(d[26]), "+f"(d[27]), "+f"(d[28]), "+f"(d[29]), "+f"(d[30]), "+f"(d[31]),
          "+f"(d[32]), "+f"(d[33]), "+f"(d[34]), "+f"(d[35]), "+f"(d[36]), "+f"(d[37]), "+f"(d[38]), "+f"(d[39]),
          "+f"(d[40]), "+f"(d[41]), "+f"(d[42]), "+f"(d[43]), "+f"(d[44]), "+f"(d[45]), "+f"(d[46]), "+f"(d[47]),
          "+f"(d[48]), "+f"(d[49]), "+f"(d[50]), "+f"(d[51]), "+f"(d[52]), "+f"(d[53]), "+f"(d[54]), "+f"(d[55]),
          "+f"(d[56]), "+f"(d[57]), "+f"(d[58]), "+f"(d[59]), "+f"(d[60]), "+f"(d[61]), "+f"(d[62]), "+f"(d[63])
        : "r"(a0), "r"(a1), "r"(a2), "r"(a3), "l"(db));
}

constexpr uint64_t kDescHi = (uint64_t)(64u | 0x40000000u) << 32;
template <int MODE>
__device__ __forceinline__ void mma_kblock(float (&acc)[128], uint32_t a_lo, uint32_t b_lo, int keep) {
    constexpr uint32_t HALF = (MODE == 1) ? 12288u : 16384u;
    constexpr bool BN = (MODE == 1 || MODE == 2 || MODE == 4);
#pragma unroll
    for (int kk = 0; kk < 4; ++kk) {
        const uint32_t ao = (MODE == 3) ? kk * 2048u : kk * 32u;
        const uint32_t bo = BN ? ((kk >> 1) * HALF + (kk & 1) * 2048u) : kk * 32u;
        const uint64_t da = kDescHi | (uint64_t)(a_lo + (ao >> 4) + (1u << 16));
        const uint64_t db = kDescHi | (uint64_t)(b_lo + (bo >> 4) + (BN ? (256u << 16) : (1u << 16)));
        if (MODE == 1) wgmma_n192<0, 1>(acc, da, db, kk == 0 ? keep : 1);
        else if (MODE == 4) wgmma_n128<0, 1>(acc, da, db, 1);
        else wgmma_n256<(MODE == 3), BN>(acc, da, db, kk == 0 ? keep : 1);
    }
}

struct Params {
    Scratch* s;
    const __nv_bfloat16* x;
    const __nv_bfloat16* b_re;
    const __nv_bfloat16* b_im;
    const __nv_bfloat16* gate_w;
    const __nv_bfloat16* lam_re;
    const __nv_bfloat16* lam_im;
    const __nv_bfloat16* log_dt;
    const __nv_bfloat16* dskip;
    const __nv_bfloat16* b1;
    const __nv_bfloat16* b2;
    float* out;
    int swap;
};

#define CMUL(rr, ri, ar, ai, br, bi) do { float _r = (ar) * (br) - (ai) * (bi); float _i = (ar) * (bi) + (ai) * (br); rr = _r; ri = _i; } while (0)
#define CFMA(rr, ri, ar, ai, br, bi) do { float _r = fmaf(-(ai), (bi), fmaf((ar), (br), rr)); float _i = fmaf((ai), (br), fmaf((ar), (bi), ri)); rr = _r; ri = _i; } while (0)

#define KB_OPEN(IT, LAST)                                                                        \
    KT(IT, 0);                                                                                   \
    if (ORDER && (LAST) && wg == 1) bar_sync(7, 256);                                            \
    mbar_wait(bar_full + 8 * ((IT) & 3), ((IT) >> 2) & 1);                                \
    KT(IT, 1);
#define KB_CLOSE(IT, LAST, REL)                                                                  \
    if (ORDER && (LAST) && wg == 0) bar_arrive(7, 256);                                          \
    wgmma_wait<1>();                                                                             \
    if (lane < 2 && (REL)) mbar_arrive_cluster(rel_addr + 8 * (((IT) - 1) & 3));
#define KBLOCK(MODE, IT, FIRST, LAST)                                                            \
    {                                                                                            \
        const uint32_t so = ((IT) & 3) * (kStageBytes >> 4);                                     \
        KB_OPEN(IT, LAST);                                                                       \
        wgmma_fence();                                                                           \
        mma_kblock<MODE>(acc, a_lo + so, b_lo + so, !(FIRST));                                   \
        wgmma_commit();                                                                          \
        KB_CLOSE(IT, LAST, !(FIRST));                                                            \
    }
#define TILE_END() do { wgmma_wait<0>(); if (lane < 2) mbar_arrive_cluster(rel_addr + 24); } while (0)

__global__ void __cluster_dims__(2, 1, 1) __launch_bounds__(384, 1)
fused_kernel(const __grid_constant__ CUtensorMap mB, const __grid_constant__ CUtensorMap mXs, const __grid_constant__ CUtensorMap mXf,
             const __grid_constant__ CUtensorMap mW1b, const __grid_constant__ CUtensorMap mW1a, const __grid_constant__ CUtensorMap mHs,
             const __grid_constant__ CUtensorMap mHf, const __grid_constant__ CUtensorMap mCre, const __grid_constant__ CUtensorMap mCim,
             const __grid_constant__ CUtensorMap mW2, const __grid_constant__ CUtensorMap mW2n, const Params p) {
    extern __shared__ __align__(1024) uint8_t smem_raw[];
    const uint32_t sbase = smem_u32(smem_raw);
    if ((sbase & 0x3ffffu) != kSmemOrg) return;
    const uint32_t bar_full = sbase + kBarOff, bar_empty = bar_full + 32, bar_dep = bar_full + 64;
    const uint32_t bar_x = bar_full + 88, bar_c = bar_full + 96, role_s = bar_full + 104, tag_s = bar_full + 112 + (threadIdx.x & 1) * 4;

    const int tid = threadIdx.x, lane = tid & 31;
    const int warp = __shfl_sync(0xffffffffu, tid >> 5, 0);
    const uint32_t rank = blockIdx.x & 1;

    int pref;
    {
        unsigned smid;
        asm("mov.u32 %0, %%smid;" : "=r"(smid));
        const int t = smid >> 1, u = t - 32, d = (u * 37) >> 8;
        pref = (t < 32) ? (t & 7) * 8 + (t >> 3) : (t < 60) ? (1 + u - 7 * d) * 8 + 4 + d : ((t - 58) & 7);
    }
#define FIRST_FILL(ROLE)                                                                     \
    {                                                                                        \
        mbar_expect_tx(bar_full, 49152);                                                     \
        tma4(sbase, &mB, bar_full, 0, 0, 0, (((ROLE) & 7) * 2 + (int)rank) * 8);             \
        tma5(sbase + kABytes, &mXs, bar_full, 0, 0, 0, 0, (ROLE) >> 3);                      \
        tma5(sbase + kABytes + 16384, &mXs, bar_full, 0, 0, 0, 16, (ROLE) >> 3);             \
    }
    STAMP(tid == 0, 0);
    if (warp < 2) {
        if (elect_one()) {
            if (warp & 1) {
                if (rank == 0) {
                    int role = pref;
                    unsigned taken = atom_exch(&p.s->claim[pref], 1u);
#pragma unroll 1
                    for (int i = 0; taken != 0 && i < 64; ++i) { role = i; taken = atom_exch(&p.s->claim[i], 1u); }
                    sts32(role_s, role);
                    asm volatile("fence.acq_rel.cluster;" ::: "memory");
                }
            } else {
                prefetch_map(&mB); prefetch_map(&mXs);
#pragma unroll
                for (int s = 0; s < kStages; ++s) {
                    mbar_init(bar_full + 8 * s, 1);
                    mbar_init(bar_empty + 8 * s, 16);
                    mbar_init(bar_dep + 8 * s, 1);
                }
                mbar_init(bar_c, 96);
                asm volatile("fence.mbarrier_init.release.cluster;\nfence.proxy.async.shared::cta;" ::: "memory");
                FIRST_FILL(pref);
                mbar_expect_tx(bar_x, 2048);
                bulk_load(sbase + kXOff, p.gate_w, 2048, bar_x);
            }
        }
    } else if (warp < 2 + PF0LINES) {
        const int row = blockIdx.x * 32 + lane;
        const __nv_bfloat16* src = (row < 2048) ? p.x : (row < 3072) ? p.b_re - 2048 * kD : p.b_im - 3072 * kD;
        asm volatile("prefetch.global.L2 [%0];" ::"l"(src + row * kD + (warp - 2) * 64) : "memory");
    }
    __syncwarp();
    cluster_arrive();
    cluster_wait();
    const int role = __shfl_sync(0xffffffffu, (int)lds32_cluster(mapa(role_s, 0)), 0);
    if (__builtin_expect(role != pref, 0)) {
        if (warp == 0 && elect_one()) {
            mbar_wait(bar_full, 0);
            asm volatile("mbarrier.inval.shared::cta.b64 [%0];" ::"r"(bar_full) : "memory");
            mbar_init(bar_full, 1);
            asm volatile("fence.mbarrier_init.release.cluster;\nfence.proxy.async.shared::cta;" ::: "memory");
            FIRST_FILL(role);
        }
        __syncwarp();
        bar_sync(0, 384);
    }
    const int c = role >> 3;
    const int j8 = role & 7;
    const int cb = j8 * 2 + (int)rank;
    const int rb = 2 * c + (int)rank;
    const int kh = j8 >> 2;
    const int colK = (j8 & 3) * 256 + kh * 128, colS = colK ^ 128;

    if (warp >= 8) {
        asm volatile("setmaxnreg.dec.sync.aligned.u32 24;");
        if (warp > 8) {
            if (warp == 11) {
                if (lane < 9) prefetch_map(&mXf + lane);
#pragma unroll 1
                for (int en = lane; en < 88; en += 32) {
                    const int J = en >> 2;
                    const __nv_bfloat16* src = ((J < 14) ? p.b1 : (J < 18) ? p.dskip : p.b2) + 32 * J + 2 * (en & 3) +
                                               ((J < 6) ? 2048 + 192 * j8 : (J < 14) ? 256 * j8 - 192 : colK - ((J < 18) ? 448 : 576));
                    sts128(sbase + kBiasOff + en * 16, ldg32(src), ldg32(src + 8), ldg32(src + 16), ldg32(src + 24));
                }
                mbar_arrive_local(bar_c);
            } else {
                {
                    sts32(tag_s, ld_relaxed32(&p.s->epoch) + 1);
                    const int ch = cb * 64 + (tid - 288);
                    const uint32_t t_s = sbase + kTabOff + (tid - 288) * 64;
                    const float Lr = bf_lo(ldg16(p.lam_re + ch)), Li = bf_lo(ldg16(p.lam_im + ch));
                    const float dt = bf16_round(expf(bf_lo(ldg16(p.log_dt + ch))));
                    const float ea = expf(dt * Lr);
                    float lr, li;
                    sincospif((dt * Li) * 0.31830988618379067f, &li, &lr);
                    lr *= ea; li *= ea;
                    const float nr = lr - 1.0f, ni = li;
                    const bool big = fabsf(Lr) >= fabsf(Li);
                    const float u = big ? Lr : Li, v = big ? Li : Lr;
                    const float t = v / u, d = 2.0f / fmaf(v, t, u);
                    const float cr = (big ? fmaf(ni, t, nr) : fmaf(nr, t, ni)) * d, ci = (big ? fmaf(-nr, t, ni) : fmaf(ni, t, -nr)) * d;
                    if (p.swap) li = -li;
                    const float m00 = p.swap ? -ci : cr, m01 = p.swap ? cr : -ci, m10 = p.swap ? -cr : -ci, m11 = p.swap ? -ci : -cr;
#pragma unroll
                    for (int q = 0; q < 4; ++q) {
                        sts128f(t_s + q * 16, lr, li, m00, m01);
                        sts128f(t_s + 12288 + q * 16, 0.f, 0.f, 0.f, 0.f);
                    }
#pragma unroll 1
                    for (int i = 0; i < 6; ++i) CMUL(lr, li, lr, li, lr, li);
                    float ar, ai, br, bi;
                    CMUL(ar, ai, lr, li, lr, li);
                    CMUL(br, bi, ar, ai, lr, li);
                    sts128f(t_s + 4096, m10, m11, 0.f, 0.f);
#pragma unroll
                    for (int q = 1; q < 4; ++q) sts128f(t_s + 4096 + q * 16, m10, m11, lr, li);
                    sts128f(t_s + 8192, 0.f, 0.f, 1.f, 0.f);
                    sts128f(t_s + 8192 + 16, 0.f, 0.f, lr, li);
                    sts128f(t_s + 8192 + 32, ar, ai, ar, ai);
                    sts128f(t_s + 8192 + 48, ar, ai, br, bi);
                    CMUL(ar, ai, ar, ai, ar, ai);
                    br = 1.f; bi = 0.f;
#pragma unroll 1
                    for (int k = c - 1; k >= 0; --k) {
                        sts64f(t_s + 12288 + (k & 3) * 16 + (k >> 2) * 8, br, bi);
                        CMUL(br, bi, br, bi, ar, ai);
                    }
                    mbar_arrive_local(bar_c);
                }
                if (warp == 9) {
#pragma unroll 1
                    for (int ev = 0; ev < 3; ++ev) {
                        bar_sync(3 + ev, 288);
                        if (lane == 0) {
                            unsigned* cnt = &p.s->cnt[(ev == 0 ? c : 16 * ev - 8 + rb) * 32];
                            asm volatile("fence.acq_rel.gpu;\nfence.proxy.async.global;" ::: "memory");
                            asm volatile("red.relaxed.gpu.global.add.u32 [%0], 1;" ::"l"(cnt) : "memory");
                        }
                        __syncwarp();
                    }
                } else if (lane == 0) {
                    const unsigned tag = lds32(tag_s);
#pragma unroll 1
                    for (int ev = 0; ev < 3; ++ev) {
                        wait_counter(&p.s->cnt[(ev == 0 ? c : 16 * ev - 8 + rb) * 32], tag * (ev == 0 ? 16u : 8u));
                        mbar_arrive_local(bar_dep + 8 * ev);
                        if (ev == 0 && atomicInc(&p.s->done, 127u) == 127u) {
                            st_relaxed32(&p.s->epoch, tag);
#pragma unroll 1
                            for (int i = 0; i < 64; i += 4) stg128(&p.s->claim[i], 0, 0, 0, 0);
                        }
                    }
                }
            }
        } else if (elect_one()) {
            int it = 1;
#define ACQUIRE(BYTES)                                                   \
    const uint32_t st = sbase + (it & 3) * kStageBytes, fb = bar_full + 8 * (it & 3); \
    mbar_wait(bar_empty + 8 * (it & 3), ((it >> 2) & 1) ^ 1);     \
    mbar_expect_tx(fb, BYTES);
#pragma unroll 1
            for (; it < 16; ++it) {
                ACQUIRE(49152);
                tma4(st, &mB, fb, it * 64, 0, 0, cb * 8);
                tma5_mc(st + kABytes + rank * 16384, &mXs, fb, it * 64, 0, 0, rank * 16, c);
            }
#pragma unroll 1
            for (; it < 48; ++it) {
                const bool t1 = it < 32;
                const int k0 = (it & 15) * 64;
                ACQUIRE(t1 ? 40960 : 49152);
                tma5(st, &mXf, fb, k0, 0, 0, rank * 4, c);
                tma3_mc(st + kABytes + rank * (t1 ? 12288 : 16384), t1 ? &mW1b : &mW1a, fb, 0, k0 + rank * 32, t1 ? 32 + 3 * j8 : 4 * j8);
                if ((it & ~2) == XLDKB) {
                    const int h = (it >> 1) & 1;
                    if (h == 0) mbar_expect_tx(bar_x, 32768);
                    tma5(sbase + kXOff + h * 16384, &mXf, bar_x, colK + h * 64, 0, 0, rank * 4, c);
                }
            }
            STAMP(true, 8);
            mbar_wait(bar_dep, 0);
            asm volatile("fence.proxy.async.global;" ::: "memory");
            STAMP(true, 9);
#pragma unroll 1
            for (; it < 64; ++it) {
                const int k0 = (it & 15) * 64;
                ACQUIRE(49152);
                tma3(st, &mHs, fb, 0, kh * 1024 + k0, rb * 2);
                tma2_mc(st + kABytes + rank * 16384, kh ? &mCim : &mCre, fb, k0, rank ? colS : colK);
            }
            int f0 = 2048 + 768 * kh;
#pragma unroll 1
            for (; it < kTotal; ++it, f0 += 64) {
                if (it == 64 || it == 76) {
                    mbar_wait(bar_dep + (it == 64 ? 8 : 16), 0);
                    asm volatile("fence.proxy.async.global;" ::: "memory");
                    if (it == 76) f0 = 1024 * kh;
                }
                if (f0 == 256 * j8) f0 += 256;
                if (it == 88) f0 = 256 * (j8 ^ 4);
                ACQUIRE(49152);
                tma2(st, &mHf, fb, f0, rb * 128);
                tma5_mc(st + kABytes + rank * 16384, &mW2, fb, 0, 0, (f0 >> 3) + 4 * rank, 0, colK >> 6);
                if (it < 88) tma5_mc(st + kABytes + rank * 16384 + 8192, &mW2, fb, 0, 0, (f0 >> 3) + 4 * rank, 0, colS >> 6);
                else tma3_mc(st + kABytes + rank * 16384 + 8192, &mW2n, fb, 0, (f0 ^ 1024) + 32 * rank, colK >> 6);
            }
        }
    } else {
        asm volatile("setmaxnreg.inc.sync.aligned.u32 240;");
        const int wg = warp >> 2, w = warp & 3, r = lane >> 2, q = lane & 3, tw = tid & 127;
        uint32_t a_lo = (kSmemOrg + wg * 8192) >> 4;
        constexpr uint32_t b_lo = (kSmemOrg + kABytes) >> 4;
        const uint32_t rel_addr = mapa(bar_empty, (uint32_t)(lane & 1));
        const uint32_t gate_s = sbase + kGateOff;
        float acc[128];
        uint32_t pk[64];
        unsigned tag;
        UNDEF_R(tag);

#pragma unroll
        for (int i = 0; i < 128; ++i) UNDEF_F(acc[i]);
        {
            const uint32_t gx_s = sbase + kABytes + (16 * cb + 2 * warp + (lane >> 4)) * 128 +
                                  ((((lane & 15) >> 1) ^ (2 * w + (lane >> 4))) << 4) + (lane & 1) * 8;
            const uint32_t gw_s = sbase + kXOff + (lane & 15) * 8;
            float gs = 0.f;
            mbar_wait(bar_x, 0);
#pragma unroll 1
            for (uint32_t it = 0; it < 16; ++it) {
                KBLOCK(0, it, it == 0, it == 15);
                STAMP(tid == 0 && it == 0, 1);
                const uint2 xa = lds64(gx_s + (it & 3) * kStageBytes), wa = lds64(gw_s + it * 128);
                const uint32_t pa = bf2_mul(xa.x, wa.x), pb = bf2_mul(xa.y, wa.y);
                gs += (bf_lo(pa) + bf_hi(pa)) + (bf_lo(pb) + bf_hi(pb));
            }
            mbar_wait(bar_c, 0);
            tag = lds32(tag_s);
#pragma unroll
            for (int o = 8; o > 0; o >>= 1) gs += __shfl_xor_sync(0xffffffffu, gs, o);
            const float g = bf16_round(__frcp_rn(1.0f + expf(-bf16_round(gs))));
            if ((lane & 15) == 0) st_relaxed64(&p.s->gate[c * 256 + (lane >> 4) + 64 * w + 4 * cb + 2 * wg], __float_as_uint(g), tag);
        }
        const uint32_t tab_s = sbase + kTabOff + tid * 16;
        const float4 k0 = lds128f(tab_s);
        TILE_END();
        STAMP(tid == 0, 2);
#pragma unroll
        for (int s = 0; s < 64; ++s) pk[s] = pack_bf16_v(acc[4 * (s >> 1) + (s & 1)], acc[4 * (s >> 1) + 2 + (s & 1)]);
#pragma unroll
        for (int i = 0; i < 96; ++i) UNDEF_F(acc[i]);

        const float lr = k0.x, li = k0.y, m00 = k0.z, m01 = k0.w;
        float m10, m11, hr = 0.f, hi = 0.f;
        uint32_t gg[4], orr[4], oii[4];
        const int ch = cb * 64 + warp * 8 + r;
        __nv_bfloat16* hs = p.s->Hs + (size_t)ch * 2048 + c * 256 + q * 8;
#define PASS2(KB)                                                                                      \
    _Pragma("unroll") for (int s = 0; s < 64; s += 2) {                                                \
        if (pass2_kb(s) != (KB)) continue;                                                             \
        if ((s & 7) == 0) {                                                                            \
            const uint4 ga = lds128(gate_s + (q * 72 + s) * 2);                                        \
            gg[0] = ga.x; gg[1] = ga.y; gg[2] = ga.z; gg[3] = ga.w;                                    \
        }                                                                                              \
        float o0[2], o1[2];                                                                            \
        _Pragma("unroll") for (int k = 0; k < 2; ++k) {                                                \
            PIN_R(pk[s + k]);                                                                          \
            float nr = bf_lo(pk[s + k]), ni = bf_hi(pk[s + k]);                                        \
            CFMA(nr, ni, lr, li, hr, hi);                                                              \
            hr = nr; hi = ni;                                                                          \
            o0[k] = fmaf(m00, hr, m01 * hi);                                                           \
            o1[k] = fmaf(m10, hr, m11 * hi);                                                           \
        }                                                                                              \
        orr[(s >> 1) & 3] = bf2_mul(pack_bf16(o0[0], o0[1]), gg[(s >> 1) & 3]);                        \
        oii[(s >> 1) & 3] = bf2_mul(pack_bf16(o1[0], o1[1]), gg[(s >> 1) & 3]);                        \
        if ((s & 7) == 6) {                                                                            \
            stg128(hs + 32 * (s >> 3), orr[0], orr[1], orr[2], orr[3]);                                \
            stg128(hs + 1024 * 2048 + 32 * (s >> 3), oii[0], oii[1], oii[2], oii[3]);                  \
        }                                                                                              \
    }                                                                                                  \
    PIN_F(hr); PIN_F(hi);
        {
            uint4 av0, av1, gv;
            float lqr, lqi;
#pragma unroll
            for (int kb = 0; kb < 16; ++kb) {
                PIN_R(a_lo);
                KBLOCK(1, 16 + kb, kb == 0, kb == 15);
                if (kb < 4) {
#pragma unroll
                    for (int s = kb * 16; s < kb * 16 + 16; ++s) {
                        float nr = bf_lo(pk[s]), ni = bf_hi(pk[s]);
                        CFMA(nr, ni, lr, li, hr, hi);
                        hr = nr; hi = ni;
                    }
                    PIN_F(hr); PIN_F(hi);
                }
                if (kb == 2) gv = ld_relaxed2x64(&p.s->gate[c * 256 + 2 * tw]);
                if (kb == 3) {
                    const float4 k1 = lds128f(tab_s + 4096), k2 = lds128f(tab_s + 8192);
                    m10 = k1.x; m11 = k1.y; lqr = k2.z; lqi = k2.w;
                    float tr = __shfl_up_sync(0xffffffffu, hr, 1, 4), ti = __shfl_up_sync(0xffffffffu, hi, 1, 4);
                    if (q >= 1) CFMA(hr, hi, k1.z, k1.w, tr, ti);
                    tr = __shfl_up_sync(0xffffffffu, hr, 2, 4); ti = __shfl_up_sync(0xffffffffu, hi, 2, 4);
                    if (q >= 2) CFMA(hr, hi, k2.x, k2.y, tr, ti);
                    if (q == 3) st_relaxed2x64(&p.s->agg[c * 1024 + ch], __float_as_uint(hr), tag, __float_as_uint(hi), tag);
                    tr = __shfl_up_sync(0xffffffffu, hr, 1, 4); ti = __shfl_up_sync(0xffffffffu, hi, 1, 4);
                    hr = (q >= 1) ? tr : 0.f; hi = (q >= 1) ? ti : 0.f;
                }
                if (kb == 4) {
                    unsigned spins = 0;
                    while (__any_sync(0xffffffffu, gv.y != tag || gv.w != tag)) {
                        if (++spins > kSpinLimit) break;
                        gv = ld_relaxed2x64(&p.s->gate[c * 256 + 2 * tw]);
                    }
                    sts32(gate_s + ((tw >> 5) * 72 + 2 * lane) * 2, __byte_perm(gv.x, gv.z, 0x7632));
                }
                if (kb == 5) {
                    av0 = make_uint4(0, tag, 0, tag); av1 = av0;
                    if (q < c) av0 = ld_relaxed2x64(&p.s->agg[q * 1024 + ch]);
                    if (q + 4 < c) av1 = ld_relaxed2x64(&p.s->agg[(q + 4) * 1024 + ch]);
                    bar_sync(1 + wg, 128);
                }
                if (kb == 6) {
                    const float4 k3 = lds128f(tab_s + 12288);
                    unsigned spins = 0;
                    while (__any_sync(0xffffffffu, av0.y != tag || av0.w != tag || av1.y != tag || av1.w != tag)) {
                        if (++spins > kSpinLimit) break;
                        if (q < c) av0 = ld_relaxed2x64(&p.s->agg[q * 1024 + ch]);
                        if (q + 4 < c) av1 = ld_relaxed2x64(&p.s->agg[(q + 4) * 1024 + ch]);
                    }
                    float vr, vi;
                    CMUL(vr, vi, k3.x, k3.y, __uint_as_float(av0.x), __uint_as_float(av0.z));
                    CFMA(vr, vi, k3.z, k3.w, __uint_as_float(av1.x), __uint_as_float(av1.z));
                    vr += __shfl_xor_sync(0xffffffffu, vr, 1); vi += __shfl_xor_sync(0xffffffffu, vi, 1);
                    vr += __shfl_xor_sync(0xffffffffu, vr, 2); vi += __shfl_xor_sync(0xffffffffu, vi, 2);
                    CFMA(hr, hi, lqr, lqi, vr, vi);
                }
                if (kb >= 6) { PASS2(kb); }
            }
            TILE_END();
        }
        STAMP(tid == 0, 3);
#pragma unroll
        for (int i = 0; i < 48; ++i) pk[i] = pack_bf16_v(acc[2 * i], acc[2 * i + 1]);
#pragma unroll
        for (int i = 0; i < 128; ++i) UNDEF_F(acc[i]);

        PIN_R(a_lo);
        KBLOCK(2, 32, true, false);
        PASS2(16);
        PIN_R(a_lo);
        KBLOCK(2, 33, false, false);
        PASS2(17);
        bar_arrive(3, 288);
        const uint32_t gate_row = gate_s + ((2 * (w & 1)) * 72 + 8 * (4 * rank + 2 * wg + (w >> 1)) + r) * 2;
        uint32_t om0, om1;
        {
            const float a = 1.0f - bf_lo(lds16(gate_row)), b = 1.0f - bf_lo(lds16(gate_row + 72 * 2));
            om0 = pack_bf16(a, a); om1 = pack_bf16(b, b);
        }
        __nv_bfloat16* hf = p.s->Hf + (size_t)(rb * 128 + wg * 64 + w * 16 + r) * kF + q * 8 + 2048 + 192 * j8;
        uint32_t bias_s = sbase + kBiasOff + q * 16;
#define FFN_SLICE(J)                                                                                   \
    {                                                                                                  \
        const uint4 bv = lds128(bias_s + (J) * 64);                                                    \
        const uint32_t bb[4] = {bv.x, bv.y, bv.z, bv.w};                                               \
        _Pragma("unroll") for (int jj = 0; jj < 4; ++jj) {                                             \
            const uint32_t r0 = bf2_add_relu(pk[8 * (J) + 2 * jj], bb[jj]), r1 = bf2_add_relu(pk[8 * (J) + 2 * jj + 1], bb[jj]); \
            pk[8 * (J) + 2 * jj] = bf2_mul(bf2_mul(r0, r0), om0);                                      \
            pk[8 * (J) + 2 * jj + 1] = bf2_mul(bf2_mul(r1, r1), om1);                                  \
        }                                                                                              \
        stg128(hf + 32 * (J), pk[8 * (J)], pk[8 * (J) + 2], pk[8 * (J) + 4], pk[8 * (J) + 6]);         \
        stg128(hf + 8 * kF + 32 * (J), pk[8 * (J) + 1], pk[8 * (J) + 3], pk[8 * (J) + 5], pk[8 * (J) + 7]); \
    }
        {
            uint32_t j = 0, nsl = 6;
#pragma unroll 1
            for (uint32_t it = 34; it < 88; ++it, ++j) {
                const uint32_t so = (it & 3) * (kStageBytes >> 4);
                KB_OPEN(it, it == 47);
                if ((it & ~15u) == 48) {
                    wgmma_fence();
                    mma_kblock<3>(acc, a_lo + so, b_lo + so, it != 48);
                    wgmma_commit();
                } else {
                    wgmma_fence();
                    mma_kblock<2>(acc, a_lo + so, b_lo + so, 1);
                    wgmma_commit();
                }
                KB_CLOSE(it, it == 47, it != 48);
                if (j < nsl) {
                    if (j & 4) {
                        if (j & 2) { if (j & 1) FFN_SLICE(7) else FFN_SLICE(6) } else { if (j & 1) FFN_SLICE(5) else FFN_SLICE(4) }
                    } else {
                        if (j & 2) { if (j & 1) FFN_SLICE(3) else FFN_SLICE(2) } else { if (j & 1) FFN_SLICE(1) else FFN_SLICE(0) }
                    }
                    if (j + 1 == nsl) bar_arrive(1 + (nsl >> 1), 288);
                } else if (it == 47) {
                    hf += 64 * j8 - 2048;
                    bias_s += 6 * 64;
                    j = -1; nsl = 8;
                    TILE_END();
                    STAMP(tid == 0, 4);
#pragma unroll
                    for (int i = 0; i < 64; ++i) pk[i] = pack_bf16_v(acc[2 * i], acc[2 * i + 1]);
                }
            }
        }
        {
            uint8_t* xo = p.s->X + (size_t)(role * 2 + rank) * kXBytes + tid * 16;
            const uint8_t* xi = xo + (kh ? -8 * kXBytes : 8 * kXBytes);
            const uint32_t x_s = sbase + kXOff + (wg * 64 + w * 16 + (lane & 15)) * 128 + (((lane >> 4) ^ (lane & 7)) << 4);
            uint4 rx[8];
            uint32_t rs;
#define ETERM(K)                                                                                       \
    {                                                                                                  \
        const int jb = (K) * 4;                                                                        \
        const float g0 = bf_lo(lds16(gate_row)), g1 = bf_lo(lds16(gate_row + 72 * 2));                 \
        const float o0f = bf_lo(om0), o1f = bf_lo(om1);                                                \
        const uint4 dq = lds128(bias_s + (8 + (K)) * 64), bq = lds128(bias_s + (12 + (K)) * 64);       \
        const uint4 xa = ldsm4((x_s ^ ((jb & 7) << 4)) + (jb >> 3) * 16384), xb = ldsm4((x_s ^ (((jb + 2) & 7) << 4)) + (jb >> 3) * 16384); \
        const uint32_t dv[4] = {dq.x, dq.y, dq.z, dq.w}, bv2[4] = {bq.x, bq.y, bq.z, bq.w};            \
        const uint32_t xv[8] = {xa.x, xa.y, xa.z, xa.w, xb.x, xb.y, xb.z, xb.w};                       \
        _Pragma("unroll") for (int jj = 0; jj < 4; ++jj) {                                             \
            const uint32_t x0 = bf2_mul(xv[2 * jj], dv[jj]), x1 = bf2_mul(xv[2 * jj + 1], dv[jj]);     \
            const float bl = bf_lo(bv2[jj]), bh = bf_hi(bv2[jj]);                                      \
            const int v = 64 + 4 * (jb + jj);                                                          \
            acc[v + 0] = fmaf(g0, bf_lo(x0), o0f * bl);                                                \
            acc[v + 1] = fmaf(g0, bf_hi(x0), o0f * bh);                                                \
            acc[v + 2] = fmaf(g1, bf_lo(x1), o1f * bl);                                                \
            acc[v + 3] = fmaf(g1, bf_hi(x1), o1f * bh);                                                \
            PIN_F(acc[v]); PIN_F(acc[v + 1]); PIN_F(acc[v + 2]); PIN_F(acc[v + 3]);                    \
        }                                                                                              \
    }
#define RXLOAD()                                                                                       \
    {                                                                                                  \
        rs = ld_relaxed32((const unsigned*)(xi + 32768 - tid * 12));                                   \
        _Pragma("unroll") for (int u = 0; u < 8; ++u) rx[u] = ld_relaxed2x64(xi + u * 4096);           \
    }
#pragma unroll
            for (int t = 0; t < 4; ++t) {
                PIN_R(a_lo);
                KB_OPEN(88 + t, t == 3);
                wgmma_fence();
                mma_kblock<4>(acc, a_lo + t * (kStageBytes >> 4), b_lo + t * (kStageBytes >> 4), 1);
#pragma unroll
                for (int kk = 0; kk < 4; ++kk)
                    wgmma_n128_rs(acc, pk[16 * t + 4 * kk], pk[16 * t + 4 * kk + 1], pk[16 * t + 4 * kk + 2], pk[16 * t + 4 * kk + 3],
                                  kDescHi | (uint64_t)(b_lo + ((t * kStageBytes + 8192 + (kk >> 1) * 16384 + (kk & 1) * 2048) >> 4) + (256u << 16)));
                wgmma_commit();
                KB_CLOSE(88 + t, t == 3, t == 0);
                if (t == 0) {
                    STAMP(tid == 0, 15);
                    float m[4] = {0.f, 0.f, 0.f, 0.f};
#pragma unroll
                    for (int i = 64; i < 128; ++i) m[i & 3] = fmaxf(m[i & 3], fabsf(acc[i]));
                    const uint32_t eb = max(__float_as_uint(fmaxf(fmaxf(m[0], m[1]), fmaxf(m[2], m[3]))) >> 23, 15u);
                    const float xsc = __uint_as_float((268u - eb) << 23);
                    st_relaxed32(xo + 32768 - tid * 12, lop3<0xd8>((eb - 14u) << 23, tag, 1));
#pragma unroll
                    for (int u = 0; u < 8; ++u) {
                        const int v = 64 + 8 * u;
                        st_relaxed2x64(xo + u * 4096, lop3<0xd8>(pack_f16(acc[v] * xsc, acc[v + 1] * xsc), tag, 1), pack_f16(acc[v + 2] * xsc, acc[v + 3] * xsc),
                                       lop3<0xd8>(pack_f16(acc[v + 4] * xsc, acc[v + 5] * xsc), tag, 1), pack_f16(acc[v + 6] * xsc, acc[v + 7] * xsc));
                    }
                    STAMP(tid == 0, 12);
                }
                if (t == 1) { mbar_wait(bar_x, 1); ETERM(0); ETERM(1); }
                if (t == 2) { ETERM(2); mbar_wait(bar_x, 1); RXLOAD(); ETERM(3); }
                if (t == 3) {
                    unsigned spins = 0;
                    mbar_wait(bar_x, 1);
#pragma unroll 1
                    while (true) {
                        uint32_t bad = rs ^ tag;
#pragma unroll
                        for (int u = 0; u < 8; u += 2) bad = lop3<0xfe>(bad, lop3<0x7e>(rx[u].x, rx[u].z, tag), lop3<0x7e>(rx[u + 1].x, rx[u + 1].z, tag));
                        if (!__any_sync(0xffffffffu, bad & 1) || ++spins > kSpinLimit) break;
                        RXLOAD();
                        RESPIN();
                    }
                    STAMP(tid == 0, 13);
                    const float xsc = __uint_as_float(rs & ~1u);
#pragma unroll
                    for (int u = 0; u < 8; ++u) {
                        const uint32_t rr[4] = {rx[u].x, rx[u].y, rx[u].z, rx[u].w};
#pragma unroll
                        for (int k = 0; k < 4; ++k) {
                            const int v = 64 + 8 * u + 2 * k;
                            const float2 f = __half22float2(*reinterpret_cast<const __half2*>(&rr[k]));
                            acc[v] = fmaf(f.x, xsc, acc[v]); acc[v + 1] = fmaf(f.y, xsc, acc[v + 1]);
                            PIN_F(acc[v]); PIN_F(acc[v + 1]);
                        }
                    }
                    STAMP(tid == 0, 14);
                }
            }
        }
        wgmma_wait<0>();
        STAMP(tid == 0, 6);
        {
            const bool odd = q & 1;
            const int tb = c * 256 + 128 * (w & 1) + 8 * (4 * rank + 2 * wg + (w >> 1));
            float* o0 = p.out + (size_t)(tb + r) * kD + colK + (odd ? 2 * q + 6 : 2 * q);
#pragma unroll
            for (int i = 0; i < 16; i += 2) {
#pragma unroll
                for (int h = 0; h < 2; ++h) {
                    const int va = 4 * i + 2 * h, vb = va + 4;
                    PIN_F(acc[va]); PIN_F(acc[va + 1]); PIN_F(acc[vb]); PIN_F(acc[vb + 1]);
                    const float a0 = acc[va] + acc[64 + va], a1 = acc[va + 1] + acc[65 + va];
                    const float b0 = acc[vb] + acc[64 + vb], b1 = acc[vb + 1] + acc[65 + vb];
                    const float t0 = __shfl_xor_sync(0xffffffffu, odd ? a0 : b0, 1), t1 = __shfl_xor_sync(0xffffffffu, odd ? a1 : b1, 1);
                    stg128f(o0 + h * 64 * kD + 8 * i, odd ? t0 : a0, odd ? t1 : a1, odd ? b0 : t0, odd ? b1 : t1);
                }
            }
        }
        STAMP(tid == 0, 7);
        STAMP(tid == 128, 5);
    }
}

typedef CUresult (*EncodeFn)(CUtensorMap*, CUtensorMapDataType, cuuint32_t, void*, const cuuint64_t*, const cuuint64_t*,
                             const cuuint32_t*, const cuuint32_t*, CUtensorMapInterleave, CUtensorMapSwizzle,
                             CUtensorMapL2promotion, CUtensorMapFloatOOBfill);

bool encode(EncodeFn fn, CUtensorMap* m, const void* base, int rank, const cuuint64_t* dims, const cuuint64_t* strides,
            const cuuint32_t* box) {
    cuuint32_t es[5] = {1, 1, 1, 1, 1};
    return fn(m, CU_TENSOR_MAP_DATA_TYPE_BFLOAT16, rank, const_cast<void*>(base), dims, strides, box, es,
              CU_TENSOR_MAP_INTERLEAVE_NONE, CU_TENSOR_MAP_SWIZZLE_128B, CU_TENSOR_MAP_L2_PROMOTION_L2_256B,
              CU_TENSOR_MAP_FLOAT_OOB_FILL_NONE) == CUDA_SUCCESS;
}

}

extern "C" void kernel_launch(void* const* d_in, const int* in_sizes, int n_in, void* d_out, int out_size) {
    (void)in_sizes; (void)n_in; (void)out_size;
    typedef const __nv_bfloat16* bp;
    bp x = (bp)d_in[0], lam_re = (bp)d_in[1], lam_im = (bp)d_in[2], B_re = (bp)d_in[3], B_im = (bp)d_in[4];
    bp C_re = (bp)d_in[5], C_im = (bp)d_in[6], log_dt = (bp)d_in[7], dskip = (bp)d_in[8];
    bp w1 = (bp)d_in[10], b1 = (bp)d_in[11], w2 = (bp)d_in[12], b2 = (bp)d_in[13], gate_w = (bp)d_in[14];

    static EncodeFn fn = nullptr;
    static Scratch* ps = nullptr;
    if (!fn) {
        void* f = nullptr;
        cudaDriverEntryPointQueryResult qr;
        cudaGetDriverEntryPoint("cuTensorMapEncodeTiled", &f, cudaEnableDefault, &qr);
        fn = (EncodeFn)f;
        cudaGetSymbolAddress((void**)&ps, g_s);
        cudaFuncSetAttribute(fused_kernel, cudaFuncAttributeMaxDynamicSharedMemorySize, kSmemBytes);
    }
    cudaStream_t stream = cudaStreamPerThread;

    Params p;
    p.x = x; p.lam_re = lam_re; p.lam_im = lam_im; p.log_dt = log_dt; p.dskip = dskip; p.b1 = b1; p.b2 = b2;
    p.gate_w = gate_w; p.b_re = B_re; p.b_im = B_im; p.out = (float*)d_out; p.s = ps;
    char* const pHs = (char*)ps + offsetof(Scratch, Hs);
    char* const pHf = (char*)ps + offsetof(Scratch, Hf);
    char* const pBc = (char*)ps + offsetof(Scratch, Bcopy);

    const char* lo = (const char*)B_re; const char* hi = (const char*)B_im;
    p.swap = 0;
    if (hi < lo) { const char* t = lo; lo = hi; hi = t; p.swap = 1; }
    unsigned long long diff = (unsigned long long)(hi - lo);
    if (diff >= (1ull << 40) || (diff & 15) || diff == 0) {
        cudaMemcpyAsync(pBc, B_re, 2u << 20, cudaMemcpyDeviceToDevice, stream);
        cudaMemcpyAsync((char*)pBc + (2u << 20), B_im, 2u << 20, cudaMemcpyDeviceToDevice, stream);
        lo = (const char*)pBc; diff = 2u << 20; p.swap = 0;
    }

    CUtensorMap mB, mXs, mXf, mW1a, mW1b, mHs, mHf, mCre, mCim, mW2, mW2n;
    bool ok = true;
    { cuuint64_t d[4] = {1024, 8, 2, 128}, s[3] = {2048, diff, 16384}; cuuint32_t b[4] = {64, 8, 2, 8};
      ok &= encode(fn, &mB, lo, 4, d, s, b); }
    { cuuint64_t d[5] = {1024, 2, 4, 32, 8}, s[4] = {2048, 64 * 2048, 2 * 2048, 256 * 2048}; cuuint32_t b[5] = {64, 2, 4, 16, 1};
      ok &= encode(fn, &mXs, x, 5, d, s, b); }
    { cuuint64_t d[5] = {1024, 8, 4, 8, 8}, s[4] = {2048, 64 * 2048, 8 * 2048, 256 * 2048}; cuuint32_t b[5] = {64, 8, 4, 4, 1};
      ok &= encode(fn, &mXf, x, 5, d, s, b); }
    { cuuint64_t d[3] = {64, 1024, 56}, s[2] = {7168, 128}; cuuint32_t ba[3] = {64, 32, 4}, bb[3] = {64, 32, 3};
      ok &= encode(fn, &mW1a, w1, 3, d, s, ba); ok &= encode(fn, &mW1b, w1, 3, d, s, bb); }
    { cuuint64_t d[3] = {64, 2048, 32}, s[2] = {4096, 128}; cuuint32_t b[3] = {64, 64, 2};
      ok &= encode(fn, &mHs, pHs, 3, d, s, b); }
    { cuuint64_t d[2] = {3584, 2048}, s[1] = {7168}; cuuint32_t b[2] = {64, 128};
      ok &= encode(fn, &mHf, pHf, 2, d, s, b); }
    { cuuint64_t d[2] = {1024, 1024}, s[1] = {2048}; cuuint32_t b[2] = {64, 128};
      ok &= encode(fn, &mCre, C_re, 2, d, s, b); ok &= encode(fn, &mCim, C_im, 2, d, s, b); }
    { cuuint64_t d[5] = {64, 2, 448, 4, 16}, s[4] = {2048, 8 * 2048, 2 * 2048, 128}; cuuint32_t b[5] = {64, 2, 4, 4, 2};
      ok &= encode(fn, &mW2, w2, 5, d, s, b); }
    { cuuint64_t d[3] = {64, 3584, 16}, s[2] = {2048, 128}; cuuint32_t b[3] = {64, 32, 2};
      ok &= encode(fn, &mW2n, w2, 3, d, s, b); }
    if (!ok) return;

    fused_kernel<<<128, 384, kSmemBytes, stream>>>(mB, mXs, mXf, mW1b, mW1a, mHs, mHf, mCre, mCim, mW2, mW2n, p);
}
```

```cpp
#include <cuda_runtime.h>
#include <cuda_bf16.h>
#include <cuda_fp16.h>
#include <cuda.h>
#include <stdint.h>
#include <stddef.h>

#define XLDKB 40
#define PF0LINES 2
#define ETKB 60
#define RXT 2
#define ORDER 0

namespace {

constexpr int kD = 1024, kF = 3584;
constexpr int kStages = 4;
constexpr int kStageBytes = 49152;
constexpr int kABytes = 16384;
constexpr int kXOff = kStages * kStageBytes;
constexpr int kTabOff = kXOff + 2048;
constexpr int kGateOff = kXOff + 32768;
constexpr int kBiasOff = kGateOff + 4 * 72 * 2;
constexpr int kBarOff = kBiasOff + 88 * 16;
constexpr int kSmemBytes = 232448;
static_assert(kBarOff + 128 <= kSmemBytes, "smem");
constexpr int kXBytes = 33792;
constexpr uint32_t kSmemOrg = 1024;
constexpr unsigned kSpinLimit = 1u << 18;
constexpr int kTotal = 92;

__host__ __device__ constexpr int pass2_kb(int s) {
    return s < 2 ? 6 : s < 8 ? 7 : s < 12 ? 8 : s < 18 ? 9 : s < 22 ? 10 : s < 28 ? 11 : s < 32 ? 12 : s < 38 ? 13 : s < 42 ? 14 : s < 48 ? 15 : s < 56 ? 16 : 17;
}

struct Scratch {
    unsigned claim[64];
    unsigned epoch, pad0[31];
    unsigned done, pad1[31];
    unsigned cnt[40 * 32];
    uint2 gate[2048];
    uint4 agg[8 * 1024];
    __align__(1024) uint8_t X[128 * kXBytes];
    __align__(1024) __nv_bfloat16 Hs[2048 * 2048];
    __align__(1024) __nv_bfloat16 Hf[2048 * 3584];
    __align__(1024) __nv_bfloat16 Bcopy[2 * 1024 * 1024];
};
__device__ Scratch g_s;

#define TRAP() break
#define PIN_F(x) asm volatile("" : "+f"(x))
#define PIN_R(x) asm volatile("" : "+r"(x))
#define UNDEF_F(x) asm volatile("" : "=f"(x))
#define UNDEF_R(x) asm volatile("" : "=r"(x))
#define RESPIN()
__device__ __forceinline__ uint32_t smem_u32(const void* p) { return (uint32_t)__cvta_generic_to_shared(p); }
__device__ __forceinline__ void mbar_init(uint32_t bar, uint32_t count) {
    asm volatile("mbarrier.init.shared::cta.b64 [%0], %1;" ::"r"(bar), "r"(count) : "memory");
}
__device__ __forceinline__ void mbar_expect_tx(uint32_t bar, uint32_t bytes) {
    asm volatile("mbarrier.arrive.expect_tx.shared::cta.b64 _, [%0], %1;" ::"r"(bar), "r"(bytes) : "memory");
}
__device__ __forceinline__ void mbar_wait(uint32_t bar, uint32_t parity) {
    asm volatile(
        "{\n.reg .pred p;\n.reg .u32 n;\n"
        "mbarrier.try_wait.parity.shared::cta.b64 p, [%0], %1;\n"
        "@p bra DONE;\n"
        "mov.u32 n, 0;\n"
        "LOOP:\n"
        "mbarrier.try_wait.parity.shared::cta.b64 p, [%0], %1;\n"
        "@p bra DONE;\n"
        "add.u32 n, n, 1;\n"
        "setp.lt.u32 p, n, %2;\n"
        "@p bra LOOP;\n"
        "DONE:\n}\n"
        ::"r"(bar), "r"(parity), "n"(kSpinLimit) : "memory");
}
__device__ __forceinline__ void mbar_arrive_local(uint32_t bar) {
    asm volatile("mbarrier.arrive.shared::cta.b64 _, [%0];" ::"r"(bar) : "memory");
}
__device__ __forceinline__ void mbar_arrive_cluster(uint32_t cluster_addr) {
    asm volatile("mbarrier.arrive.shared::cluster.b64 _, [%0];" ::"r"(cluster_addr) : "memory");
}
__device__ __forceinline__ uint32_t mapa(uint32_t addr, uint32_t rank) {
    uint32_t r;
    asm("mapa.shared::cluster.u32 %0, %1, %2;" : "=r"(r) : "r"(addr), "r"(rank));
    return r;
}
__device__ __forceinline__ void cluster_arrive() { asm volatile("barrier.cluster.arrive.relaxed.aligned;" ::: "memory"); }
__device__ __forceinline__ void cluster_wait() { asm volatile("barrier.cluster.wait.acquire.aligned;" ::: "memory"); }
__device__ __forceinline__ void bar_sync(int id, int n) { asm volatile("bar.sync %0, %1;" ::"r"(id), "r"(n) : "memory"); }
__device__ __forceinline__ void bar_arrive(int id, int n) { asm volatile("bar.arrive %0, %1;" ::"r"(id), "r"(n) : "memory"); }
__device__ __forceinline__ bool elect_one() {
    uint32_t p;
    asm volatile("{\n.reg .pred P;\nelect.sync _|P, 0xffffffff;\nselp.u32 %0, 1, 0, P;\n}\n" : "=r"(p));
    return p != 0;
}

__device__ __forceinline__ void tma2(uint32_t dst, const CUtensorMap* m, uint32_t bar, int c0, int c1) {
    asm volatile("cp.async.bulk.tensor.2d.shared::cluster.global.mbarrier::complete_tx::bytes [%0], [%1, {%3, %4}], [%2];"
                 ::"r"(dst), "l"(m), "r"(bar), "r"(c0), "r"(c1) : "memory");
}
__device__ __forceinline__ void tma3(uint32_t dst, const CUtensorMap* m, uint32_t bar, int c0, int c1, int c2) {
    asm volatile("cp.async.bulk.tensor.3d.shared::cluster.global.mbarrier::complete_tx::bytes [%0], [%1, {%3, %4, %5}], [%2];"
                 ::"r"(dst), "l"(m), "r"(bar), "r"(c0), "r"(c1), "r"(c2) : "memory");
}
__device__ __forceinline__ void tma4(uint32_t dst, const CUtensorMap* m, uint32_t bar, int c0, int c1, int c2, int c3) {
    asm volatile("cp.async.bulk.tensor.4d.shared::cluster.global.mbarrier::complete_tx::bytes [%0], [%1, {%3, %4, %5, %6}], [%2];"
                 ::"r"(dst), "l"(m), "r"(bar), "r"(c0), "r"(c1), "r"(c2), "r"(c3) : "memory");
}
__device__ __forceinline__ void tma5(uint32_t dst, const CUtensorMap* m, uint32_t bar, int c0, int c1, int c2, int c3, int c4) {
    asm volatile("cp.async.bulk.tensor.5d.shared::cluster.global.mbarrier::complete_tx::bytes [%0], [%1, {%3, %4, %5, %6, %7}], [%2];"
                 ::"r"(dst), "l"(m), "r"(bar), "r"(c0), "r"(c1), "r"(c2), "r"(c3), "r"(c4) : "memory");
}
__device__ __forceinline__ void tma2_mc(uint32_t dst, const CUtensorMap* m, uint32_t bar, int c0, int c1) {
    asm volatile("cp.async.bulk.tensor.2d.shared::cluster.global.mbarrier::complete_tx::bytes.multicast::cluster [%0], [%1, {%3, %4}], [%2], %5;"
                 ::"r"(dst), "l"(m), "r"(bar), "r"(c0), "r"(c1), "h"((uint16_t)3) : "memory");
}
__device__ __forceinline__ void tma3_mc(uint32_t dst, const CUtensorMap* m, uint32_t bar, int c0, int c1, int c2) {
    asm volatile("cp.async.bulk.tensor.3d.shared::cluster.global.mbarrier::complete_tx::bytes.multicast::cluster [%0], [%1, {%3, %4, %5}], [%2], %6;"
                 ::"r"(dst), "l"(m), "r"(bar), "r"(c0), "r"(c1), "r"(c2), "h"((uint16_t)3) : "memory");
}
__device__ __forceinline__ void tma5_mc(uint32_t dst, const CUtensorMap* m, uint32_t bar, int c0, int c1, int c2, int c3, int c4) {
    asm volatile("cp.async.bulk.tensor.5d.shared::cluster.global.mbarrier::complete_tx::bytes.multicast::cluster [%0], [%1, {%3, %4, %5, %6, %7}], [%2], %8;"
                 ::"r"(dst), "l"(m), "r"(bar), "r"(c0), "r"(c1), "r"(c2), "r"(c3), "r"(c4), "h"((uint16_t)3) : "memory");
}
__device__ __forceinline__ void bulk_store(void* dst, uint32_t src, uint32_t bytes) {
    asm volatile("cp.async.bulk.global.shared::cta.bulk_group [%0], [%1], %2;" ::"l"(dst), "r"(src), "r"(bytes) : "memory");
}
__device__ __forceinline__ void bulk_load(uint32_t dst, const void* src, uint32_t bytes, uint32_t bar) {
    asm volatile("cp.async.bulk.shared::cluster.global.mbarrier::complete_tx::bytes [%0], [%1], %2, [%3];"
                 ::"r"(dst), "l"(src), "r"(bytes), "r"(bar) : "memory");
}
__device__ __forceinline__ unsigned atom_exch(unsigned* p, unsigned v) {
    unsigned r;
    asm volatile("atom.relaxed.gpu.global.exch.b32 %0, [%1], %2;" : "=r"(r) : "l"(p), "r"(v) : "memory");
    return r;
}
__device__ __forceinline__ uint32_t lds32_cluster(uint32_t a) {
    uint32_t v;
    asm volatile("ld.shared::cluster.u32 %0, [%1];" : "=r"(v) : "r"(a) : "memory");
    return v;
}
__device__ __forceinline__ void sts128f(uint32_t a, float x, float y, float z, float w) {
    asm volatile("st.shared.v4.f32 [%0], {%1, %2, %3, %4};" ::"r"(a), "f"(x), "f"(y), "f"(z), "f"(w) : "memory");
}
__device__ __forceinline__ void prefetch_map(const CUtensorMap* m) {
    asm volatile("prefetch.tensormap [%0];" ::"l"(m) : "memory");
}

__device__ __forceinline__ void prefetch_l2(const void* p, uint32_t bytes) {
    asm volatile("cp.async.bulk.prefetch.L2.global [%0], %1;" ::"l"(p), "r"(bytes) : "memory");
}

__device__ __forceinline__ void wgmma_fence() { asm volatile("wgmma.fence.sync.aligned;" ::: "memory"); }
__device__ __forceinline__ void wgmma_commit() { asm volatile("wgmma.commit_group.sync.aligned;" ::: "memory"); }
template <int N>
__device__ __forceinline__ void wgmma_wait() { asm volatile("wgmma.wait_group.sync.aligned %0;" ::"n"(N) : "memory"); }

__device__ __forceinline__ uint32_t pack_bf16(float lo, float hi) {
    uint32_t r;
    asm("cvt.rn.bf16x2.f32 %0, %1, %2;" : "=r"(r) : "f"(hi), "f"(lo));
    return r;
}
__device__ __forceinline__ uint32_t pack_f16(float lo, float hi) {
    uint32_t r;
    asm("cvt.rn.f16x2.f32 %0, %1, %2;" : "=r"(r) : "f"(hi), "f"(lo));
    return r;
}
__device__ __forceinline__ uint32_t pack_bf16_v(float lo, float hi) {
    uint32_t r;
    asm volatile("cvt.rn.bf16x2.f32 %0, %1, %2;" : "=r"(r) : "f"(hi), "f"(lo));
    return r;
}
template <int LUT>
__device__ __forceinline__ uint32_t lop3(uint32_t a, uint32_t b, uint32_t c) {
    uint32_t r;
    asm("lop3.b32 %0, %1, %2, %3, %4;" : "=r"(r) : "r"(a), "r"(b), "r"(c), "n"(LUT));
    return r;
}
__device__ __forceinline__ float bf_lo(uint32_t v) { return __uint_as_float(v << 16); }
__device__ __forceinline__ float bf_hi(uint32_t v) { return __uint_as_float(v & 0xffff0000u); }
__device__ __forceinline__ float bf16_round(float v) { return __bfloat162float(__float2bfloat16_rn(v)); }
__device__ __forceinline__ uint32_t bf2_mul(uint32_t a, uint32_t b) {
    uint32_t r;
    asm("mul.rn.bf16x2 %0, %1, %2;" : "=r"(r) : "r"(a), "r"(b));
    return r;
}
__device__ __forceinline__ uint32_t bf2_add_relu(uint32_t a, uint32_t b) {
    uint32_t r;
    asm("fma.rn.relu.bf16x2 %0, %1, %2, %3;" : "=r"(r) : "r"(a), "r"(0x3f803f80u), "r"(b));
    return r;
}
__device__ __forceinline__ uint4 ldg128(const void* p) {
    uint4 v;
    asm volatile("ld.global.nc.v4.u32 {%0, %1, %2, %3}, [%4];" : "=r"(v.x), "=r"(v.y), "=r"(v.z), "=r"(v.w) : "l"(p));
    return v;
}
__device__ __forceinline__ uint32_t ldg32(const void* p) {
    uint32_t v;
    asm volatile("ld.global.nc.u32 %0, [%1];" : "=r"(v) : "l"(p));
    return v;
}
__device__ __forceinline__ uint32_t ldg32na(const void* p) {
    uint32_t v;
    asm volatile("ld.global.nc.L1::no_allocate.u32 %0, [%1];" : "=r"(v) : "l"(p));
    return v;
}
__device__ __forceinline__ uint32_t ldg16(const __nv_bfloat16* p) {
    uint32_t v;
    asm volatile("ld.global.nc.u16 %0, [%1];" : "=r"(v) : "l"(p));
    return v;
}
__device__ __forceinline__ uint4 ld_relaxed128(const void* p) {
    uint4 v;
    asm volatile("ld.relaxed.gpu.global.v4.u32 {%0, %1, %2, %3}, [%4];" : "=r"(v.x), "=r"(v.y), "=r"(v.z), "=r"(v.w) : "l"(p) : "memory");
    return v;
}
__device__ __forceinline__ uint2 ld_relaxed64(const void* p) {
    unsigned long long v;
    asm volatile("ld.relaxed.gpu.global.u64 %0, [%1];" : "=l"(v) : "l"(p) : "memory");
    return make_uint2((uint32_t)v, (uint32_t)(v >> 32));
}
__device__ __forceinline__ void st_relaxed64(void* p, uint32_t lo, uint32_t hi) {
    unsigned long long v = ((unsigned long long)hi << 32) | lo;
    asm volatile("st.relaxed.gpu.global.u64 [%0], %1;" ::"l"(p), "l"(v) : "memory");
}
__device__ __forceinline__ void st_relaxed2x64(void* p, uint32_t a, uint32_t b, uint32_t c, uint32_t d) {
    unsigned long long v0 = ((unsigned long long)b << 32) | a, v1 = ((unsigned long long)d << 32) | c;
    asm volatile("st.relaxed.gpu.global.v2.u64 [%0], {%1, %2};" ::"l"(p), "l"(v0), "l"(v1) : "memory");
}
__device__ __forceinline__ uint4 ld_relaxed2x64(const void* p) {
    unsigned long long v0, v1;
    asm volatile("ld.relaxed.gpu.global.v2.u64 {%0, %1}, [%2];" : "=l"(v0), "=l"(v1) : "l"(p) : "memory");
    return make_uint4((uint32_t)v0, (uint32_t)(v0 >> 32), (uint32_t)v1, (uint32_t)(v1 >> 32));
}
__device__ __forceinline__ void stg128(void* p, uint32_t a, uint32_t b, uint32_t c, uint32_t d) {
    asm volatile("st.global.v4.u32 [%0], {%1, %2, %3, %4};" ::"l"(p), "r"(a), "r"(b), "r"(c), "r"(d) : "memory");
}
__device__ __forceinline__ void stg64f(void* p, float a, float b) {
    asm volatile("st.global.v2.f32 [%0], {%1, %2};" ::"l"(p), "f"(a), "f"(b) : "memory");
}
__device__ __forceinline__ uint4 lds128(uint32_t a) {
    uint4 v;
    asm volatile("ld.shared.v4.u32 {%0, %1, %2, %3}, [%4];" : "=r"(v.x), "=r"(v.y), "=r"(v.z), "=r"(v.w) : "r"(a) : "memory");
    return v;
}
__device__ __forceinline__ uint2 lds64(uint32_t a) {
    uint2 v;
    asm volatile("ld.shared.v2.u32 {%0, %1}, [%2];" : "=r"(v.x), "=r"(v.y) : "r"(a) : "memory");
    return v;
}
__device__ __forceinline__ uint4 ldsm4(uint32_t a) {
    uint4 v;
    asm volatile("ldmatrix.sync.aligned.m8n8.x4.shared.b16 {%0, %1, %2, %3}, [%4];" : "=r"(v.x), "=r"(v.y), "=r"(v.z), "=r"(v.w) : "r"(a) : "memory");
    return v;
}
__device__ __forceinline__ uint32_t lds16(uint32_t a) {
    uint32_t v;
    asm volatile("ld.shared.u16 %0, [%1];" : "=r"(v) : "r"(a) : "memory");
    return v;
}
__device__ __forceinline__ void sts16(uint32_t a, uint32_t x) {
    asm volatile("st.shared.u16 [%0], %1;" ::"r"(a), "h"((uint16_t)x) : "memory");
}
__device__ __forceinline__ void st_relaxed32(void* p, uint32_t v) {
    asm volatile("st.relaxed.gpu.global.u32 [%0], %1;" ::"l"(p), "r"(v) : "memory");
}
__device__ __forceinline__ float lds32f(uint32_t a) {
    float v;
    asm volatile("ld.shared.f32 %0, [%1];" : "=f"(v) : "r"(a) : "memory");
    return v;
}
__device__ __forceinline__ void sts128(uint32_t a, uint32_t x, uint32_t y, uint32_t z, uint32_t w) {
    asm volatile("st.shared.v4.u32 [%0], {%1, %2, %3, %4};" ::"r"(a), "r"(x), "r"(y), "r"(z), "r"(w) : "memory");
}
__device__ __forceinline__ void sts64f(uint32_t a, float x, float y) {
    asm volatile("st.shared.v2.f32 [%0], {%1, %2};" ::"r"(a), "f"(x), "f"(y) : "memory");
}
__device__ __forceinline__ float4 lds128f(uint32_t a) {
    float4 v;
    asm volatile("ld.shared.v4.f32 {%0, %1, %2, %3}, [%4];" : "=f"(v.x), "=f"(v.y), "=f"(v.z), "=f"(v.w) : "r"(a) : "memory");
    return v;
}
__device__ __forceinline__ uint32_t lds32(uint32_t a) {
    uint32_t v;
    asm volatile("ld.shared.u32 %0, [%1];" : "=r"(v) : "r"(a) : "memory");
    return v;
}
__device__ __forceinline__ void sts32(uint32_t a, uint32_t x) {
    asm volatile("st.shared.u32 [%0], %1;" ::"r"(a), "r"(x) : "memory");
}
__device__ __forceinline__ void stg128f(void* p, float a, float b, float c, float d) {
    asm volatile("st.global.v4.f32 [%0], {%1, %2, %3, %4};" ::"l"(p), "f"(a), "f"(b), "f"(c), "f"(d) : "memory");
}
__device__ __forceinline__ unsigned ld_relaxed32(const unsigned* p) {
    unsigned v;
    asm volatile("ld.relaxed.gpu.global.u32 %0, [%1];" : "=r"(v) : "l"(p) : "memory");
    return v;
}
__device__ __forceinline__ void wait_counter(const unsigned* p, unsigned target) {
    unsigned n = 0, v;
    while (true) {
        asm volatile("ld.acquire.gpu.global.u32 %0, [%1];" : "=r"(v) : "l"(p) : "memory");
        if ((int)(v - target) >= 0) break;
        if (++n > kSpinLimit) TRAP();
        __nanosleep(32);
    }
}
#define KT(IT, W) do { } while (0)
#define STAMP(cond, slot) do { } while (0)

template <int TA, int TB>
__device__ __forceinline__ void wgmma_n256(float (&d)[128], uint64_t da, uint64_t db, int keep) {
    asm volatile(
        "{\n.reg .pred p;\nsetp.ne.b32 p, %132, 0;\n"
        "wgmma.mma_async.sync.aligned.m64n256k16.f32.bf16.bf16 "
        "{%0, %1, %2, %3, %4, %5, %6, %7, %8, %9, %10, %11, %12, %13, %14, %15, "
        "%16, %17, %18, %19, %20, %21, %22, %23, %24, %25, %26, %27, %28, %29, %30, %31, "
        "%32, %33, %34, %35, %36, %37, %38, %39, %40, %41, %42, %43, %44, %45, %46, %47, "
        "%48, %49, %50, %51, %52, %53, %54, %55, %56, %57, %58, %59, %60, %61, %62, %63, "
        "%64, %65, %66, %67, %68, %69, %70, %71, %72, %73, %74, %75, %76, %77, %78, %79, "
        "%80, %81, %82, %83, %84, %85, %86, %87, %88, %89, %90, %91, %92, %93, %94, %95, "
        "%96, %97, %98, %99, %100, %101, %102, %103, %104, %105, %106, %107, %108, %109, %110, %111, "
        "%112, %113, %114, %115, %116, %117, %118, %119, %120, %121, %122, %123, %124, %125, %126, %127}, "
        "%128, %129, p, 1, 1, %130, %131;\n}\n"
        : "+f"(d[0]), "+f"(d[1]), "+f"(d[2]), "+f"(d[3]), "+f"(d[4]), "+f"(d[5]), "+f"(d[6]), "+f"(d[7]),
          "+f"(d[8]), "+f"(d[9]), "+f"(d[10]), "+f"(d[11]), "+f"(d[12]), "+f"(d[13]), "+f"(d[14]), "+f"(d[15]),
          "+f"(d[16]), "+f"(d[17]), "+f"(d[18]), "+f"(d[19]), "+f"(d[20]), "+f"(d[21]), "+f"(d[22]), "+f"(d[23]),
          "+f"(d[24]), "+f"(d[25]), "+f"(d[26]), "+f"(d[27]), "+f"(d[28]), "+f"(d[29]), "+f"(d[30]), "+f"(d[31]),
          "+f"(d[32]), "+f"(d[33]), "+f"(d[34]), "+f"(d[35]), "+f"(d[36]), "+f"(d[37]), "+f"(d[38]), "+f"(d[39]),
          "+f"(d[40]), "+f"(d[41]), "+f"(d[42]), "+f"(d[43]), "+f"(d[44]), "+f"(d[45]), "+f"(d[46]), "+f"(d[47]),
          "+f"(d[48]), "+f"(d[49]), "+f"(d[50]), "+f"(d[51]), "+f"(d[52]), "+f"(d[53]), "+f"(d[54]), "+f"(d[55]),
          "+f"(d[56]), "+f"(d[57]), "+f"(d[58]), "+f"(d[59]), "+f"(d[60]), "+f"(d[61]), "+f"(d[62]), "+f"(d[63]),
          "+f"(d[64]), "+f"(d[65]), "+f"(d[66]), "+f"(d[67]), "+f"(d[68]), "+f"(d[69]), "+f"(d[70]), "+f"(d[71]),
          "+f"(d[72]), "+f"(d[73]), "+f"(d[74]), "+f"(d[75]), "+f"(d[76]), "+f"(d[77]), "+f"(d[78]), "+f"(d[79]),
          "+f"(d[80]), "+f"(d[81]), "+f"(d[82]), "+f"(d[83]), "+f"(d[84]), "+f"(d[85]), "+f"(d[86]), "+f"(d[87]),
          "+f"(d[88]), "+f"(d[89]), "+f"(d[90]), "+f"(d[91]), "+f"(d[92]), "+f"(d[93]), "+f"(d[94]), "+f"(d[95]),
          "+f"(d[96]), "+f"(d[97]), "+f"(d[98]), "+f"(d[99]), "+f"(d[100]), "+f"(d[101]), "+f"(d[102]), "+f"(d[103]),
          "+f"(d[104]), "+f"(d[105]), "+f"(d[106]), "+f"(d[107]), "+f"(d[108]), "+f"(d[109]), "+f"(d[110]), "+f"(d[111]),
          "+f"(d[112]), "+f"(d[113]), "+f"(d[114]), "+f"(d[115]), "+f"(d[116]), "+f"(d[117]), "+f"(d[118]), "+f"(d[119]),
          "+f"(d[120]), "+f"(d[121]), "+f"(d[122]), "+f"(d[123]), "+f"(d[124]), "+f"(d[125]), "+f"(d[126]), "+f"(d[127])
        : "l"(da), "l"(db), "n"(TA), "n"(TB), "r"(keep));
}
template <int TA, int TB>
__device__ __forceinline__ void wgmma_n192(float (&d)[128], uint64_t da, uint64_t db, int keep) {
    asm volatile(
        "{\n.reg .pred p;\nsetp.ne.b32 p, %100, 0;\n"
        "wgmma.mma_async.sync.aligned.m64n192k16.f32.bf16.bf16 "
        "{%0, %1, %2, %3, %4, %5, %6, %7, %8, %9, %10, %11, %12, %13, %14, %15, "
        "%16, %17, %18, %19, %20, %21, %22, %23, %24, %25, %26, %27, %28, %29, %30, %31, "
        "%32, %33, %34, %35, %36, %37, %38, %39, %40, %41, %42, %43, %44, %45, %46, %47, "
        "%48, %49, %50, %51, %52, %53, %54, %55, %56, %57, %58, %59, %60, %61, %62, %63, "
        "%64, %65, %66, %67, %68, %69, %70, %71, %72, %73, %74, %75, %76, %77, %78, %79, "
        "%80, %81, %82, %83, %84, %85, %86, %87, %88, %89, %90, %91, %92, %93, %94, %95}, "
        "%96, %97, p, 1, 1, %98, %99;\n}\n"
        : "+f"(d[0]), "+f"(d[1]), "+f"(d[2]), "+f"(d[3]), "+f"(d[4]), "+f"(d[5]), "+f"(d[6]), "+f"(d[7]),
          "+f"(d[8]), "+f"(d[9]), "+f"(d[10]), "+f"(d[11]), "+f"(d[12]), "+f"(d[13]), "+f"(d[14]), "+f"(d[15]),
          "+f"(d[16]), "+f"(d[17]), "+f"(d[18]), "+f"(d[19]), "+f"(d[20]), "+f"(d[21]), "+f"(d[22]), "+f"(d[23]),
          "+f"(d[24]), "+f"(d[25]), "+f"(d[26]), "+f"(d[27]), "+f"(d[28]), "+f"(d[29]), "+f"(d[30]), "+f"(d[31]),
          "+f"(d[32]), "+f"(d[33]), "+f"(d[34]), "+f"(d[35]), "+f"(d[36]), "+f"(d[37]), "+f"(d[38]), "+f"(d[39]),
          "+f"(d[40]), "+f"(d[41]), "+f"(d[42]), "+f"(d[43]), "+f"(d[44]), "+f"(d[45]), "+f"(d[46]), "+f"(d[47]),
          "+f"(d[48]), "+f"(d[49]), "+f"(d[50]), "+f"(d[51]), "+f"(d[52]), "+f"(d[53]), "+f"(d[54]), "+f"(d[55]),
          "+f"(d[56]), "+f"(d[57]), "+f"(d[58]), "+f"(d[59]), "+f"(d[60]), "+f"(d[61]), "+f"(d[62]), "+f"(d[63]),
          "+f"(d[64]), "+f"(d[65]), "+f"(d[66]), "+f"(d[67]), "+f"(d[68]), "+f"(d[69]), "+f"(d[70]), "+f"(d[71]),
          "+f"(d[72]), "+f"(d[73]), "+f"(d[74]), "+f"(d[75]), "+f"(d[76]), "+f"(d[77]), "+f"(d[78]), "+f"(d[79]),
          "+f"(d[80]), "+f"(d[81]), "+f"(d[82]), "+f"(d[83]), "+f"(d[84]), "+f"(d[85]), "+f"(d[86]), "+f"(d[87]),
          "+f"(d[88]), "+f"(d[89]), "+f"(d[90]), "+f"(d[91]), "+f"(d[92]), "+f"(d[93]), "+f"(d[94]), "+f"(d[95])
        : "l"(da), "l"(db), "n"(TA), "n"(TB), "r"(keep));
}
template <int TA, int TB>
__device__ __forceinline__ void wgmma_n128(float (&d)[128], uint64_t da, uint64_t db, int keep) {
    asm volatile(
        "{\n.reg .pred p;\nsetp.ne.b32 p, %68, 0;\n"
        "wgmma.mma_async.sync.aligned.m64n128k16.f32.bf16.bf16 "
        "{%0, %1, %2, %3, %4, %5, %6, %7, %8, %9, %10, %11, %12, %13, %14, %15, "
        "%16, %17, %18, %19, %20, %21, %22, %23, %24, %25, %26, %27, %28, %29, %30, %31, "
        "%32, %33, %34, %35, %36, %37, %38, %39, %40, %41, %42, %43, %44, %45, %46, %47, "
        "%48, %49, %50, %51, %52, %53, %54, %55, %56, %57, %58, %59, %60, %61, %62, %63}, "
        "%64, %65, p, 1, 1, %66, %67;\n}\n"
        : "+f"(d[0]), "+f"(d[1]), "+f"(d[2]), "+f"(d[3]), "+f"(d[4]), "+f"(d[5]), "+f"(d[6]), "+f"(d[7]),
          "+f"(d[8]), "+f"(d[9]), "+f"(d[10]), "+f"(d[11]), "+f"(d[12]), "+f"(d[13]), "+f"(d[14]), "+f"(d[15]),
          "+f"(d[16]), "+f"(d[17]), "+f"(d[18]), "+f"(d[19]), "+f"(d[20]), "+f"(d[21]), "+f"(d[22]), "+f"(d[23]),
          "+f"(d[24]), "+f"(d[25]), "+f"(d[26]), "+f"(d[27]), "+f"(d[28]), "+f"(d[29]), "+f"(d[30]), "+f"(d[31]),
          "+f"(d[32]), "+f"(d[33]), "+f"(d[34]), "+f"(d[35]), "+f"(d[36]), "+f"(d[37]), "+f"(d[38]), "+f"(d[39]),
          "+f"(d[40]), "+f"(d[41]), "+f"(d[42]), "+f"(d[43]), "+f"(d[44]), "+f"(d[45]), "+f"(d[46]), "+f"(d[47]),
          "+f"(d[48]), "+f"(d[49]), "+f"(d[50]), "+f"(d[51]), "+f"(d[52]), "+f"(d[53]), "+f"(d[54]), "+f"(d[55]),
          "+f"(d[56]), "+f"(d[57]), "+f"(d[58]), "+f"(d[59]), "+f"(d[60]), "+f"(d[61]), "+f"(d[62]), "+f"(d[63])
        : "l"(da), "l"(db), "n"(TA), "n"(TB), "r"(keep));
}
__device__ __forceinline__ void wgmma_n128_rs(float (&d)[128], uint32_t a0, uint32_t a1, uint32_t a2, uint32_t a3, uint64_t db) {
    asm volatile(
        "{\n.reg .pred p;\nsetp.ne.b32 p, 1, 0;\n"
        "wgmma.mma_async.sync.aligned.m64n128k16.f32.bf16.bf16 "
        "{%0, %1, %2, %3, %4, %5, %6, %7, %8, %9, %10, %11, %12, %13, %14, %15, "
        "%16, %17, %18, %19, %20, %21, %22, %23, %24, %25, %26, %27, %28, %29, %30, %31, "
        "%32, %33, %34, %35, %36, %37, %38, %39, %40, %41, %42, %43, %44, %45, %46, %47, "
        "%48, %49, %50, %51, %52, %53, %54, %55, %56, %57, %58, %59, %60, %61, %62, %63}, "
        "{%64, %65, %66, %67}, %68, p, 1, 1, 1;\n}\n"
        : "+f"(d[0]), "+f"(d[1]), "+f"(d[2]), "+f"(d[3]), "+f"(d[4]), "+f"(d[5]), "+f"(d[6]), "+f"(d[7]),
          "+f"(d[8]), "+f"(d[9]), "+f"(d[10]), "+f"(d[11]), "+f"(d[12]), "+f"(d[13]), "+f"(d[14]), "+f"(d[15]),
          "+f"(d[16]), "+f"(d[17]), "+f"(d[18]), "+f"(d[19]), "+f"(d[20]), "+f"(d[21]), "+f"(d[22]), "+f"(d[23]),
          "+f"(d[24]), "+f"(d[25]), "+f"(d[26]), "+f"(d[27]), "+f"(d[28]), "+f"(d[29]), "+f"(d[30]), "+f"(d[31]),
          "+f"(d[32]), "+f"(d[33]), "+f"(d[34]), "+f"(d[35]), "+f"(d[36]), "+f"(d[37]), "+f"(d[38]), "+f"(d[39]),
          "+f"(d[40]), "+f"(d[41]), "+f"(d[42]), "+f"(d[43]), "+f"(d[44]), "+f"(d[45]), "+f"(d[46]), "+f"(d[47]),
          "+f"(d[48]), "+f"(d[49]), "+f"(d[50]), "+f"(d[51]), "+f"(d[52]), "+f"(d[53]), "+f"(d[54]), "+f"(d[55]),
          "+f"(d[56]), "+f"(d[57]), "+f"(d[58]), "+f"(d[59]), "+f"(d[60]), "+f"(d[61]), "+f"(d[62]), "+f"(d[63])
        : "r"(a0), "r"(a1), "r"(a2), "r"(a3), "l"(db));
}

constexpr uint64_t kDescHi = (uint64_t)(64u | 0x40000000u) << 32;
template <int MODE>
__device__ __forceinline__ void mma_kblock(float (&acc)[128], uint32_t a_lo, uint32_t b_lo, int keep) {
    constexpr uint32_t HALF = (MODE == 1) ? 12288u : 16384u;
    constexpr bool BN = (MODE == 1 || MODE == 2 || MODE == 4);
#pragma unroll
    for (int kk = 0; kk < 4; ++kk) {
        const uint32_t ao = (MODE == 3) ? kk * 2048u : kk * 32u;
        const uint32_t bo = BN ? ((kk >> 1) * HALF + (kk & 1) * 2048u) : kk * 32u;
        const uint64_t da = kDescHi | (uint64_t)(a_lo + (ao >> 4) + (1u << 16));
        const uint64_t db = kDescHi | (uint64_t)(b_lo + (bo >> 4) + (BN ? (256u << 16) : (1u << 16)));
        if (MODE == 1) wgmma_n192<0, 1>(acc, da, db, kk == 0 ? keep : 1);
        else if (MODE == 4) wgmma_n128<0, 1>(acc, da, db, 1);
        else wgmma_n256<(MODE == 3), BN>(acc, da, db, kk == 0 ? keep : 1);
    }
}

struct Params {
    Scratch* s;
    const __nv_bfloat16* x;
    const __nv_bfloat16* b_re;
    const __nv_bfloat16* b_im;
    const __nv_bfloat16* gate_w;
    const __nv_bfloat16* lam_re;
    const __nv_bfloat16* lam_im;
    const __nv_bfloat16* log_dt;
    const __nv_bfloat16* dskip;
    const __nv_bfloat16* b1;
    const __nv_bfloat16* b2;
    float* out;
    int swap;
};

#define CMUL(rr, ri, ar, ai, br, bi) do { float _r = (ar) * (br) - (ai) * (bi); float _i = (ar) * (bi) + (ai) * (br); rr = _r; ri = _i; } while (0)
#define CFMA(rr, ri, ar, ai, br, bi) do { float _r = fmaf(-(ai), (bi), fmaf((ar), (br), rr)); float _i = fmaf((ai), (br), fmaf((ar), (bi), ri)); rr = _r; ri = _i; } while (0)

#define KB_OPEN(IT, LAST)                                                                        \
    KT(IT, 0);                                                                                   \
    if (ORDER && (LAST) && wg == 1) bar_sync(7, 256);                                            \
    mbar_wait(bar_full + 8 * ((IT) & 3), ((IT) >> 2) & 1);                                \
    KT(IT, 1);
#define KB_CLOSE(IT, LAST, REL)                                                                  \
    if (ORDER && (LAST) && wg == 0) bar_arrive(7, 256);                                          \
    wgmma_wait<1>();                                                                             \
    if (lane < 2 && (REL)) mbar_arrive_cluster(rel_addr + 8 * (((IT) - 1) & 3));
#define KBLOCK(MODE, IT, FIRST, LAST)                                                            \
    {                                                                                            \
        const uint32_t so = ((IT) & 3) * (kStageBytes >> 4);                                     \
        KB_OPEN(IT, LAST);                                                                       \
        wgmma_fence();                                                                           \
        mma_kblock<MODE>(acc, a_lo + so, b_lo + so, !(FIRST));                                   \
        wgmma_commit();                                                                          \
        KB_CLOSE(IT, LAST, !(FIRST));                                                            \
    }
#define TILE_END() do { wgmma_wait<0>(); if (lane < 2) mbar_arrive_cluster(rel_addr + 24); } while (0)

__global__ void __cluster_dims__(2, 1, 1) __launch_bounds__(384, 1)
fused_kernel(const __grid_constant__ CUtensorMap mB, const __grid_constant__ CUtensorMap mXs, const __grid_constant__ CUtensorMap mXf,
             const __grid_constant__ CUtensorMap mW1b, const __grid_constant__ CUtensorMap mW1a, const __grid_constant__ CUtensorMap mHs,
             const __grid_constant__ CUtensorMap mHf, const __grid_constant__ CUtensorMap mCre, const __grid_constant__ CUtensorMap mCim,
             const __grid_constant__ CUtensorMap mW2, const __grid_constant__ CUtensorMap mW2n, const Params p) {
    extern __shared__ __align__(1024) uint8_t smem_raw[];
    const uint32_t sbase = smem_u32(smem_raw);
    if ((sbase & 0x3ffffu) != kSmemOrg) return;
    const uint32_t bar_full = sbase + kBarOff, bar_empty = bar_full + 32, bar_dep = bar_full + 64;
    const uint32_t bar_x = bar_full + 88, bar_c = bar_full + 96, role_s = bar_full + 104, tag_s = bar_full + 112 + (threadIdx.x & 1) * 4;

    const int tid = threadIdx.x, lane = tid & 31;
    const int warp = __shfl_sync(0xffffffffu, tid >> 5, 0);
    const uint32_t rank = blockIdx.x & 1;

    int pref;
    {
        unsigned smid;
        asm("mov.u32 %0, %%smid;" : "=r"(smid));
        const int t = smid >> 1, u = t - 32, d = (u * 37) >> 8;
        pref = (t < 32) ? (t & 7) * 8 + (t >> 3) : (t < 60) ? (1 + u - 7 * d) * 8 + 4 + d : ((t - 58) & 7);
    }
#define FIRST_FILL(ROLE)                                                                     \
    {                                                                                        \
        mbar_expect_tx(bar_full, 49152);                                                     \
        tma4(sbase, &mB, bar_full, 0, 0, 0, (((ROLE) & 7) * 2 + (int)rank) * 8);             \
        tma5(sbase + kABytes, &mXs, bar_full, 0, 0, 0, 0, (ROLE) >> 3);                      \
        tma5(sbase + kABytes + 16384, &mXs, bar_full, 0, 0, 0, 16, (ROLE) >> 3);             \
    }
    STAMP(tid == 0, 0);
    if (warp < 2) {
        if (elect_one()) {
            if (warp & 1) {
                if (rank == 0) {
                    int role = pref;
                    unsigned taken = atom_exch(&p.s->claim[pref], 1u);
#pragma unroll 1
                    for (int i = 0; taken != 0 && i < 64; ++i) { role = i; taken = atom_exch(&p.s->claim[i], 1u); }
                    sts32(role_s, role);
                    asm volatile("fence.acq_rel.cluster;" ::: "memory");
                }
            } else {
                prefetch_map(&mB); prefetch_map(&mXs);
#pragma unroll
                for (int s = 0; s < kStages; ++s) {
                    mbar_init(bar_full + 8 * s, 1);
                    mbar_init(bar_empty + 8 * s, 16);
                    mbar_init(bar_dep + 8 * s, 1);
                }
                mbar_init(bar_c, 96);
                asm volatile("fence.mbarrier_init.release.cluster;\nfence.proxy.async.shared::cta;" ::: "memory");
                FIRST_FILL(pref);
                mbar_expect_tx(bar_x, 2048);
                bulk_load(sbase + kXOff, p.gate_w, 2048, bar_x);
            }
        }
    } else if (warp < 2 + PF0LINES) {
        const int row = blockIdx.x * 32 + lane;
        const __nv_bfloat16* src = (row < 2048) ? p.x : (row < 3072) ? p.b_re - 2048 * kD : p.b_im - 3072 * kD;
        asm volatile("prefetch.global.L2 [%0];" ::"l"(src + row * kD + (warp - 2) * 64) : "memory");
    }
    __syncwarp();
    cluster_arrive();
    cluster_wait();
    const int role = __shfl_sync(0xffffffffu, (int)lds32_cluster(mapa(role_s, 0)), 0);
    if (__builtin_expect(role != pref, 0)) {
        if (warp == 0 && elect_one()) {
            mbar_wait(bar_full, 0);
            asm volatile("mbarrier.inval.shared::cta.b64 [%0];" ::"r"(bar_full) : "memory");
            mbar_init(bar_full, 1);
            asm volatile("fence.mbarrier_init.release.cluster;\nfence.proxy.async.shared::cta;" ::: "memory");
            FIRST_FILL(role);
        }
        __syncwarp();
        bar_sync(0, 384);
    }
    const int c = role >> 3;
    const int j8 = role & 7;
    const int cb = j8 * 2 + (int)rank;
    const int rb = 2 * c + (int)rank;
    const int kh = j8 >> 2;
    const int colK = (j8 & 3) * 256 + kh * 128, colS = colK ^ 128;

    if (warp >= 8) {
        asm volatile("setmaxnreg.dec.sync.aligned.u32 24;");
        if (warp > 8) {
            if (warp == 11) {
                if (lane < 9) prefetch_map(&mXf + lane);
#pragma unroll 1
                for (int en = lane; en < 88; en += 32) {
                    const int J = en >> 2;
                    const __nv_bfloat16* src = ((J < 14) ? p.b1 : (J < 18) ? p.dskip : p.b2) + 32 * J + 2 * (en & 3) +
                                               ((J < 6) ? 2048 + 192 * j8 : (J < 14) ? 256 * j8 - 192 : colK - ((J < 18) ? 448 : 576));
                    sts128(sbase + kBiasOff + en * 16, ldg32(src), ldg32(src + 8), ldg32(src + 16), ldg32(src + 24));
                }
                mbar_arrive_local(bar_c);
            } else {
                {
                    sts32(tag_s, ld_relaxed32(&p.s->epoch) + 1);
                    const int ch = cb * 64 + (tid - 288);
                    const uint32_t t_s = sbase + kTabOff + (tid - 288) * 64;
                    const float Lr = bf_lo(ldg16(p.lam_re + ch)), Li = bf_lo(ldg16(p.lam_im + ch));
                    const float dt = bf16_round(expf(bf_lo(ldg16(p.log_dt + ch))));
                    const float ea = expf(dt * Lr);
                    float lr, li;
                    sincospif((dt * Li) * 0.31830988618379067f, &li, &lr);
                    lr *= ea; li *= ea;
                    const float nr = lr - 1.0f, ni = li;
                    const bool big = fabsf(Lr) >= fabsf(Li);
                    const float u = big ? Lr : Li, v = big ? Li : Lr;
                    const float t = v / u, d = 2.0f / fmaf(v, t, u);
                    const float cr = (big ? fmaf(ni, t, nr) : fmaf(nr, t, ni)) * d, ci = (big ? fmaf(-nr, t, ni) : fmaf(ni, t, -nr)) * d;
                    if (p.swap) li = -li;
                    const float m00 = p.swap ? -ci : cr, m01 = p.swap ? cr : -ci, m10 = p.swap ? -cr : -ci, m11 = p.swap ? -ci : -cr;
#pragma unroll
                    for (int q = 0; q < 4; ++q) {
                        sts128f(t_s + q * 16, lr, li, m00, m01);
                        sts128f(t_s + 12288 + q * 16, 0.f, 0.f, 0.f, 0.f);
                    }
#pragma unroll 1
                    for (int i = 0; i < 6; ++i) CMUL(lr, li, lr, li, lr, li);
                    float ar, ai, br, bi;
                    CMUL(ar, ai, lr, li, lr, li);
                    CMUL(br, bi, ar, ai, lr, li);
                    sts128f(t_s + 4096, m10, m11, 0.f, 0.f);
#pragma unroll
                    for (int q = 1; q < 4; ++q) sts128f(t_s + 4096 + q * 16, m10, m11, lr, li);
                    sts128f(t_s + 8192, 0.f, 0.f, 1.f, 0.f);
                    sts128f(t_s + 8192 + 16, 0.f, 0.f, lr, li);
                    sts128f(t_s + 8192 + 32, ar, ai, ar, ai);
                    sts128f(t_s + 8192 + 48, ar, ai, br, bi);
                    CMUL(ar, ai, ar, ai, ar, ai);
                    br = 1.f; bi = 0.f;
#pragma unroll 1
                    for (int k = c - 1; k >= 0; --k) {
                        sts64f(t_s + 12288 + (k & 3) * 16 + (k >> 2) * 8, br, bi);
                        CMUL(br, bi, br, bi, ar, ai);
                    }
                    mbar_arrive_local(bar_c);
                }
                if (warp == 9) {
#pragma unroll 1
                    for (int ev = 0; ev < 3; ++ev) {
                        bar_sync(3 + ev, 288);
                        if (lane == 0) {
                            unsigned* cnt = &p.s->cnt[(ev == 0 ? c : 16 * ev - 8 + rb) * 32];
                            asm volatile("fence.acq_rel.gpu;\nfence.proxy.async.global;" ::: "memory");
                            asm volatile("red.relaxed.gpu.global.add.u32 [%0], 1;" ::"l"(cnt) : "memory");
                        }
                        __syncwarp();
                    }
                } else if (lane == 0) {
                    const unsigned tag = lds32(tag_s);
#pragma unroll 1
                    for (int ev = 0; ev < 3; ++ev) {
                        wait_counter(&p.s->cnt[(ev == 0 ? c : 16 * ev - 8 + rb) * 32], tag * (ev == 0 ? 16u : 8u));
                        mbar_arrive_local(bar_dep + 8 * ev);
                        if (ev == 0 && atomicInc(&p.s->done, 127u) == 127u) {
                            st_relaxed32(&p.s->epoch, tag);
#pragma unroll 1
                            for (int i = 0; i < 64; i += 4) stg128(&p.s->claim[i], 0, 0, 0, 0);
                        }
                    }
                }
            }
        } else if (elect_one()) {
            int it = 1;
#define ACQUIRE(BYTES)                                                   \
    const uint32_t st = sbase + (it & 3) * kStageBytes, fb = bar_full + 8 * (it & 3); \
    mbar_wait(bar_empty + 8 * (it & 3), ((it >> 2) & 1) ^ 1);     \
    mbar_expect_tx(fb, BYTES);
#pragma unroll 1
            for (; it < 16; ++it) {
                ACQUIRE(49152);
                tma4(st, &mB, fb, it * 64, 0, 0, cb * 8);
                tma5_mc(st + kABytes + rank * 16384, &mXs, fb, it * 64, 0, 0, rank * 16, c);
            }
#pragma unroll 1
            for (; it < 48; ++it) {
                const bool t1 = it < 32;
                const int k0 = (it & 15) * 64;
                ACQUIRE(t1 ? 40960 : 49152);
                tma5(st, &mXf, fb, k0, 0, 0, rank * 4, c);
                tma3_mc(st + kABytes + rank * (t1 ? 12288 : 16384), t1 ? &mW1b : &mW1a, fb, 0, k0 + rank * 32, t1 ? 32 + 3 * j8 : 4 * j8);
                if ((it & ~2) == XLDKB) {
                    const int h = (it >> 1) & 1;
                    if (h == 0) mbar_expect_tx(bar_x, 32768);
                    tma5(sbase + kXOff + h * 16384, &mXf, bar_x, colK + h * 64, 0, 0, rank * 4, c);
                }
            }
            STAMP(true, 8);
            mbar_wait(bar_dep, 0);
            asm volatile("fence.proxy.async.global;" ::: "memory");
            STAMP(true, 9);
#pragma unroll 1
            for (; it < 64; ++it) {
                const int k0 = (it & 15) * 64;
                ACQUIRE(49152);
                tma3(st, &mHs, fb, 0, kh * 1024 + k0, rb * 2);
                tma2_mc(st + kABytes + rank * 16384, kh ? &mCim : &mCre, fb, k0, rank ? colS : colK);
            }
            int f0 = 2048 + 768 * kh;
#pragma unroll 1
            for (; it < kTotal; ++it, f0 += 64) {
                if (it == 64 || it == 76) {
                    mbar_wait(bar_dep + (it == 64 ? 8 : 16), 0);
                    asm volatile("fence.proxy.async.global;" ::: "memory");
                    if (it == 76) f0 = 1024 * kh;
                }
                if (f0 == 256 * j8) f0 += 256;
                if (it == 88) f0 = 256 * (j8 ^ 4);
                ACQUIRE(49152);
                tma2(st, &mHf, fb, f0, rb * 128);
                tma5_mc(st + kABytes + rank * 16384, &mW2, fb, 0, 0, (f0 >> 3) + 4 * rank, 0, colK >> 6);
                if (it < 88) tma5_mc(st + kABytes + rank * 16384 + 8192, &mW2, fb, 0, 0, (f0 >> 3) + 4 * rank, 0, colS >> 6);
                else tma3_mc(st + kABytes + rank * 16384 + 8192, &mW2n, fb, 0, (f0 ^ 1024) + 32 * rank, colK >> 6);
            }
        }
    } else {
        asm volatile("setmaxnreg.inc.sync.aligned.u32 240;");
        const int wg = warp >> 2, w = warp & 3, r = lane >> 2, q = lane & 3, tw = tid & 127;
        uint32_t a_lo = (kSmemOrg + wg * 8192) >> 4;
        constexpr uint32_t b_lo = (kSmemOrg + kABytes) >> 4;
        const uint32_t rel_addr = mapa(bar_empty, (uint32_t)(lane & 1));
        const uint32_t gate_s = sbase + kGateOff;
        float acc[128];
        uint32_t pk[64];
        unsigned tag;
        UNDEF_R(tag);

#pragma unroll
        for (int i = 0; i < 128; ++i) UNDEF_F(acc[i]);
        {
            const uint32_t gx_s = sbase + kABytes + (16 * cb + 2 * warp + (lane >> 4)) * 128 +
                                  ((((lane & 15) >> 1) ^ (2 * w + (lane >> 4))) << 4) + (lane & 1) * 8;
            const uint32_t gw_s = sbase + kXOff + (lane & 15) * 8;
            float gs = 0.f;
            mbar_wait(bar_x, 0);
#pragma unroll 1
            for (uint32_t it = 0; it < 16; ++it) {
                KBLOCK(0, it, it == 0, it == 15);
                STAMP(tid == 0 && it == 0, 1);
                const uint2 xa = lds64(gx_s + (it & 3) * kStageBytes), wa = lds64(gw_s + it * 128);
                const uint32_t pa = bf2_mul(xa.x, wa.x), pb = bf2_mul(xa.y, wa.y);
                gs += (bf_lo(pa) + bf_hi(pa)) + (bf_lo(pb) + bf_hi(pb));
            }
            mbar_wait(bar_c, 0);
            tag = lds32(tag_s);
#pragma unroll
            for (int o = 8; o > 0; o >>= 1) gs += __shfl_xor_sync(0xffffffffu, gs, o);
            const float g = bf16_round(__frcp_rn(1.0f + expf(-bf16_round(gs))));
            if ((lane & 15) == 0) st_relaxed64(&p.s->gate[c * 256 + (lane >> 4) + 64 * w + 4 * cb + 2 * wg], __float_as_uint(g), tag);
        }
        const uint32_t tab_s = sbase + kTabOff + tid * 16;
        const float4 k0 = lds128f(tab_s);
        TILE_END();
        STAMP(tid == 0, 2);
#pragma unroll
        for (int s = 0; s < 64; ++s) pk[s] = pack_bf16_v(acc[4 * (s >> 1) + (s & 1)], acc[4 * (s >> 1) + 2 + (s & 1)]);
#pragma unroll
        for (int i = 0; i < 96; ++i) UNDEF_F(acc[i]);

        const float lr = k0.x, li = k0.y, m00 = k0.z, m01 = k0.w;
        float m10, m11, hr = 0.f, hi = 0.f;
        uint32_t gg[4], orr[4], oii[4];
        const int ch = cb * 64 + warp * 8 + r;
        __nv_bfloat16* hs = p.s->Hs + (size_t)ch * 2048 + c * 256 + q * 8;
#define PASS2(KB)                                                                                      \
    _Pragma("unroll") for (int s = 0; s < 64; s += 2) {                                                \
        if (pass2_kb(s) != (KB)) continue;                                                             \
        if ((s & 7) == 0) {                                                                            \
            const uint4 ga = lds128(gate_s + (q * 72 + s) * 2);                                        \
            gg[0] = ga.x; gg[1] = ga.y; gg[2] = ga.z; gg[3] = ga.w;                                    \
        }                                                                                              \
        float o0[2], o1[2];                                                                            \
        _Pragma("unroll") for (int k = 0; k < 2; ++k) {                                                \
            PIN_R(pk[s + k]);                                                                          \
            float nr = bf_lo(pk[s + k]), ni = bf_hi(pk[s + k]);                                        \
            CFMA(nr, ni, lr, li, hr, hi);                                                              \
            hr = nr; hi = ni;                                                                          \
            o0[k] = fmaf(m00, hr, m01 * hi);                                                           \
            o1[k] = fmaf(m10, hr, m11 * hi);                                                           \
        }                                                                                              \
        orr[(s >> 1) & 3] = bf2_mul(pack_bf16(o0[0], o0[1]), gg[(s >> 1) & 3]);                        \
        oii[(s >> 1) & 3] = bf2_mul(pack_bf16(o1[0], o1[1]), gg[(s >> 1) & 3]);                        \
        if ((s & 7) == 6) {                                                                            \
            stg128(hs + 32 * (s >> 3), orr[0], orr[1], orr[2], orr[3]);                                \
            stg128(hs + 1024 * 2048 + 32 * (s >> 3), oii[0], oii[1], oii[2], oii[3]);                  \
        }                                                                                              \
    }                                                                                                  \
    PIN_F(hr); PIN_F(hi);
        {
            uint4 av0, av1, gv;
            float lqr, lqi;
#pragma unroll
            for (int kb = 0; kb < 16; ++kb) {
                PIN_R(a_lo);
                KBLOCK(1, 16 + kb, kb == 0, kb == 15);
                if (kb < 4) {
#pragma unroll
                    for (int s = kb * 16; s < kb * 16 + 16; ++s) {
                        float nr = bf_lo(pk[s]), ni = bf_hi(pk[s]);
                        CFMA(nr, ni, lr, li, hr, hi);
                        hr = nr; hi = ni;
                    }
                    PIN_F(hr); PIN_F(hi);
                }
                if (kb == 2) gv = ld_relaxed2x64(&p.s->gate[c * 256 + 2 * tw]);
                if (kb == 3) {
                    const float4 k1 = lds128f(tab_s + 4096), k2 = lds128f(tab_s + 8192);
                    m10 = k1.x; m11 = k1.y; lqr = k2.z; lqi = k2.w;
                    float tr = __shfl_up_sync(0xffffffffu, hr, 1, 4), ti = __shfl_up_sync(0xffffffffu, hi, 1, 4);
                    if (q >= 1) CFMA(hr, hi, k1.z, k1.w, tr, ti);
                    tr = __shfl_up_sync(0xffffffffu, hr, 2, 4); ti = __shfl_up_sync(0xffffffffu, hi, 2, 4);
                    if (q >= 2) CFMA(hr, hi, k2.x, k2.y, tr, ti);
                    if (q == 3) st_relaxed2x64(&p.s->agg[c * 1024 + ch], __float_as_uint(hr), tag, __float_as_uint(hi), tag);
                    tr = __shfl_up_sync(0xffffffffu, hr, 1, 4); ti = __shfl_up_sync(0xffffffffu, hi, 1, 4);
                    hr = (q >= 1) ? tr : 0.f; hi = (q >= 1) ? ti : 0.f;
                }
                if (kb == 4) {
                    unsigned spins = 0;
                    while (__any_sync(0xffffffffu, gv.y != tag || gv.w != tag)) {
                        if (++spins > kSpinLimit) break;
                        gv = ld_relaxed2x64(&p.s->gate[c * 256 + 2 * tw]);
                    }
                    sts32(gate_s + ((tw >> 5) * 72 + 2 * lane) * 2, __byte_perm(gv.x, gv.z, 0x7632));
                }
                if (kb == 5) {
                    av0 = make_uint4(0, tag, 0, tag); av1 = av0;
                    if (q < c) av0 = ld_relaxed2x64(&p.s->agg[q * 1024 + ch]);
                    if (q + 4 < c) av1 = ld_relaxed2x64(&p.s->agg[(q + 4) * 1024 + ch]);
                    bar_sync(1 + wg, 128);
                }
                if (kb == 6) {
                    const float4 k3 = lds128f(tab_s + 12288);
                    unsigned spins = 0;
                    while (__any_sync(0xffffffffu, av0.y != tag || av0.w != tag || av1.y != tag || av1.w != tag)) {
                        if (++spins > kSpinLimit) break;
                        if (q < c) av0 = ld_relaxed2x64(&p.s->agg[q * 1024 + ch]);
                        if (q + 4 < c) av1 = ld_relaxed2x64(&p.s->agg[(q + 4) * 1024 + ch]);
                    }
                    float vr, vi;
                    CMUL(vr, vi, k3.x, k3.y, __uint_as_float(av0.x), __uint_as_float(av0.z));
                    CFMA(vr, vi, k3.z, k3.w, __uint_as_float(av1.x), __uint_as_float(av1.z));
                    vr += __shfl_xor_sync(0xffffffffu, vr, 1); vi += __shfl_xor_sync(0xffffffffu, vi, 1);
                    vr += __shfl_xor_sync(0xffffffffu, vr, 2); vi += __shfl_xor_sync(0xffffffffu, vi, 2);
                    CFMA(hr, hi, lqr, lqi, vr, vi);
                }
                if (kb >= 6) { PASS2(kb); }
            }
            TILE_END();
        }
        STAMP(tid == 0, 3);
#pragma unroll
        for (int i = 0; i < 48; ++i) pk[i] = pack_bf16_v(acc[2 * i], acc[2 * i + 1]);
#pragma unroll
        for (int i = 0; i < 128; ++i) UNDEF_F(acc[i]);

        PIN_R(a_lo);
        KBLOCK(2, 32, true, false);
        PASS2(16);
        PIN_R(a_lo);
        KBLOCK(2, 33, false, false);
        PASS2(17);
        bar_arrive(3, 288);
        const uint32_t gate_row = gate_s + ((2 * (w & 1)) * 72 + 8 * (4 * rank + 2 * wg + (w >> 1)) + r) * 2;
        uint32_t om0, om1;
        {
            const float a = 1.0f - bf_lo(lds16(gate_row)), b = 1.0f - bf_lo(lds16(gate_row + 72 * 2));
            om0 = pack_bf16(a, a); om1 = pack_bf16(b, b);
        }
        __nv_bfloat16* hf = p.s->Hf + (size_t)(rb * 128 + wg * 64 + w * 16 + r) * kF + q * 8 + 2048 + 192 * j8;
        uint32_t bias_s = sbase + kBiasOff + q * 16;
#define FFN_SLICE(J)                                                                                   \
    {                                                                                                  \
        const uint4 bv = lds128(bias_s + (J) * 64);                                                    \
        const uint32_t bb[4] = {bv.x, bv.y, bv.z, bv.w};                                               \
        _Pragma("unroll") for (int jj = 0; jj < 4; ++jj) {                                             \
            const uint32_t r0 = bf2_add_relu(pk[8 * (J) + 2 * jj], bb[jj]), r1 = bf2_add_relu(pk[8 * (J) + 2 * jj + 1], bb[jj]); \
            pk[8 * (J) + 2 * jj] = bf2_mul(bf2_mul(r0, r0), om0);                                      \
            pk[8 * (J) + 2 * jj + 1] = bf2_mul(bf2_mul(r1, r1), om1);                                  \
        }                                                                                              \
        stg128(hf + 32 * (J), pk[8 * (J)], pk[8 * (J) + 2], pk[8 * (J) + 4], pk[8 * (J) + 6]);         \
        stg128(hf + 8 * kF + 32 * (J), pk[8 * (J) + 1], pk[8 * (J) + 3], pk[8 * (J) + 5], pk[8 * (J) + 7]); \
    }
        const uint32_t x_s = sbase + kXOff + (wg * 64 + w * 16 + (lane & 15)) * 128 + (((lane >> 4) ^ (lane & 7)) << 4);
        {
            uint32_t j = 0, nsl = 6;
#pragma unroll 1
            for (uint32_t it = 34; it < 88; ++it, ++j) {
                const uint32_t so = (it & 3) * (kStageBytes >> 4);
                if (wg == 1 && (it == 86 || (ORDER && it == 47))) bar_sync(7, 256);
                KB_OPEN(it, false);
                if ((it & ~15u) == 48) {
                    wgmma_fence();
                    mma_kblock<3>(acc, a_lo + so, b_lo + so, it != 48);
                    wgmma_commit();
                } else {
                    wgmma_fence();
                    mma_kblock<2>(acc, a_lo + so, b_lo + so, 1);
                    wgmma_commit();
                }
                if (wg == 0 && (it == 87 || (ORDER && it == 47))) bar_arrive(7, 256);
                KB_CLOSE(it, false, it != 48);
                if (j < nsl) {
                    if (j & 4) {
                        if (j & 2) { if (j & 1) FFN_SLICE(7) else FFN_SLICE(6) } else { if (j & 1) FFN_SLICE(5) else FFN_SLICE(4) }
                    } else {
                        if (j & 2) { if (j & 1) FFN_SLICE(3) else FFN_SLICE(2) } else { if (j & 1) FFN_SLICE(1) else FFN_SLICE(0) }
                    }
                    if (j + 1 == nsl) bar_arrive(1 + (nsl >> 1), 288);
                } else if (it == 47) {
                    hf += 64 * j8 - 2048;
                    bias_s += 6 * 64;
                    j = -1; nsl = 8;
                    TILE_END();
                    STAMP(tid == 0, 4);
#pragma unroll
                    for (int i = 0; i < 64; ++i) pk[i] = pack_bf16_v(acc[2 * i], acc[2 * i + 1]);
                } else if ((it >> 2) == ETKB / 4) {
                    mbar_wait(bar_x, 1);
                    const uint32_t xa_s = (x_s ^ ((it & 1) << 6)) + (it & 2) * 8192;
                    const float g0 = bf_lo(lds16(gate_row)), g1 = bf_lo(lds16(gate_row + 72 * 2));
                    const float o0f = bf_lo(om0), o1f = bf_lo(om1);
                    const uint4 dq = lds128(bias_s + (8 + (it & 3)) * 64), bq = lds128(bias_s + (12 + (it & 3)) * 64);
                    const uint4 xa = ldsm4(xa_s), xb = ldsm4(xa_s ^ 32);
                    const uint32_t dv[4] = {dq.x, dq.y, dq.z, dq.w}, bv2[4] = {bq.x, bq.y, bq.z, bq.w};
                    uint32_t xv[8] = {xa.x, xa.y, xa.z, xa.w, xb.x, xb.y, xb.z, xb.w};
#pragma unroll
                    for (int jj = 0; jj < 4; ++jj) {
                        const uint32_t x0 = bf2_mul(xv[2 * jj], dv[jj]), x1 = bf2_mul(xv[2 * jj + 1], dv[jj]);
                        const float bl = bf_lo(bv2[jj]), bh = bf_hi(bv2[jj]);
                        xv[2 * jj] = pack_bf16(fmaf(g0, bf_lo(x0), o0f * bl), fmaf(g0, bf_hi(x0), o0f * bh));
                        xv[2 * jj + 1] = pack_bf16(fmaf(g1, bf_lo(x1), o1f * bl), fmaf(g1, bf_hi(x1), o1f * bh));
                    }
                    sts128(xa_s, xv[0], xv[1], xv[2], xv[3]);
                    sts128(xa_s ^ 32, xv[4], xv[5], xv[6], xv[7]);
                }
            }
        }
        TILE_END();
        {
            uint8_t* xo = p.s->X + (size_t)(role * 2 + rank) * kXBytes + tid * 16;
            const uint8_t* xi = xo + (kh ? -8 * kXBytes : 8 * kXBytes);
            uint4 rx[8];
            uint32_t rs;
#define RXLOAD()                                                                                       \
    {                                                                                                  \
        rs = ld_relaxed32((const unsigned*)(xi + 32768 - tid * 12));                                   \
        _Pragma("unroll") for (int u = 0; u < 8; ++u) rx[u] = ld_relaxed2x64(xi + u * 4096);           \
    }
            {
                STAMP(tid == 0, 15);
                float m[4] = {0.f, 0.f, 0.f, 0.f};
#pragma unroll
                for (int i = 64; i < 128; ++i) m[i & 3] = fmaxf(m[i & 3], fabsf(acc[i]));
                const uint32_t eb = max(__float_as_uint(fmaxf(fmaxf(m[0], m[1]), fmaxf(m[2], m[3]))) >> 23, 15u);
                const float xsc = __uint_as_float((268u - eb) << 23);
                st_relaxed32(xo + 32768 - tid * 12, lop3<0xd8>((eb - 14u) << 23, tag, 1));
#pragma unroll
                for (int u = 0; u < 8; ++u) {
                    const int v = 64 + 8 * u;
                    st_relaxed2x64(xo + u * 4096, lop3<0xd8>(pack_f16(acc[v] * xsc, acc[v + 1] * xsc), tag, 1), pack_f16(acc[v + 2] * xsc, acc[v + 3] * xsc),
                                   lop3<0xd8>(pack_f16(acc[v + 4] * xsc, acc[v + 5] * xsc), tag, 1), pack_f16(acc[v + 6] * xsc, acc[v + 7] * xsc));
                }
                STAMP(tid == 0, 12);
            }
            if (wg == 1) bar_sync(7, 256);
#pragma unroll
            for (int t = 0; t < 4; ++t) {
                PIN_R(a_lo);
                KB_OPEN(88 + t, false);
                if (t == RXT) RXLOAD();
                wgmma_fence();
                mma_kblock<4>(acc, a_lo + t * (kStageBytes >> 4), b_lo + t * (kStageBytes >> 4), 1);
#pragma unroll
                for (int kk = 0; kk < 4; ++kk)
                    wgmma_n128_rs(acc, pk[16 * t + 4 * kk], pk[16 * t + 4 * kk + 1], pk[16 * t + 4 * kk + 2], pk[16 * t + 4 * kk + 3],
                                  kDescHi | (uint64_t)(b_lo + ((t * kStageBytes + 8192 + (kk >> 1) * 16384 + (kk & 1) * 2048) >> 4) + (256u << 16)));
                wgmma_commit();
            }
            if (wg == 0) bar_arrive(7, 256);
            unsigned spins = 0;
            mbar_wait(bar_x, 1);
#pragma unroll 1
            while (true) {
                uint32_t bad = rs ^ tag;
#pragma unroll
                for (int u = 0; u < 8; u += 2) bad = lop3<0xfe>(bad, lop3<0x7e>(rx[u].x, rx[u].z, tag), lop3<0x7e>(rx[u + 1].x, rx[u + 1].z, tag));
                if (!__any_sync(0xffffffffu, bad & 1) || ++spins > kSpinLimit) break;
                RXLOAD();
                RESPIN();
            }
            STAMP(tid == 0, 13);
            const float xsc = __uint_as_float(rs & ~1u);
#pragma unroll
            for (int u = 0; u < 8; ++u) {
                const uint4 ev = lds128((x_s ^ ((u & 3) << 5)) + (u >> 2) * 16384);
                const uint32_t rr[4] = {rx[u].x, rx[u].y, rx[u].z, rx[u].w}, ee[4] = {ev.x, ev.y, ev.z, ev.w};
#pragma unroll
                for (int k = 0; k < 4; ++k) {
                    const int v = 64 + 8 * u + 2 * k;
                    const float2 f = __half22float2(*reinterpret_cast<const __half2*>(&rr[k]));
                    acc[v] = fmaf(f.x, xsc, bf_lo(ee[k])); acc[v + 1] = fmaf(f.y, xsc, bf_hi(ee[k]));
                    PIN_F(acc[v]); PIN_F(acc[v + 1]);
                }
            }
            STAMP(tid == 0, 14);
        }
        wgmma_wait<0>();
        STAMP(tid == 0, 6);
        {
            const bool odd = q & 1;
            const int tb = c * 256 + 128 * (w & 1) + 8 * (4 * rank + 2 * wg + (w >> 1));
            float* o0 = p.out + (size_t)(tb + r) * kD + colK + (odd ? 2 * q + 6 : 2 * q);
#pragma unroll
            for (int i = 0; i < 16; i += 2) {
#pragma unroll
                for (int h = 0; h < 2; ++h) {
                    const int va = 4 * i + 2 * h, vb = va + 4;
                    PIN_F(acc[va]); PIN_F(acc[va + 1]); PIN_F(acc[vb]); PIN_F(acc[vb + 1]);
                    const float a0 = acc[va] + acc[64 + va], a1 = acc[va + 1] + acc[65 + va];
                    const float b0 = acc[vb] + acc[64 + vb], b1 = acc[vb + 1] + acc[65 + vb];
                    const float t0 = __shfl_xor_sync(0xffffffffu, odd ? a0 : b0, 1), t1 = __shfl_xor_sync(0xffffffffu, odd ? a1 : b1, 1);
                    stg128f(o0 + h * 64 * kD + 8 * i, odd ? t0 : a0, odd ? t1 : a1, odd ? b0 : t0, odd ? b1 : t1);
                }
            }
        }
        STAMP(tid == 0, 7);
        STAMP(tid == 128, 5);
    }
}

typedef CUresult (*EncodeFn)(CUtensorMap*, CUtensorMapDataType, cuuint32_t, void*, const cuuint64_t*, const cuuint64_t*,
                             const cuuint32_t*, const cuuint32_t*, CUtensorMapInterleave, CUtensorMapSwizzle,
                             CUtensorMapL2promotion, CUtensorMapFloatOOBfill);

bool encode(EncodeFn fn, CUtensorMap* m, const void* base, int rank, const cuuint64_t* dims, const cuuint64_t* strides,
            const cuuint32_t* box) {
    cuuint32_t es[5] = {1, 1, 1, 1, 1};
    return fn(m, CU_TENSOR_MAP_DATA_TYPE_BFLOAT16, rank, const_cast<void*>(base), dims, strides, box, es,
              CU_TENSOR_MAP_INTERLEAVE_NONE, CU_TENSOR_MAP_SWIZZLE_128B, CU_TENSOR_MAP_L2_PROMOTION_L2_256B,
              CU_TENSOR_MAP_FLOAT_OOB_FILL_NONE) == CUDA_SUCCESS;
}

}

extern "C" void kernel_launch(void* const* d_in, const int* in_sizes, int n_in, void* d_out, int out_size) {
    (void)in_sizes; (void)n_in; (void)out_size;
    typedef const __nv_bfloat16* bp;
    bp x = (bp)d_in[0], lam_re = (bp)d_in[1], lam_im = (bp)d_in[2], B_re = (bp)d_in[3], B_im = (bp)d_in[4];
    bp C_re = (bp)d_in[5], C_im = (bp)d_in[6], log_dt = (bp)d_in[7], dskip = (bp)d_in[8];
    bp w1 = (bp)d_in[10], b1 = (bp)d_in[11], w2 = (bp)d_in[12], b2 = (bp)d_in[13], gate_w = (bp)d_in[14];

    static EncodeFn fn = nullptr;
    static Scratch* ps = nullptr;
    if (!fn) {
        void* f = nullptr;
        cudaDriverEntryPointQueryResult qr;
        cudaGetDriverEntryPoint("cuTensorMapEncodeTiled", &f, cudaEnableDefault, &qr);
        fn = (EncodeFn)f;
        cudaGetSymbolAddress((void**)&ps, g_s);
        cudaFuncSetAttribute(fused_kernel, cudaFuncAttributeMaxDynamicSharedMemorySize, kSmemBytes);
    }
    cudaStream_t stream = cudaStreamPerThread;

    Params p;
    p.x = x; p.lam_re = lam_re; p.lam_im = lam_im; p.log_dt = log_dt; p.dskip = dskip; p.b1 = b1; p.b2 = b2;
    p.gate_w = gate_w; p.b_re = B_re; p.b_im = B_im; p.out = (float*)d_out; p.s = ps;
    char* const pHs = (char*)ps + offsetof(Scratch, Hs);
    char* const pHf = (char*)ps + offsetof(Scratch, Hf);
    char* const pBc = (char*)ps + offsetof(Scratch, Bcopy);

    const char* lo = (const char*)B_re; const char* hi = (const char*)B_im;
    p.swap = 0;
    if (hi < lo) { const char* t = lo; lo = hi; hi = t; p.swap = 1; }
    unsigned long long diff = (unsigned long long)(hi - lo);
    if (diff >= (1ull << 40) || (diff & 15) || diff == 0) {
        cudaMemcpyAsync(pBc, B_re, 2u << 20, cudaMemcpyDeviceToDevice, stream);
        cudaMemcpyAsync((char*)pBc + (2u << 20), B_im, 2u << 20, cudaMemcpyDeviceToDevice, stream);
        lo = (const char*)pBc; diff = 2u << 20; p.swap = 0;
    }

    CUtensorMap mB, mXs, mXf, mW1a, mW1b, mHs, mHf, mCre, mCim, mW2, mW2n;
    bool ok = true;
    { cuuint64_t d[4] = {1024, 8, 2, 128}, s[3] = {2048, diff, 16384}; cuuint32_t b[4] = {64, 8, 2, 8};
      ok &= encode(fn, &mB, lo, 4, d, s, b); }
    { cuuint64_t d[5] = {1024, 2, 4, 32, 8}, s[4] = {2048, 64 * 2048, 2 * 2048, 256 * 2048}; cuuint32_t b[5] = {64, 2, 4, 16, 1};
      ok &= encode(fn, &mXs, x, 5, d, s, b); }
    { cuuint64_t d[5] = {1024, 8, 4, 8, 8}, s[4] = {2048, 64 * 2048, 8 * 2048, 256 * 2048}; cuuint32_t b[5] = {64, 8, 4, 4, 1};
      ok &= encode(fn, &mXf, x, 5, d, s, b); }
    { cuuint64_t d[3] = {64, 1024, 56}, s[2] = {7168, 128}; cuuint32_t ba[3] = {64, 32, 4}, bb[3] = {64, 32, 3};
      ok &= encode(fn, &mW1a, w1, 3, d, s, ba); ok &= encode(fn, &mW1b, w1, 3, d, s, bb); }
    { cuuint64_t d[3] = {64, 2048, 32}, s[2] = {4096, 128}; cuuint32_t b[3] = {64, 64, 2};
      ok &= encode(fn, &mHs, pHs, 3, d, s, b); }
    { cuuint64_t d[2] = {3584, 2048}, s[1] = {7168}; cuuint32_t b[2] = {64, 128};
      ok &= encode(fn, &mHf, pHf, 2, d, s, b); }
    { cuuint64_t d[2] = {1024, 1024}, s[1] = {2048}; cuuint32_t b[2] = {64, 128};
      ok &= encode(fn, &mCre, C_re, 2, d, s, b); ok &= encode(fn, &mCim, C_im, 2, d, s, b); }
    { cuuint64_t d[5] = {64, 2, 448, 4, 16}, s[4] = {2048, 8 * 2048, 2 * 2048, 128}; cuuint32_t b[5] = {64, 2, 4, 4, 2};
      ok &= encode(fn, &mW2, w2, 5, d, s, b); }
    { cuuint64_t d[3] = {64, 3584, 16}, s[2] = {2048, 128}; cuuint32_t b[3] = {64, 32, 2};
      ok &= encode(fn, &mW2n, w2, 3, d, s, b); }
    if (!ok) return;

    fused_kernel<<<128, 384, kSmemBytes, stream>>>(mB, mXs, mXf, mW1b, mW1a, mHs, mHf, mCre, mCim, mW2, mW2n, p);
}
```

```cpp
#include <cuda_runtime.h>
#include <cuda_bf16.h>
#include <cuda_fp16.h>
#include <cuda.h>
#include <stdint.h>
#include <stddef.h>

#define XLDKB 40
#define PF0LINES 2
#define ETKB 60
#define PFKB 80
#define RXT 2
#define ORDER 0

namespace {

constexpr int kD = 1024, kF = 3584;
constexpr int kStages = 4;
constexpr int kStageBytes = 49152;
constexpr int kABytes = 16384;
constexpr int kXOff = kStages * kStageBytes;
constexpr int kTabOff = kXOff + 2048;
constexpr int kGateOff = kXOff + 32768;
constexpr int kBiasOff = kGateOff + 4 * 72 * 2;
constexpr int kBarOff = kBiasOff + 88 * 16;
constexpr int kSmemBytes = 232448;
static_assert(kBarOff + 160 <= kSmemBytes, "smem");
constexpr int kXBytes = 33792;
constexpr uint32_t kSmemOrg = 1024;
constexpr unsigned kSpinLimit = 1u << 18;
constexpr int kTotal = 92;

__host__ __device__ constexpr int pass2_kb(int s) {
    return s < 2 ? 6 : s < 8 ? 7 : s < 12 ? 8 : s < 18 ? 9 : s < 22 ? 10 : s < 28 ? 11 : s < 32 ? 12 : s < 38 ? 13 : s < 42 ? 14 : s < 48 ? 15 : s < 56 ? 16 : 17;
}

struct Scratch {
    unsigned claim[64];
    unsigned epoch, pad0[31];
    unsigned done, pad1[31];
    unsigned cnt[40 * 32];
    uint2 gate[2048];
    uint4 agg[8 * 1024];
    __align__(1024) uint8_t X[128 * kXBytes];
    __align__(1024) __nv_bfloat16 Hs[2048 * 2048];
    __align__(1024) __nv_bfloat16 Hf[2048 * 3584];
    __align__(1024) __nv_bfloat16 Bcopy[2 * 1024 * 1024];
};
__device__ Scratch g_s;

#define TRAP() break
#define PIN_F(x) asm volatile("" : "+f"(x))
#define PIN_R(x) asm volatile("" : "+r"(x))
#define UNDEF_F(x) asm volatile("" : "=f"(x))
#define UNDEF_R(x) asm volatile("" : "=r"(x))
#define RESPIN()
__device__ __forceinline__ uint32_t smem_u32(const void* p) { return (uint32_t)__cvta_generic_to_shared(p); }
__device__ __forceinline__ void mbar_init(uint32_t bar, uint32_t count) {
    asm volatile("mbarrier.init.shared::cta.b64 [%0], %1;" ::"r"(bar), "r"(count) : "memory");
}
__device__ __forceinline__ void mbar_expect_tx(uint32_t bar, uint32_t bytes) {
    asm volatile("mbarrier.arrive.expect_tx.shared::cta.b64 _, [%0], %1;" ::"r"(bar), "r"(bytes) : "memory");
}
__device__ __forceinline__ void mbar_wait(uint32_t bar, uint32_t parity) {
    asm volatile(
        "{\n.reg .pred p;\n.reg .u32 n;\n"
        "mbarrier.try_wait.parity.shared::cta.b64 p, [%0], %1;\n"
        "@p bra DONE;\n"
        "mov.u32 n, 0;\n"
        "LOOP:\n"
        "mbarrier.try_wait.parity.shared::cta.b64 p, [%0], %1;\n"
        "@p bra DONE;\n"
        "add.u32 n, n, 1;\n"
        "setp.lt.u32 p, n, %2;\n"
        "@p bra LOOP;\n"
        "DONE:\n}\n"
        ::"r"(bar), "r"(parity), "n"(kSpinLimit) : "memory");
}
__device__ __forceinline__ void sched_fence(uint32_t nonzero) {
    asm volatile("{\n.reg .pred p;\n.reg .u32 n;\nsetp.ne.u32 p, %0, 0;\n@p bra DONE;\nLOOP:\nmov.u32 n, %%clock;\n"
                 "setp.eq.u32 p, n, 0;\n@p bra LOOP;\nDONE:\n}\n" ::"r"(nonzero) : "memory");
}
__device__ __forceinline__ void mbar_arrive_local(uint32_t bar) {
    asm volatile("mbarrier.arrive.shared::cta.b64 _, [%0];" ::"r"(bar) : "memory");
}
__device__ __forceinline__ void mbar_arrive_cluster(uint32_t cluster_addr) {
    asm volatile("mbarrier.arrive.shared::cluster.b64 _, [%0];" ::"r"(cluster_addr) : "memory");
}
__device__ __forceinline__ uint32_t mapa(uint32_t addr, uint32_t rank) {
    uint32_t r;
    asm("mapa.shared::cluster.u32 %0, %1, %2;" : "=r"(r) : "r"(addr), "r"(rank));
    return r;
}
__device__ __forceinline__ void cluster_arrive() { asm volatile("barrier.cluster.arrive.relaxed.aligned;" ::: "memory"); }
__device__ __forceinline__ void cluster_wait() { asm volatile("barrier.cluster.wait.acquire.aligned;" ::: "memory"); }
__device__ __forceinline__ void bar_sync(int id, int n) { asm volatile("bar.sync %0, %1;" ::"r"(id), "r"(n) : "memory"); }
__device__ __forceinline__ void bar_arrive(int id, int n) { asm volatile("bar.arrive %0, %1;" ::"r"(id), "r"(n) : "memory"); }
__device__ __forceinline__ bool elect_one() {
    uint32_t p;
    asm volatile("{\n.reg .pred P;\nelect.sync _|P, 0xffffffff;\nselp.u32 %0, 1, 0, P;\n}\n" : "=r"(p));
    return p != 0;
}

__device__ __forceinline__ void tma2(uint32_t dst, const CUtensorMap* m, uint32_t bar, int c0, int c1) {
    asm volatile("cp.async.bulk.tensor.2d.shared::cluster.global.mbarrier::complete_tx::bytes [%0], [%1, {%3, %4}], [%2];"
                 ::"r"(dst), "l"(m), "r"(bar), "r"(c0), "r"(c1) : "memory");
}
__device__ __forceinline__ void tma3(uint32_t dst, const CUtensorMap* m, uint32_t bar, int c0, int c1, int c2) {
    asm volatile("cp.async.bulk.tensor.3d.shared::cluster.global.mbarrier::complete_tx::bytes [%0], [%1, {%3, %4, %5}], [%2];"
                 ::"r"(dst), "l"(m), "r"(bar), "r"(c0), "r"(c1), "r"(c2) : "memory");
}
__device__ __forceinline__ void tma4(uint32_t dst, const CUtensorMap* m, uint32_t bar, int c0, int c1, int c2, int c3) {
    asm volatile("cp.async.bulk.tensor.4d.shared::cluster.global.mbarrier::complete_tx::bytes [%0], [%1, {%3, %4, %5, %6}], [%2];"
                 ::"r"(dst), "l"(m), "r"(bar), "r"(c0), "r"(c1), "r"(c2), "r"(c3) : "memory");
}
__device__ __forceinline__ void tma5(uint32_t dst, const CUtensorMap* m, uint32_t bar, int c0, int c1, int c2, int c3, int c4) {
    asm volatile("cp.async.bulk.tensor.5d.shared::cluster.global.mbarrier::complete_tx::bytes [%0], [%1, {%3, %4, %5, %6, %7}], [%2];"
                 ::"r"(dst), "l"(m), "r"(bar), "r"(c0), "r"(c1), "r"(c2), "r"(c3), "r"(c4) : "memory");
}
__device__ __forceinline__ void tma2_mc(uint32_t dst, const CUtensorMap* m, uint32_t bar, int c0, int c1) {
    asm volatile("cp.async.bulk.tensor.2d.shared::cluster.global.mbarrier::complete_tx::bytes.multicast::cluster [%0], [%1, {%3, %4}], [%2], %5;"
                 ::"r"(dst), "l"(m), "r"(bar), "r"(c0), "r"(c1), "h"((uint16_t)3) : "memory");
}
__device__ __forceinline__ void tma3_mc(uint32_t dst, const CUtensorMap* m, uint32_t bar, int c0, int c1, int c2) {
    asm volatile("cp.async.bulk.tensor.3d.shared::cluster.global.mbarrier::complete_tx::bytes.multicast::cluster [%0], [%1, {%3, %4, %5}], [%2], %6;"
                 ::"r"(dst), "l"(m), "r"(bar), "r"(c0), "r"(c1), "r"(c2), "h"((uint16_t)3) : "memory");
}
__device__ __forceinline__ void tma5_mc(uint32_t dst, const CUtensorMap* m, uint32_t bar, int c0, int c1, int c2, int c3, int c4) {
    asm volatile("cp.async.bulk.tensor.5d.shared::cluster.global.mbarrier::complete_tx::bytes.multicast::cluster [%0], [%1, {%3, %4, %5, %6, %7}], [%2], %8;"
                 ::"r"(dst), "l"(m), "r"(bar), "r"(c0), "r"(c1), "r"(c2), "r"(c3), "r"(c4), "h"((uint16_t)3) : "memory");
}
__device__ __forceinline__ void tma3_pf(const CUtensorMap* m, int c0, int c1, int c2) {
    asm volatile("cp.async.bulk.prefetch.tensor.3d.L2.global [%0, {%1, %2, %3}];" ::"l"(m), "r"(c0), "r"(c1), "r"(c2) : "memory");
}
__device__ __forceinline__ void bulk_store(void* dst, uint32_t src, uint32_t bytes) {
    asm volatile("cp.async.bulk.global.shared::cta.bulk_group [%0], [%1], %2;" ::"l"(dst), "r"(src), "r"(bytes) : "memory");
}
__device__ __forceinline__ void bulk_load(uint32_t dst, const void* src, uint32_t bytes, uint32_t bar) {
    asm volatile("cp.async.bulk.shared::cluster.global.mbarrier::complete_tx::bytes [%0], [%1], %2, [%3];"
                 ::"r"(dst), "l"(src), "r"(bytes), "r"(bar) : "memory");
}
__device__ __forceinline__ unsigned atom_exch(unsigned* p, unsigned v) {
    unsigned r;
    asm volatile("atom.relaxed.gpu.global.exch.b32 %0, [%1], %2;" : "=r"(r) : "l"(p), "r"(v) : "memory");
    return r;
}
__device__ __forceinline__ uint32_t lds32_cluster(uint32_t a) {
    uint32_t v;
    asm volatile("ld.shared::cluster.u32 %0, [%1];" : "=r"(v) : "r"(a) : "memory");
    return v;
}
__device__ __forceinline__ void sts128f(uint32_t a, float x, float y, float z, float w) {
    asm volatile("st.shared.v4.f32 [%0], {%1, %2, %3, %4};" ::"r"(a), "f"(x), "f"(y), "f"(z), "f"(w) : "memory");
}
__device__ __forceinline__ void prefetch_map(const CUtensorMap* m) {
    asm volatile("prefetch.tensormap [%0];" ::"l"(m) : "memory");
}

__device__ __forceinline__ void prefetch_l2(const void* p, uint32_t bytes) {
    asm volatile("cp.async.bulk.prefetch.L2.global [%0], %1;" ::"l"(p), "r"(bytes) : "memory");
}

__device__ __forceinline__ void wgmma_fence() { asm volatile("wgmma.fence.sync.aligned;" ::: "memory"); }
__device__ __forceinline__ void wgmma_commit() { asm volatile("wgmma.commit_group.sync.aligned;" ::: "memory"); }
template <int N>
__device__ __forceinline__ void wgmma_wait() { asm volatile("wgmma.wait_group.sync.aligned %0;" ::"n"(N) : "memory"); }

__device__ __forceinline__ uint32_t pack_bf16(float lo, float hi) {
    uint32_t r;
    asm("cvt.rn.bf16x2.f32 %0, %1, %2;" : "=r"(r) : "f"(hi), "f"(lo));
    return r;
}
__device__ __forceinline__ uint32_t pack_f16(float lo, float hi) {
    uint32_t r;
    asm("cvt.rn.f16x2.f32 %0, %1, %2;" : "=r"(r) : "f"(hi), "f"(lo));
    return r;
}
__device__ __forceinline__ uint32_t pack_bf16_v(float lo, float hi) {
    uint32_t r;
    asm volatile("cvt.rn.bf16x2.f32 %0, %1, %2;" : "=r"(r) : "f"(hi), "f"(lo));
    return r;
}
template <int LUT>
__device__ __forceinline__ uint32_t lop3(uint32_t a, uint32_t b, uint32_t c) {
    uint32_t r;
    asm("lop3.b32 %0, %1, %2, %3, %4;" : "=r"(r) : "r"(a), "r"(b), "r"(c), "n"(LUT));
    return r;
}
__device__ __forceinline__ float bf_lo(uint32_t v) { return __uint_as_float(v << 16); }
__device__ __forceinline__ float bf_hi(uint32_t v) { return __uint_as_float(v & 0xffff0000u); }
__device__ __forceinline__ float bf16_round(float v) { return __bfloat162float(__float2bfloat16_rn(v)); }
__device__ __forceinline__ uint32_t bf2_mul(uint32_t a, uint32_t b) {
    uint32_t r;
    asm("mul.rn.bf16x2 %0, %1, %2;" : "=r"(r) : "r"(a), "r"(b));
    return r;
}
__device__ __forceinline__ uint32_t bf2_add_relu(uint32_t a, uint32_t b) {
    uint32_t r;
    asm("fma.rn.relu.bf16x2 %0, %1, %2, %3;" : "=r"(r) : "r"(a), "r"(0x3f803f80u), "r"(b));
    return r;
}
__device__ __forceinline__ uint4 ldg128(const void* p) {
    uint4 v;
    asm volatile("ld.global.nc.v4.u32 {%0, %1, %2, %3}, [%4];" : "=r"(v.x), "=r"(v.y), "=r"(v.z), "=r"(v.w) : "l"(p));
    return v;
}
__device__ __forceinline__ uint32_t ldg32(const void* p) {
    uint32_t v;
    asm volatile("ld.global.nc.u32 %0, [%1];" : "=r"(v) : "l"(p));
    return v;
}
__device__ __forceinline__ uint32_t ldg32na(const void* p) {
    uint32_t v;
    asm volatile("ld.global.nc.L1::no_allocate.u32 %0, [%1];" : "=r"(v) : "l"(p));
    return v;
}
__device__ __forceinline__ uint32_t ldg16(const __nv_bfloat16* p) {
    uint32_t v;
    asm volatile("ld.global.nc.u16 %0, [%1];" : "=r"(v) : "l"(p));
    return v;
}
__device__ __forceinline__ uint4 ld_relaxed128(const void* p) {
    uint4 v;
    asm volatile("ld.relaxed.gpu.global.v4.u32 {%0, %1, %2, %3}, [%4];" : "=r"(v.x), "=r"(v.y), "=r"(v.z), "=r"(v.w) : "l"(p) : "memory");
    return v;
}
__device__ __forceinline__ uint2 ld_relaxed64(const void* p) {
    unsigned long long v;
    asm volatile("ld.relaxed.gpu.global.u64 %0, [%1];" : "=l"(v) : "l"(p) : "memory");
    return make_uint2((uint32_t)v, (uint32_t)(v >> 32));
}
__device__ __forceinline__ void st_relaxed64(void* p, uint32_t lo, uint32_t hi) {
    unsigned long long v = ((unsigned long long)hi << 32) | lo;
    asm volatile("st.relaxed.gpu.global.u64 [%0], %1;" ::"l"(p), "l"(v) : "memory");
}
__device__ __forceinline__ void st_relaxed2x64(void* p, uint32_t a, uint32_t b, uint32_t c, uint32_t d) {
    unsigned long long v0 = ((unsigned long long)b << 32) | a, v1 = ((unsigned long long)d << 32) | c;
    asm volatile("st.relaxed.gpu.global.v2.u64 [%0], {%1, %2};" ::"l"(p), "l"(v0), "l"(v1) : "memory");
}
__device__ __forceinline__ uint4 ld_relaxed2x64(const void* p) {
    unsigned long long v0, v1;
    asm volatile("ld.relaxed.gpu.global.v2.u64 {%0, %1}, [%2];" : "=l"(v0), "=l"(v1) : "l"(p) : "memory");
    return make_uint4((uint32_t)v0, (uint32_t)(v0 >> 32), (uint32_t)v1, (uint32_t)(v1 >> 32));
}
__device__ __forceinline__ void stg128(void* p, uint32_t a, uint32_t b, uint32_t c, uint32_t d) {
    asm volatile("st.global.v4.u32 [%0], {%1, %2, %3, %4};" ::"l"(p), "r"(a), "r"(b), "r"(c), "r"(d) : "memory");
}
__device__ __forceinline__ void stg64f(void* p, float a, float b) {
    asm volatile("st.global.v2.f32 [%0], {%1, %2};" ::"l"(p), "f"(a), "f"(b) : "memory");
}
__device__ __forceinline__ uint4 lds128(uint32_t a) {
    uint4 v;
    asm volatile("ld.shared.v4.u32 {%0, %1, %2, %3}, [%4];" : "=r"(v.x), "=r"(v.y), "=r"(v.z), "=r"(v.w) : "r"(a) : "memory");
    return v;
}
__device__ __forceinline__ uint2 lds64(uint32_t a) {
    uint2 v;
    asm volatile("ld.shared.v2.u32 {%0, %1}, [%2];" : "=r"(v.x), "=r"(v.y) : "r"(a) : "memory");
    return v;
}
__device__ __forceinline__ uint4 ldsm4(uint32_t a) {
    uint4 v;
    asm volatile("ldmatrix.sync.aligned.m8n8.x4.shared.b16 {%0, %1, %2, %3}, [%4];" : "=r"(v.x), "=r"(v.y), "=r"(v.z), "=r"(v.w) : "r"(a) : "memory");
    return v;
}
__device__ __forceinline__ uint32_t lds16(uint32_t a) {
    uint32_t v;
    asm volatile("ld.shared.u16 %0, [%1];" : "=r"(v) : "r"(a) : "memory");
    return v;
}
__device__ __forceinline__ void sts16(uint32_t a, uint32_t x) {
    asm volatile("st.shared.u16 [%0], %1;" ::"r"(a), "h"((uint16_t)x) : "memory");
}
__device__ __forceinline__ void st_relaxed32(void* p, uint32_t v) {
    asm volatile("st.relaxed.gpu.global.u32 [%0], %1;" ::"l"(p), "r"(v) : "memory");
}
__device__ __forceinline__ float lds32f(uint32_t a) {
    float v;
    asm volatile("ld.shared.f32 %0, [%1];" : "=f"(v) : "r"(a) : "memory");
    return v;
}
__device__ __forceinline__ void sts128(uint32_t a, uint32_t x, uint32_t y, uint32_t z, uint32_t w) {
    asm volatile("st.shared.v4.u32 [%0], {%1, %2, %3, %4};" ::"r"(a), "r"(x), "r"(y), "r"(z), "r"(w) : "memory");
}
__device__ __forceinline__ void sts64f(uint32_t a, float x, float y) {
    asm volatile("st.shared.v2.f32 [%0], {%1, %2};" ::"r"(a), "f"(x), "f"(y) : "memory");
}
__device__ __forceinline__ float4 lds128f(uint32_t a) {
    float4 v;
    asm volatile("ld.shared.v4.f32 {%0, %1, %2, %3}, [%4];" : "=f"(v.x), "=f"(v.y), "=f"(v.z), "=f"(v.w) : "r"(a) : "memory");
    return v;
}
__device__ __forceinline__ uint32_t lds32(uint32_t a) {
    uint32_t v;
    asm volatile("ld.shared.u32 %0, [%1];" : "=r"(v) : "r"(a) : "memory");
    return v;
}
__device__ __forceinline__ void sts32(uint32_t a, uint32_t x) {
    asm volatile("st.shared.u32 [%0], %1;" ::"r"(a), "r"(x) : "memory");
}
__device__ __forceinline__ void stg128f(void* p, float a, float b, float c, float d) {
    asm volatile("st.global.v4.f32 [%0], {%1, %2, %3, %4};" ::"l"(p), "f"(a), "f"(b), "f"(c), "f"(d) : "memory");
}
__device__ __forceinline__ unsigned ld_relaxed32(const unsigned* p) {
    unsigned v;
    asm volatile("ld.relaxed.gpu.global.u32 %0, [%1];" : "=r"(v) : "l"(p) : "memory");
    return v;
}
__device__ __forceinline__ void wait_counter(const unsigned* p, unsigned target) {
    unsigned n = 0, v;
    while (true) {
        asm volatile("ld.acquire.gpu.global.u32 %0, [%1];" : "=r"(v) : "l"(p) : "memory");
        if ((int)(v - target) >= 0) break;
        if (++n > kSpinLimit) TRAP();
        __nanosleep(32);
    }
}
#define KT(IT, W) do { } while (0)
#define STAMP(cond, slot) do { } while (0)
#define STAMPA(cond, slot) STAMP(cond, slot)
#define STAMPB(cond, slot) do { } while (0)

template <int TA, int TB>
__device__ __forceinline__ void wgmma_n256(float (&d)[128], uint64_t da, uint64_t db, int keep) {
    asm volatile(
        "{\n.reg .pred p;\nsetp.ne.b32 p, %132, 0;\n"
        "wgmma.mma_async.sync.aligned.m64n256k16.f32.bf16.bf16 "
        "{%0, %1, %2, %3, %4, %5, %6, %7, %8, %9, %10, %11, %12, %13, %14, %15, "
        "%16, %17, %18, %19, %20, %21, %22, %23, %24, %25, %26, %27, %28, %29, %30, %31, "
        "%32, %33, %34, %35, %36, %37, %38, %39, %40, %41, %42, %43, %44, %45, %46, %47, "
        "%48, %49, %50, %51, %52, %53, %54, %55, %56, %57, %58, %59, %60, %61, %62, %63, "
        "%64, %65, %66, %67, %68, %69, %70, %71, %72, %73, %74, %75, %76, %77, %78, %79, "
        "%80, %81, %82, %83, %84, %85, %86, %87, %88, %89, %90, %91, %92, %93, %94, %95, "
        "%96, %97, %98, %99, %100, %101, %102, %103, %104, %105, %106, %107, %108, %109, %110, %111, "
        "%112, %113, %114, %115, %116, %117, %118, %119, %120, %121, %122, %123, %124, %125, %126, %127}, "
        "%128, %129, p, 1, 1, %130, %131;\n}\n"
        : "+f"(d[0]), "+f"(d[1]), "+f"(d[2]), "+f"(d[3]), "+f"(d[4]), "+f"(d[5]), "+f"(d[6]), "+f"(d[7]),
          "+f"(d[8]), "+f"(d[9]), "+f"(d[10]), "+f"(d[11]), "+f"(d[12]), "+f"(d[13]), "+f"(d[14]), "+f"(d[15]),
          "+f"(d[16]), "+f"(d[17]), "+f"(d[18]), "+f"(d[19]), "+f"(d[20]), "+f"(d[21]), "+f"(d[22]), "+f"(d[23]),
          "+f"(d[24]), "+f"(d[25]), "+f"(d[26]), "+f"(d[27]), "+f"(d[28]), "+f"(d[29]), "+f"(d[30]), "+f"(d[31]),
          "+f"(d[32]), "+f"(d[33]), "+f"(d[34]), "+f"(d[35]), "+f"(d[36]), "+f"(d[37]), "+f"(d[38]), "+f"(d[39]),
          "+f"(d[40]), "+f"(d[41]), "+f"(d[42]), "+f"(d[43]), "+f"(d[44]), "+f"(d[45]), "+f"(d[46]), "+f"(d[47]),
          "+f"(d[48]), "+f"(d[49]), "+f"(d[50]), "+f"(d[51]), "+f"(d[52]), "+f"(d[53]), "+f"(d[54]), "+f"(d[55]),
          "+f"(d[56]), "+f"(d[57]), "+f"(d[58]), "+f"(d[59]), "+f"(d[60]), "+f"(d[61]), "+f"(d[62]), "+f"(d[63]),
          "+f"(d[64]), "+f"(d[65]), "+f"(d[66]), "+f"(d[67]), "+f"(d[68]), "+f"(d[69]), "+f"(d[70]), "+f"(d[71]),
          "+f"(d[72]), "+f"(d[73]), "+f"(d[74]), "+f"(d[75]), "+f"(d[76]), "+f"(d[77]), "+f"(d[78]), "+f"(d[79]),
          "+f"(d[80]), "+f"(d[81]), "+f"(d[82]), "+f"(d[83]), "+f"(d[84]), "+f"(d[85]), "+f"(d[86]), "+f"(d[87]),
          "+f"(d[88]), "+f"(d[89]), "+f"(d[90]), "+f"(d[91]), "+f"(d[92]), "+f"(d[93]), "+f"(d[94]), "+f"(d[95]),
          "+f"(d[96]), "+f"(d[97]), "+f"(d[98]), "+f"(d[99]), "+f"(d[100]), "+f"(d[101]), "+f"(d[102]), "+f"(d[103]),
          "+f"(d[104]), "+f"(d[105]), "+f"(d[106]), "+f"(d[107]), "+f"(d[108]), "+f"(d[109]), "+f"(d[110]), "+f"(d[111]),
          "+f"(d[112]), "+f"(d[113]), "+f"(d[114]), "+f"(d[115]), "+f"(d[116]), "+f"(d[117]), "+f"(d[118]), "+f"(d[119]),
          "+f"(d[120]), "+f"(d[121]), "+f"(d[122]), "+f"(d[123]), "+f"(d[124]), "+f"(d[125]), "+f"(d[126]), "+f"(d[127])
        : "l"(da), "l"(db), "n"(TA), "n"(TB), "r"(keep));
}
template <int TA, int TB>
__device__ __forceinline__ void wgmma_n192(float (&d)[128], uint64_t da, uint64_t db, int keep) {
    asm volatile(
        "{\n.reg .pred p;\nsetp.ne.b32 p, %100, 0;\n"
        "wgmma.mma_async.sync.aligned.m64n192k16.f32.bf16.bf16 "
        "{%0, %1, %2, %3, %4, %5, %6, %7, %8, %9, %10, %11, %12, %13, %14, %15, "
        "%16, %17, %18, %19, %20, %21, %22, %23, %24, %25, %26, %27, %28, %29, %30, %31, "
        "%32, %33, %34, %35, %36, %37, %38, %39, %40, %41, %42, %43, %44, %45, %46, %47, "
        "%48, %49, %50, %51, %52, %53, %54, %55, %56, %57, %58, %59, %60, %61, %62, %63, "
        "%64, %65, %66, %67, %68, %69, %70, %71, %72, %73, %74, %75, %76, %77, %78, %79, "
        "%80, %81, %82, %83, %84, %85, %86, %87, %88, %89, %90, %91, %92, %93, %94, %95}, "
        "%96, %97, p, 1, 1, %98, %99;\n}\n"
        : "+f"(d[0]), "+f"(d[1]), "+f"(d[2]), "+f"(d[3]), "+f"(d[4]), "+f"(d[5]), "+f"(d[6]), "+f"(d[7]),
          "+f"(d[8]), "+f"(d[9]), "+f"(d[10]), "+f"(d[11]), "+f"(d[12]), "+f"(d[13]), "+f"(d[14]), "+f"(d[15]),
          "+f"(d[16]), "+f"(d[17]), "+f"(d[18]), "+f"(d[19]), "+f"(d[20]), "+f"(d[21]), "+f"(d[22]), "+f"(d[23]),
          "+f"(d[24]), "+f"(d[25]), "+f"(d[26]), "+f"(d[27]), "+f"(d[28]), "+f"(d[29]), "+f"(d[30]), "+f"(d[31]),
          "+f"(d[32]), "+f"(d[33]), "+f"(d[34]), "+f"(d[35]), "+f"(d[36]), "+f"(d[37]), "+f"(d[38]), "+f"(d[39]),
          "+f"(d[40]), "+f"(d[41]), "+f"(d[42]), "+f"(d[43]), "+f"(d[44]), "+f"(d[45]), "+f"(d[46]), "+f"(d[47]),
          "+f"(d[48]), "+f"(d[49]), "+f"(d[50]), "+f"(d[51]), "+f"(d[52]), "+f"(d[53]), "+f"(d[54]), "+f"(d[55]),
          "+f"(d[56]), "+f"(d[57]), "+f"(d[58]), "+f"(d[59]), "+f"(d[60]), "+f"(d[61]), "+f"(d[62]), "+f"(d[63]),
          "+f"(d[64]), "+f"(d[65]), "+f"(d[66]), "+f"(d[67]), "+f"(d[68]), "+f"(d[69]), "+f"(d[70]), "+f"(d[71]),
          "+f"(d[72]), "+f"(d[73]), "+f"(d[74]), "+f"(d[75]), "+f"(d[76]), "+f"(d[77]), "+f"(d[78]), "+f"(d[79]),
          "+f"(d[80]), "+f"(d[81]), "+f"(d[82]), "+f"(d[83]), "+f"(d[84]), "+f"(d[85]), "+f"(d[86]), "+f"(d[87]),
          "+f"(d[88]), "+f"(d[89]), "+f"(d[90]), "+f"(d[91]), "+f"(d[92]), "+f"(d[93]), "+f"(d[94]), "+f"(d[95])
        : "l"(da), "l"(db), "n"(TA), "n"(TB), "r"(keep));
}
template <int TA, int TB>
__device__ __forceinline__ void wgmma_n128(float (&d)[128], uint64_t da, uint64_t db, int keep) {
    asm volatile(
        "{\n.reg .pred p;\nsetp.ne.b32 p, %68, 0;\n"
        "wgmma.mma_async.sync.aligned.m64n128k16.f32.bf16.bf16 "
        "{%0, %1, %2, %3, %4, %5, %6, %7, %8, %9, %10, %11, %12, %13, %14, %15, "
        "%16, %17, %18, %19, %20, %21, %22, %23, %24, %25, %26, %27, %28, %29, %30, %31, "
        "%32, %33, %34, %35, %36, %37, %38, %39, %40, %41, %42, %43, %44, %45, %46, %47, "
        "%48, %49, %50, %51, %52, %53, %54, %55, %56, %57, %58, %59, %60, %61, %62, %63}, "
        "%64, %65, p, 1, 1, %66, %67;\n}\n"
        : "+f"(d[0]), "+f"(d[1]), "+f"(d[2]), "+f"(d[3]), "+f"(d[4]), "+f"(d[5]), "+f"(d[6]), "+f"(d[7]),
          "+f"(d[8]), "+f"(d[9]), "+f"(d[10]), "+f"(d[11]), "+f"(d[12]), "+f"(d[13]), "+f"(d[14]), "+f"(d[15]),
          "+f"(d[16]), "+f"(d[17]), "+f"(d[18]), "+f"(d[19]), "+f"(d[20]), "+f"(d[21]), "+f"(d[22]), "+f"(d[23]),
          "+f"(d[24]), "+f"(d[25]), "+f"(d[26]), "+f"(d[27]), "+f"(d[28]), "+f"(d[29]), "+f"(d[30]), "+f"(d[31]),
          "+f"(d[32]), "+f"(d[33]), "+f"(d[34]), "+f"(d[35]), "+f"(d[36]), "+f"(d[37]), "+f"(d[38]), "+f"(d[39]),
          "+f"(d[40]), "+f"(d[41]), "+f"(d[42]), "+f"(d[43]), "+f"(d[44]), "+f"(d[45]), "+f"(d[46]), "+f"(d[47]),
          "+f"(d[48]), "+f"(d[49]), "+f"(d[50]), "+f"(d[51]), "+f"(d[52]), "+f"(d[53]), "+f"(d[54]), "+f"(d[55]),
          "+f"(d[56]), "+f"(d[57]), "+f"(d[58]), "+f"(d[59]), "+f"(d[60]), "+f"(d[61]), "+f"(d[62]), "+f"(d[63])
        : "l"(da), "l"(db), "n"(TA), "n"(TB), "r"(keep));
}
__device__ __forceinline__ void wgmma_n128_rs(float (&d)[128], uint32_t a0, uint32_t a1, uint32_t a2, uint32_t a3, uint64_t db) {
    asm volatile(
        "{\n.reg .pred p;\nsetp.ne.b32 p, 1, 0;\n"
        "wgmma.mma_async.sync.aligned.m64n128k16.f32.bf16.bf16 "
        "{%0, %1, %2, %3, %4, %5, %6, %7, %8, %9, %10, %11, %12, %13, %14, %15, "
        "%16, %17, %18, %19, %20, %21, %22, %23, %24, %25, %26, %27, %28, %29, %30, %31, "
        "%32, %33, %34, %35, %36, %37, %38, %39, %40, %41, %42, %43, %44, %45, %46, %47, "
        "%48, %49, %50, %51, %52, %53, %54, %55, %56, %57, %58, %59, %60, %61, %62, %63}, "
        "{%64, %65, %66, %67}, %68, p, 1, 1, 1;\n}\n"
        : "+f"(d[0]), "+f"(d[1]), "+f"(d[2]), "+f"(d[3]), "+f"(d[4]), "+f"(d[5]), "+f"(d[6]), "+f"(d[7]),
          "+f"(d[8]), "+f"(d[9]), "+f"(d[10]), "+f"(d[11]), "+f"(d[12]), "+f"(d[13]), "+f"(d[14]), "+f"(d[15]),
          "+f"(d[16]), "+f"(d[17]), "+f"(d[18]), "+f"(d[19]), "+f"(d[20]), "+f"(d[21]), "+f"(d[22]), "+f"(d[23]),
          "+f"(d[24]), "+f"(d[25]), "+f"(d[26]), "+f"(d[27]), "+f"(d[28]), "+f"(d[29]), "+f"(d[30]), "+f"(d[31]),
          "+f"(d[32]), "+f"(d[33]), "+f"(d[34]), "+f"(d[35]), "+f"(d[36]), "+f"(d[37]), "+f"(d[38]), "+f"(d[39]),
          "+f"(d[40]), "+f"(d[41]), "+f"(d[42]), "+f"(d[43]), "+f"(d[44]), "+f"(d[45]), "+f"(d[46]), "+f"(d[47]),
          "+f"(d[48]), "+f"(d[49]), "+f"(d[50]), "+f"(d[51]), "+f"(d[52]), "+f"(d[53]), "+f"(d[54]), "+f"(d[55]),
          "+f"(d[56]), "+f"(d[57]), "+f"(d[58]), "+f"(d[59]), "+f"(d[60]), "+f"(d[61]), "+f"(d[62]), "+f"(d[63])
        : "r"(a0), "r"(a1), "r"(a2), "r"(a3), "l"(db));
}

constexpr uint64_t kDescHi = (uint64_t)(64u | 0x40000000u) << 32;
template <int MODE>
__device__ __forceinline__ void mma_kblock(float (&acc)[128], uint32_t a_lo, uint32_t b_lo, int keep) {
    constexpr uint32_t HALF = (MODE == 1) ? 12288u : 16384u;
    constexpr bool BN = (MODE == 1 || MODE == 2 || MODE == 4);
#pragma unroll
    for (int kk = 0; kk < 4; ++kk) {
        const uint32_t ao = (MODE == 3) ? kk * 2048u : kk * 32u;
        const uint32_t bo = BN ? ((kk >> 1) * HALF + (kk & 1) * 2048u) : kk * 32u;
        const uint64_t da = kDescHi | (uint64_t)(a_lo + (ao >> 4) + (1u << 16));
        const uint64_t db = kDescHi | (uint64_t)(b_lo + (bo >> 4) + (BN ? (256u << 16) : (1u << 16)));
        if (MODE == 1) wgmma_n192<0, 1>(acc, da, db, kk == 0 ? keep : 1);
        else if (MODE == 4) wgmma_n128<0, 1>(acc, da, db, 1);
        else wgmma_n256<(MODE == 3), BN>(acc, da, db, kk == 0 ? keep : 1);
    }
}

struct Params {
    Scratch* s;
    const __nv_bfloat16* x;
    const __nv_bfloat16* b_re;
    const __nv_bfloat16* b_im;
    const __nv_bfloat16* gate_w;
    const __nv_bfloat16* lam_re;
    const __nv_bfloat16* lam_im;
    const __nv_bfloat16* log_dt;
    const __nv_bfloat16* dskip;
    const __nv_bfloat16* b1;
    const __nv_bfloat16* b2;
    float* out;
    int swap;
};

#define CMUL(rr, ri, ar, ai, br, bi) do { float _r = (ar) * (br) - (ai) * (bi); float _i = (ar) * (bi) + (ai) * (br); rr = _r; ri = _i; } while (0)
#define CFMA(rr, ri, ar, ai, br, bi) do { float _r = fmaf(-(ai), (bi), fmaf((ar), (br), rr)); float _i = fmaf((ai), (br), fmaf((ar), (bi), ri)); rr = _r; ri = _i; } while (0)

#define KB_OPEN(IT, LAST)                                                                        \
    KT(IT, 0);                                                                                   \
    if (ORDER && (LAST) && wg == 1) bar_sync(7, 256);                                            \
    mbar_wait(bar_full + 8 * ((IT) & 3), ((IT) >> 2) & 1);                                \
    KT(IT, 1);
#define KB_CLOSE(IT, LAST, REL)                                                                  \
    if (ORDER && (LAST) && wg == 0) bar_arrive(7, 256);                                          \
    wgmma_wait<1>();                                                                             \
    if (lane < 2 && (REL)) mbar_arrive_cluster(rel_addr + 8 * (((IT) - 1) & 3));
#define KBLOCK(MODE, IT, FIRST, LAST)                                                            \
    {                                                                                            \
        const uint32_t so = ((IT) & 3) * (kStageBytes >> 4);                                     \
        KB_OPEN(IT, LAST);                                                                       \
        wgmma_fence();                                                                           \
        mma_kblock<MODE>(acc, a_lo + so, b_lo + so, !(FIRST));                                   \
        wgmma_commit();                                                                          \
        KB_CLOSE(IT, LAST, !(FIRST));                                                            \
    }
#define TILE_END() do { wgmma_wait<0>(); if (lane < 2) mbar_arrive_cluster(rel_addr + 24); } while (0)

__global__ void __cluster_dims__(2, 1, 1) __launch_bounds__(384, 1)
fused_kernel(const __grid_constant__ CUtensorMap mB, const __grid_constant__ CUtensorMap mXs, const __grid_constant__ CUtensorMap mXf,
             const __grid_constant__ CUtensorMap mW1b, const __grid_constant__ CUtensorMap mW1a, const __grid_constant__ CUtensorMap mHs,
             const __grid_constant__ CUtensorMap mHf, const __grid_constant__ CUtensorMap mCre, const __grid_constant__ CUtensorMap mCim,
             const __grid_constant__ CUtensorMap mW2, const __grid_constant__ CUtensorMap mW2n, const Params p) {
    extern __shared__ __align__(1024) uint8_t smem_raw[];
    const uint32_t sbase = smem_u32(smem_raw);
    if ((sbase & 0x3ffffu) != kSmemOrg) return;
    const uint32_t bar_full = sbase + kBarOff, bar_empty = bar_full + 32, bar_dep = bar_full + 64;
    const uint32_t bar_x = bar_full + 88, bar_c = bar_full + 96, role_s = bar_full + 104, tag_s = bar_full + 112 + (threadIdx.x & 1) * 4;

    const int tid = threadIdx.x, lane = tid & 31;
    const int warp = __shfl_sync(0xffffffffu, tid >> 5, 0);
    const uint32_t rank = blockIdx.x & 1;

    int pref;
    {
        unsigned smid;
        asm("mov.u32 %0, %%smid;" : "=r"(smid));
        const int t = smid >> 1, u = t - 32, d = (u * 37) >> 8;
        pref = (t < 32) ? (t & 7) * 8 + (t >> 3) : (t < 60) ? (1 + u - 7 * d) * 8 + 4 + d : ((t - 58) & 7);
    }
#define FIRST_FILL(ROLE)                                                                     \
    {                                                                                        \
        mbar_expect_tx(bar_full, 49152);                                                     \
        tma4(sbase, &mB, bar_full, 0, 0, 0, (((ROLE) & 7) * 2 + (int)rank) * 8);             \
        tma5(sbase + kABytes, &mXs, bar_full, 0, 0, 0, 0, (ROLE) >> 3);                      \
        tma5(sbase + kABytes + 16384, &mXs, bar_full, 0, 0, 0, 16, (ROLE) >> 3);             \
    }
    STAMP(tid == 0, 0);
    if (warp < 2) {
        if (elect_one()) {
            if (warp & 1) {
                if (rank == 0) {
                    int role = pref;
                    unsigned taken = atom_exch(&p.s->claim[pref], 1u);
#pragma unroll 1
                    for (int i = 0; taken != 0 && i < 64; ++i) { role = i; taken = atom_exch(&p.s->claim[i], 1u); }
                    sts32(role_s, role);
                    asm volatile("fence.acq_rel.cluster;" ::: "memory");
                }
            } else {
                prefetch_map(&mB); prefetch_map(&mXs);
#pragma unroll
                for (int s = 0; s < kStages; ++s) {
                    mbar_init(bar_full + 8 * s, 1);
                    mbar_init(bar_empty + 8 * s, 16);
                    mbar_init(bar_dep + 8 * s, 1);
                }
                mbar_init(bar_c, 96);
                asm volatile("fence.mbarrier_init.release.cluster;\nfence.proxy.async.shared::cta;" ::: "memory");
                FIRST_FILL(pref);
                mbar_expect_tx(bar_x, 2048);
                bulk_load(sbase + kXOff, p.gate_w, 2048, bar_x);
            }
        }
    } else if (warp < 2 + PF0LINES) {
        const int row = blockIdx.x * 32 + lane;
        const __nv_bfloat16* src = (row < 2048) ? p.x : (row < 3072) ? p.b_re - 2048 * kD : p.b_im - 3072 * kD;
        asm volatile("prefetch.global.L2 [%0];" ::"l"(src + row * kD + (warp - 2) * 64) : "memory");
    }
    __syncwarp();
    cluster_arrive();
    cluster_wait();
    const int role = __shfl_sync(0xffffffffu, (int)lds32_cluster(mapa(role_s, 0)), 0);
    if (__builtin_expect(role != pref, 0)) {
        if (warp == 0 && elect_one()) {
            mbar_wait(bar_full, 0);
            asm volatile("mbarrier.inval.shared::cta.b64 [%0];" ::"r"(bar_full) : "memory");
            mbar_init(bar_full, 1);
            asm volatile("fence.mbarrier_init.release.cluster;\nfence.proxy.async.shared::cta;" ::: "memory");
            FIRST_FILL(role);
        }
        __syncwarp();
        bar_sync(0, 384);
    }
    const int c = role >> 3;
    const int j8 = role & 7;
    const int cb = j8 * 2 + (int)rank;
    const int rb = 2 * c + (int)rank;
    const int kh = j8 >> 2;
    const int colK = (j8 & 3) * 256 + kh * 128, colS = colK ^ 128;

    if (warp >= 8) {
        asm volatile("setmaxnreg.dec.sync.aligned.u32 24;");
        if (warp > 8) {
            if (warp == 11) {
                if (lane < 9) prefetch_map(&mXf + lane);
#pragma unroll 1
                for (int en = lane; en < 88; en += 32) {
                    const int J = en >> 2;
                    const __nv_bfloat16* src = ((J < 14) ? p.b1 : (J < 18) ? p.dskip : p.b2) + 32 * J + 2 * (en & 3) +
                                               ((J < 6) ? 2048 + 192 * j8 : (J < 14) ? 256 * j8 - 192 : colK - ((J < 18) ? 448 : 576));
                    sts128(sbase + kBiasOff + en * 16, ldg32(src), ldg32(src + 8), ldg32(src + 16), ldg32(src + 24));
                }
                mbar_arrive_local(bar_c);
            } else {
                {
                    sts32(tag_s, ld_relaxed32(&p.s->epoch) + 1);
                    const int ch = cb * 64 + (tid - 288);
                    const uint32_t t_s = sbase + kTabOff + (tid - 288) * 64;
                    const float Lr = bf_lo(ldg16(p.lam_re + ch)), Li = bf_lo(ldg16(p.lam_im + ch));
                    const float dt = bf16_round(expf(bf_lo(ldg16(p.log_dt + ch))));
                    const float ea = expf(dt * Lr);
                    float lr, li;
                    sincospif((dt * Li) * 0.31830988618379067f, &li, &lr);
                    lr *= ea; li *= ea;
                    const float nr = lr - 1.0f, ni = li;
                    const bool big = fabsf(Lr) >= fabsf(Li);
                    const float u = big ? Lr : Li, v = big ? Li : Lr;
                    const float t = v / u, d = 2.0f / fmaf(v, t, u);
                    const float cr = (big ? fmaf(ni, t, nr) : fmaf(nr, t, ni)) * d, ci = (big ? fmaf(-nr, t, ni) : fmaf(ni, t, -nr)) * d;
                    if (p.swap) li = -li;
                    const float m00 = p.swap ? -ci : cr, m01 = p.swap ? cr : -ci, m10 = p.swap ? -cr : -ci, m11 = p.swap ? -ci : -cr;
#pragma unroll
                    for (int q = 0; q < 4; ++q) {
                        sts128f(t_s + q * 16, lr, li, m00, m01);
                        sts128f(t_s + 12288 + q * 16, 0.f, 0.f, 0.f, 0.f);
                    }
#pragma unroll 1
                    for (int i = 0; i < 6; ++i) CMUL(lr, li, lr, li, lr, li);
                    float ar, ai, br, bi;
                    CMUL(ar, ai, lr, li, lr, li);
                    CMUL(br, bi, ar, ai, lr, li);
                    sts128f(t_s + 4096, m10, m11, 0.f, 0.f);
#pragma unroll
                    for (int q = 1; q < 4; ++q) sts128f(t_s + 4096 + q * 16, m10, m11, lr, li);
                    sts128f(t_s + 8192, 0.f, 0.f, 1.f, 0.f);
                    sts128f(t_s + 8192 + 16, 0.f, 0.f, lr, li);
                    sts128f(t_s + 8192 + 32, ar, ai, ar, ai);
                    sts128f(t_s + 8192 + 48, ar, ai, br, bi);
                    CMUL(ar, ai, ar, ai, ar, ai);
                    br = 1.f; bi = 0.f;
#pragma unroll 1
                    for (int k = c - 1; k >= 0; --k) {
                        sts64f(t_s + 12288 + (k & 3) * 16 + (k >> 2) * 8, br, bi);
                        CMUL(br, bi, br, bi, ar, ai);
                    }
                    mbar_arrive_local(bar_c);
                }
                if (warp == 9) {
#pragma unroll 1
                    for (int ev = 0; ev < 3; ++ev) {
                        if (ev == 2) {
                            uint8_t* box = p.s->X + (size_t)(role * 2 + rank) * kXBytes + lane * 16;
#pragma unroll 1
                            for (int i = 0; i < kXBytes; i += 512) stg128(box + i, 0, 0, 0, 0);
                        }
                        bar_sync(3 + ev, 288);
                        if (lane == 0) {
                            unsigned* cnt = &p.s->cnt[(ev == 0 ? c : 16 * ev - 8 + rb) * 32];
                            asm volatile("fence.acq_rel.gpu;\nfence.proxy.async.global;" ::: "memory");
                            asm volatile("red.relaxed.gpu.global.add.u32 [%0], 1;" ::"l"(cnt) : "memory");
                        }
                        __syncwarp();
                    }
                } else if (lane == 0) {
                    const unsigned tag = lds32(tag_s);
#pragma unroll 1
                    for (int ev = 0; ev < 3; ++ev) {
                        wait_counter(&p.s->cnt[(ev == 0 ? c : 16 * ev - 8 + rb) * 32], tag * (ev == 0 ? 16u : 8u));
                        mbar_arrive_local(bar_dep + 8 * ev);
                        if (ev == 0 && atomicInc(&p.s->done, 127u) == 127u) {
                            st_relaxed32(&p.s->epoch, tag);
#pragma unroll 1
                            for (int i = 0; i < 64; i += 4) stg128(&p.s->claim[i], 0, 0, 0, 0);
                        }
                    }
                }
            }
        } else if (elect_one()) {
            int it = 1;
#define ACQUIRE(BYTES)                                                   \
    const uint32_t st = sbase + (it & 3) * kStageBytes, fb = bar_full + 8 * (it & 3); \
    mbar_wait(bar_empty + 8 * (it & 3), ((it >> 2) & 1) ^ 1);     \
    mbar_expect_tx(fb, BYTES);
#pragma unroll 1
            for (; it < 16; ++it) {
                ACQUIRE(49152);
                tma4(st, &mB, fb, it * 64, 0, 0, cb * 8);
                tma5_mc(st + kABytes + rank * 16384, &mXs, fb, it * 64, 0, 0, rank * 16, c);
            }
#pragma unroll 1
            for (; it < 48; ++it) {
                const bool t1 = it < 32;
                const int k0 = (it & 15) * 64;
                ACQUIRE(t1 ? 40960 : 49152);
                tma5(st, &mXf, fb, k0, 0, 0, rank * 4, c);
                tma3_mc(st + kABytes + rank * (t1 ? 12288 : 16384), t1 ? &mW1b : &mW1a, fb, 0, k0 + rank * 32, t1 ? 32 + 3 * j8 : 4 * j8);
                if ((it & ~2) == XLDKB) {
                    const int h = (it >> 1) & 1;
                    if (h == 0) mbar_expect_tx(bar_x, 32768);
                    tma5(sbase + kXOff + h * 16384, &mXf, bar_x, colK + h * 64, 0, 0, rank * 4, c);
                }
            }
            STAMPA(true, 8);
            mbar_wait(bar_dep, 0);
            asm volatile("fence.proxy.async.global;" ::: "memory");
            STAMPA(true, 9);
#pragma unroll 1
            for (; it < 64; ++it) {
                const int k0 = (it & 15) * 64;
                ACQUIRE(49152);
                tma3(st, &mHs, fb, 0, kh * 1024 + k0, rb * 2);
                tma2_mc(st + kABytes + rank * 16384, kh ? &mCim : &mCre, fb, k0, rank ? colS : colK);
            }
            int f0 = 2048 + 768 * kh;
#pragma unroll 1
            for (; it < kTotal; ++it, f0 += 64) {
                if (it == 64 || it == 76) {
                    mbar_wait(bar_dep + (it == 64 ? 8 : 16), 0);
                    asm volatile("fence.proxy.async.global;" ::: "memory");
                    if (it == 76) f0 = 1024 * kh;
                }
                if (f0 == 256 * j8) f0 += 256;
                if (it == 88) f0 = 256 * (j8 ^ 4);
                ACQUIRE(49152);
                tma2(st, &mHf, fb, f0, rb * 128);
                tma5_mc(st + kABytes + rank * 16384, &mW2, fb, 0, 0, (f0 >> 3) + 4 * rank, 0, colK >> 6);
                if (it < 88) tma5_mc(st + kABytes + rank * 16384 + 8192, &mW2, fb, 0, 0, (f0 >> 3) + 4 * rank, 0, colS >> 6);
                else tma3_mc(st + kABytes + rank * 16384 + 8192, &mW2n, fb, 0, (f0 ^ 1024) + 32 * rank, colK >> 6);
                if ((it >> 3) == PFKB / 8) tma3_pf(&mW2n, 0, 256 * (j8 & 3) + (it & 4) * 256 + (it & 3) * 64 + 32 * rank, colK >> 6);
            }
        }
    } else {
        asm volatile("setmaxnreg.inc.sync.aligned.u32 240;");
        const int wg = warp >> 2, w = warp & 3, r = lane >> 2, q = lane & 3, tw = tid & 127;
        uint32_t a_lo = (kSmemOrg + wg * 8192) >> 4;
        constexpr uint32_t b_lo = (kSmemOrg + kABytes) >> 4;
        const uint32_t rel_addr = mapa(bar_empty, (uint32_t)(lane & 1));
        const uint32_t gate_s = sbase + kGateOff;
        float acc[128];
        uint32_t pk[64];
        unsigned tag;
        UNDEF_R(tag);

#pragma unroll
        for (int i = 0; i < 128; ++i) UNDEF_F(acc[i]);
        {
            const uint32_t gx_s = sbase + kABytes + (16 * cb + 2 * warp + (lane >> 4)) * 128 +
                                  ((((lane & 15) >> 1) ^ (2 * w + (lane >> 4))) << 4) + (lane & 1) * 8;
            const uint32_t gw_s = sbase + kXOff + (lane & 15) * 8;
            float gs = 0.f;
            mbar_wait(bar_x, 0);
#pragma unroll 1
            for (uint32_t it = 0; it < 16; ++it) {
                KBLOCK(0, it, it == 0, it == 15);
                STAMPA(tid == 0 && it == 0, 1);
                const uint2 xa = lds64(gx_s + (it & 3) * kStageBytes), wa = lds64(gw_s + it * 128);
                const uint32_t pa = bf2_mul(xa.x, wa.x), pb = bf2_mul(xa.y, wa.y);
                gs += (bf_lo(pa) + bf_hi(pa)) + (bf_lo(pb) + bf_hi(pb));
            }
            mbar_wait(bar_c, 0);
            tag = lds32(tag_s);
#pragma unroll
            for (int o = 8; o > 0; o >>= 1) gs += __shfl_xor_sync(0xffffffffu, gs, o);
            const float g = bf16_round(__frcp_rn(1.0f + expf(-bf16_round(gs))));
            if ((lane & 15) == 0) st_relaxed64(&p.s->gate[c * 256 + (lane >> 4) + 64 * w + 4 * cb + 2 * wg], __float_as_uint(g), tag);
        }
        const uint32_t tab_s = sbase + kTabOff + tid * 16;
        const float4 k0 = lds128f(tab_s);
        TILE_END();
        STAMPA(tid == 0, 2);
#pragma unroll
        for (int s = 0; s < 64; ++s) pk[s] = pack_bf16_v(acc[4 * (s >> 1) + (s & 1)], acc[4 * (s >> 1) + 2 + (s & 1)]);
#pragma unroll
        for (int i = 0; i < 96; ++i) UNDEF_F(acc[i]);

        const float lr = k0.x, li = k0.y, m00 = k0.z, m01 = k0.w;
        float m10, m11, hr = 0.f, hi = 0.f;
        uint32_t gg[4], orr[4], oii[4];
        const int ch = cb * 64 + warp * 8 + r;
        __nv_bfloat16* hs = p.s->Hs + (size_t)ch * 2048 + c * 256 + q * 8;
#define PASS2(KB)                                                                                      \
    _Pragma("unroll") for (int s = 0; s < 64; s += 2) {                                                \
        if (pass2_kb(s) != (KB)) continue;                                                             \
        if ((s & 7) == 0) {                                                                            \
            const uint4 ga = lds128(gate_s + (q * 72 + s) * 2);                                        \
            gg[0] = ga.x; gg[1] = ga.y; gg[2] = ga.z; gg[3] = ga.w;                                    \
        }                                                                                              \
        float o0[2], o1[2];                                                                            \
        _Pragma("unroll") for (int k = 0; k < 2; ++k) {                                                \
            PIN_R(pk[s + k]);                                                                          \
            float nr = bf_lo(pk[s + k]), ni = bf_hi(pk[s + k]);                                        \
            CFMA(nr, ni, lr, li, hr, hi);                                                              \
            hr = nr; hi = ni;                                                                          \
            o0[k] = fmaf(m00, hr, m01 * hi);                                                           \
            o1[k] = fmaf(m10, hr, m11 * hi);                                                           \
        }                                                                                              \
        orr[(s >> 1) & 3] = bf2_mul(pack_bf16(o0[0], o0[1]), gg[(s >> 1) & 3]);                        \
        oii[(s >> 1) & 3] = bf2_mul(pack_bf16(o1[0], o1[1]), gg[(s >> 1) & 3]);                        \
        if ((s & 7) == 6) {                                                                            \
            stg128(hs + 32 * (s >> 3), orr[0], orr[1], orr[2], orr[3]);                                \
            stg128(hs + 1024 * 2048 + 32 * (s >> 3), oii[0], oii[1], oii[2], oii[3]);                  \
        }                                                                                              \
    }                                                                                                  \
    PIN_F(hr); PIN_F(hi);
        {
            uint4 av0, av1, gv;
            float lqr, lqi;
#pragma unroll
            for (int kb = 0; kb < 16; ++kb) {
                PIN_R(a_lo);
                KBLOCK(1, 16 + kb, kb == 0, kb == 15);
                if (kb < 4) {
#pragma unroll
                    for (int s = kb * 16; s < kb * 16 + 16; ++s) {
                        float nr = bf_lo(pk[s]), ni = bf_hi(pk[s]);
                        CFMA(nr, ni, lr, li, hr, hi);
                        hr = nr; hi = ni;
                    }
                    PIN_F(hr); PIN_F(hi);
                }
                if (kb == 2) gv = ld_relaxed2x64(&p.s->gate[c * 256 + 2 * tw]);
                if (kb == 3) {
                    const float4 k1 = lds128f(tab_s + 4096), k2 = lds128f(tab_s + 8192);
                    m10 = k1.x; m11 = k1.y; lqr = k2.z; lqi = k2.w;
                    float tr = __shfl_up_sync(0xffffffffu, hr, 1, 4), ti = __shfl_up_sync(0xffffffffu, hi, 1, 4);
                    if (q >= 1) CFMA(hr, hi, k1.z, k1.w, tr, ti);
                    tr = __shfl_up_sync(0xffffffffu, hr, 2, 4); ti = __shfl_up_sync(0xffffffffu, hi, 2, 4);
                    if (q >= 2) CFMA(hr, hi, k2.x, k2.y, tr, ti);
                    if (q == 3) st_relaxed2x64(&p.s->agg[c * 1024 + ch], __float_as_uint(hr), tag, __float_as_uint(hi), tag);
                    tr = __shfl_up_sync(0xffffffffu, hr, 1, 4); ti = __shfl_up_sync(0xffffffffu, hi, 1, 4);
                    hr = (q >= 1) ? tr : 0.f; hi = (q >= 1) ? ti : 0.f;
                }
                if (kb == 4) {
                    unsigned spins = 0;
                    while (__any_sync(0xffffffffu, gv.y != tag || gv.w != tag)) {
                        if (++spins > kSpinLimit) break;
                        gv = ld_relaxed2x64(&p.s->gate[c * 256 + 2 * tw]);
                    }
                    sts32(gate_s + ((tw >> 5) * 72 + 2 * lane) * 2, __byte_perm(gv.x, gv.z, 0x7632));
                }
                if (kb == 5) {
                    av0 = make_uint4(0, tag, 0, tag); av1 = av0;
                    if (q < c) av0 = ld_relaxed2x64(&p.s->agg[q * 1024 + ch]);
                    if (q + 4 < c) av1 = ld_relaxed2x64(&p.s->agg[(q + 4) * 1024 + ch]);
                    bar_sync(1 + wg, 128);
                }
                if (kb == 6) {
                    const float4 k3 = lds128f(tab_s + 12288);
                    unsigned spins = 0;
                    while (__any_sync(0xffffffffu, av0.y != tag || av0.w != tag || av1.y != tag || av1.w != tag)) {
                        if (++spins > kSpinLimit) break;
                        if (q < c) av0 = ld_relaxed2x64(&p.s->agg[q * 1024 + ch]);
                        if (q + 4 < c) av1 = ld_relaxed2x64(&p.s->agg[(q + 4) * 1024 + ch]);
                    }
                    float vr, vi;
                    CMUL(vr, vi, k3.x, k3.y, __uint_as_float(av0.x), __uint_as_float(av0.z));
                    CFMA(vr, vi, k3.z, k3.w, __uint_as_float(av1.x), __uint_as_float(av1.z));
                    vr += __shfl_xor_sync(0xffffffffu, vr, 1); vi += __shfl_xor_sync(0xffffffffu, vi, 1);
                    vr += __shfl_xor_sync(0xffffffffu, vr, 2); vi += __shfl_xor_sync(0xffffffffu, vi, 2);
                    CFMA(hr, hi, lqr, lqi, vr, vi);
                }
                if (kb >= 6) { PASS2(kb); }
            }
            TILE_END();
        }
        STAMPA(tid == 0, 3);
#pragma unroll
        for (int i = 0; i < 48; ++i) pk[i] = pack_bf16_v(acc[2 * i], acc[2 * i + 1]);
#pragma unroll
        for (int i = 0; i < 128; ++i) UNDEF_F(acc[i]);

        PIN_R(a_lo);
        KBLOCK(2, 32, true, false);
        PASS2(16);
        PIN_R(a_lo);
        KBLOCK(2, 33, false, false);
        PASS2(17);
        bar_arrive(3, 288);
        const uint32_t gate_row = gate_s + ((2 * (w & 1)) * 72 + 8 * (4 * rank + 2 * wg + (w >> 1)) + r) * 2;
        uint32_t om0, om1;
        {
            const float a = 1.0f - bf_lo(lds16(gate_row)), b = 1.0f - bf_lo(lds16(gate_row + 72 * 2));
            om0 = pack_bf16(a, a); om1 = pack_bf16(b, b);
        }
        __nv_bfloat16* hf = p.s->Hf + (size_t)(rb * 128 + wg * 64 + w * 16 + r) * kF + q * 8 + 2048 + 192 * j8;
        uint32_t bias_s = sbase + kBiasOff + q * 16;
#define FFN_SLICE(J)                                                                                   \
    {                                                                                                  \
        const uint4 bv = lds128(bias_s + (J) * 64);                                                    \
        const uint32_t bb[4] = {bv.x, bv.y, bv.z, bv.w};                                               \
        _Pragma("unroll") for (int jj = 0; jj < 4; ++jj) {                                             \
            const uint32_t r0 = bf2_add_relu(pk[8 * (J) + 2 * jj], bb[jj]), r1 = bf2_add_relu(pk[8 * (J) + 2 * jj + 1], bb[jj]); \
            pk[8 * (J) + 2 * jj] = bf2_mul(bf2_mul(r0, r0), om0);                                      \
            pk[8 * (J) + 2 * jj + 1] = bf2_mul(bf2_mul(r1, r1), om1);                                  \
        }                                                                                              \
        stg128(hf + 32 * (J), pk[8 * (J)], pk[8 * (J) + 2], pk[8 * (J) + 4], pk[8 * (J) + 6]);         \
        stg128(hf + 8 * kF + 32 * (J), pk[8 * (J) + 1], pk[8 * (J) + 3], pk[8 * (J) + 5], pk[8 * (J) + 7]); \
    }
        const uint32_t x_s = sbase + kXOff + (wg * 64 + w * 16 + (lane & 15)) * 128 + (((lane >> 4) ^ (lane & 7)) << 4);
        {
            uint32_t j = 0, nsl = 6;
#pragma unroll 1
            for (uint32_t it = 34; it < 88; ++it, ++j) {
                const uint32_t so = (it & 3) * (kStageBytes >> 4);
                if (wg == 1 && (it == 86 || (ORDER && it == 47))) bar_sync(7, 256);
                KB_OPEN(it, false);
                if ((it & ~15u) == 48) {
                    wgmma_fence();
                    mma_kblock<3>(acc, a_lo + so, b_lo + so, it != 48);
                    wgmma_commit();
                } else {
                    wgmma_fence();
                    mma_kblock<2>(acc, a_lo + so, b_lo + so, 1);
                    wgmma_commit();
                }
                if (wg == 0 && (it == 87 || (ORDER && it == 47))) bar_arrive(7, 256);
                KB_CLOSE(it, false, it != 48);
                if (j < nsl) {
                    if (j & 4) {
                        if (j & 2) { if (j & 1) FFN_SLICE(7) else FFN_SLICE(6) } else { if (j & 1) FFN_SLICE(5) else FFN_SLICE(4) }
                    } else {
                        if (j & 2) { if (j & 1) FFN_SLICE(3) else FFN_SLICE(2) } else { if (j & 1) FFN_SLICE(1) else FFN_SLICE(0) }
                    }
                    if (j + 1 == nsl) bar_arrive(1 + (nsl >> 1), 288);
                } else if (it == 47) {
                    hf += 64 * j8 - 2048;
                    bias_s += 6 * 64;
                    j = -1; nsl = 8;
                    TILE_END();
                    STAMPA(tid == 0, 4);
#pragma unroll
                    for (int i = 0; i < 64; ++i) pk[i] = pack_bf16_v(acc[2 * i], acc[2 * i + 1]);
                } else if ((it >> 2) == ETKB / 4) {
                    mbar_wait(bar_x, 1);
                    const uint32_t xa_s = (x_s ^ ((it & 1) << 6)) + (it & 2) * 8192;
                    const float g0 = bf_lo(lds16(gate_row)), g1 = bf_lo(lds16(gate_row + 72 * 2));
                    const float o0f = bf_lo(om0), o1f = bf_lo(om1);
                    const uint4 dq = lds128(bias_s + (8 + (it & 3)) * 64), bq = lds128(bias_s + (12 + (it & 3)) * 64);
                    const uint4 xa = ldsm4(xa_s), xb = ldsm4(xa_s ^ 32);
                    const uint32_t dv[4] = {dq.x, dq.y, dq.z, dq.w}, bv2[4] = {bq.x, bq.y, bq.z, bq.w};
                    uint32_t xv[8] = {xa.x, xa.y, xa.z, xa.w, xb.x, xb.y, xb.z, xb.w};
#pragma unroll
                    for (int jj = 0; jj < 4; ++jj) {
                        const uint32_t x0 = bf2_mul(xv[2 * jj], dv[jj]), x1 = bf2_mul(xv[2 * jj + 1], dv[jj]);
                        const float bl = bf_lo(bv2[jj]), bh = bf_hi(bv2[jj]);
                        xv[2 * jj] = pack_bf16(fmaf(g0, bf_lo(x0), o0f * bl), fmaf(g0, bf_hi(x0), o0f * bh));
                        xv[2 * jj + 1] = pack_bf16(fmaf(g1, bf_lo(x1), o1f * bl), fmaf(g1, bf_hi(x1), o1f * bh));
                    }
                    sts128(xa_s, xv[0], xv[1], xv[2], xv[3]);
                    sts128(xa_s ^ 32, xv[4], xv[5], xv[6], xv[7]);
                }
            }
        }
#define TAIL_MMA(T)                                                                                    \
    {                                                                                                  \
        PIN_R(a_lo);                                                                                   \
        wgmma_fence();                                                                                 \
        mma_kblock<4>(acc, a_lo + (T) * (kStageBytes >> 4), b_lo + (T) * (kStageBytes >> 4), 1);       \
        _Pragma("unroll") for (int kk = 0; kk < 4; ++kk)                                               \
            wgmma_n128_rs(acc, pk[16 * (T) + 4 * kk], pk[16 * (T) + 4 * kk + 1], pk[16 * (T) + 4 * kk + 2], pk[16 * (T) + 4 * kk + 3], \
                          kDescHi | (uint64_t)(b_lo + (((T) * kStageBytes + 8192 + (kk >> 1) * 16384 + (kk & 1) * 2048) >> 4) + (256u << 16))); \
        wgmma_commit();                                                                                \
    }
        TILE_END();
        sched_fence(a_lo);
        {
            const uint8_t* xi = p.s->X + (size_t)(role * 2 + rank) * kXBytes + tid * 16;
            uint8_t* xo = const_cast<uint8_t*>(xi) + (kh ? -8 * kXBytes : 8 * kXBytes);
            uint4 rx[8], ev[8];
            uint32_t rs;
#define RXLOAD()                                                                                       \
    {                                                                                                  \
        rs = ld_relaxed32((const unsigned*)(xi + 32768 - tid * 12));                                   \
        _Pragma("unroll") for (int u = 0; u < 8; ++u) rx[u] = ld_relaxed2x64(xi + u * 4096);           \
    }
            {
                STAMP(tid == 0, 15); STAMPB(tid == 128, 1);
                float m[4] = {0.f, 0.f, 0.f, 0.f};
#pragma unroll
                for (int i = 64; i < 128; ++i) m[i & 3] = fmaxf(m[i & 3], fabsf(acc[i]));
                const uint32_t eb = max(__float_as_uint(fmaxf(fmaxf(m[0], m[1]), fmaxf(m[2], m[3]))) >> 23, 15u);
                const float xsc = __uint_as_float((268u - eb) << 23);
                st_relaxed32(xo + 32768 - tid * 12, (eb - 14u) << 23);
#pragma unroll
                for (int u = 0; u < 8; ++u) {
                    const int v = 64 + 8 * u;
                    st_relaxed2x64(xo + u * 4096, pack_f16(acc[v] * xsc, acc[v + 1] * xsc) | 1, pack_f16(acc[v + 2] * xsc, acc[v + 3] * xsc),
                                   pack_f16(acc[v + 4] * xsc, acc[v + 5] * xsc) | 1, pack_f16(acc[v + 6] * xsc, acc[v + 7] * xsc));
                }
                STAMP(tid == 0, 12); STAMPB(tid == 128, 2);
            }
            mbar_wait(bar_full, 0);
            TAIL_MMA(0);
            mbar_wait(bar_full + 8, 0);
            TAIL_MMA(1);
            if (wg == 1) bar_arrive(8, 256);
#pragma unroll
            for (int u = 0; u < 8; ++u) ev[u] = lds128((x_s ^ ((u & 3) << 5)) + (u >> 2) * 16384);
            if (wg == 1) mbar_wait(bar_full + 24, 0);
            bar_sync(8 + wg, 256);
            STAMPB(tid == 0, 9);
            RXLOAD();
            mbar_wait(bar_full + 16, 0);
            STAMPB(tid == 0, 10);
            STAMPB(tid == 128, 3);
            TAIL_MMA(2);
            if (wg == 0) mbar_wait(bar_full + 24, 0);
            STAMPB(tid == 0, 11);
            TAIL_MMA(3);
            if (wg == 0) bar_arrive(9, 256);
            sched_fence(a_lo);
            unsigned spins = 0;
#pragma unroll 1
            while (true) {
                uint32_t ok = rs != 0;
#pragma unroll
                for (int u = 0; u < 8; ++u) ok &= rx[u].x & rx[u].z;
                if (__all_sync(0xffffffffu, ok) || ++spins > kSpinLimit) break;
                RXLOAD();
                RESPIN();
            }
            STAMP(tid == 0, 13);
            const float xsc = __uint_as_float(rs);
#pragma unroll
            for (int u = 0; u < 8; ++u) {
                const uint32_t rr[4] = {rx[u].x, rx[u].y, rx[u].z, rx[u].w}, ee[4] = {ev[u].x, ev[u].y, ev[u].z, ev[u].w};
#pragma unroll
                for (int k = 0; k < 4; ++k) {
                    const int v = 64 + 8 * u + 2 * k;
                    const float2 f = __half22float2(*reinterpret_cast<const __half2*>(&rr[k]));
                    acc[v] = fmaf(f.x, xsc, bf_lo(ee[k])); acc[v + 1] = fmaf(f.y, xsc, bf_hi(ee[k]));
                    PIN_F(acc[v]); PIN_F(acc[v + 1]);
                }
            }
            sched_fence(a_lo);
            STAMP(tid == 0, 14);
        }
        wgmma_wait<0>();
        STAMP(tid == 0, 6); STAMPB(tid == 128, 4);
        {
            const bool odd = q & 1;
            const int tb = c * 256 + 128 * (w & 1) + 8 * (4 * rank + 2 * wg + (w >> 1));
            float* o0 = p.out + (size_t)(tb + r) * kD + colK + (odd ? 2 * q + 6 : 2 * q);
#pragma unroll
            for (int i = 0; i < 16; i += 2) {
#pragma unroll
                for (int h = 0; h < 2; ++h) {
                    const int va = 4 * i + 2 * h, vb = va + 4;
                    PIN_F(acc[va]); PIN_F(acc[va + 1]); PIN_F(acc[vb]); PIN_F(acc[vb + 1]);
                    const float a0 = acc[va] + acc[64 + va], a1 = acc[va + 1] + acc[65 + va];
                    const float b0 = acc[vb] + acc[64 + vb], b1 = acc[vb + 1] + acc[65 + vb];
                    const float t0 = __shfl_xor_sync(0xffffffffu, odd ? a0 : b0, 1), t1 = __shfl_xor_sync(0xffffffffu, odd ? a1 : b1, 1);
                    stg128f(o0 + h * 64 * kD + 8 * i, odd ? t0 : a0, odd ? t1 : a1, odd ? b0 : t0, odd ? b1 : t1);
                }
            }
        }
        STAMP(tid == 0, 7);
        STAMP(tid == 128, 5);
    }
}

typedef CUresult (*EncodeFn)(CUtensorMap*, CUtensorMapDataType, cuuint32_t, void*, const cuuint64_t*, const cuuint64_t*,
                             const cuuint32_t*, const cuuint32_t*, CUtensorMapInterleave, CUtensorMapSwizzle,
                             CUtensorMapL2promotion, CUtensorMapFloatOOBfill);

bool encode(EncodeFn fn, CUtensorMap* m, const void* base, int rank, const cuuint64_t* dims, const cuuint64_t* strides,
            const cuuint32_t* box) {
    cuuint32_t es[5] = {1, 1, 1, 1, 1};
    return fn(m, CU_TENSOR_MAP_DATA_TYPE_BFLOAT16, rank, const_cast<void*>(base), dims, strides, box, es,
              CU_TENSOR_MAP_INTERLEAVE_NONE, CU_TENSOR_MAP_SWIZZLE_128B, CU_TENSOR_MAP_L2_PROMOTION_L2_256B,
              CU_TENSOR_MAP_FLOAT_OOB_FILL_NONE) == CUDA_SUCCESS;
}

}

extern "C" void kernel_launch(void* const* d_in, const int* in_sizes, int n_in, void* d_out, int out_size) {
    (void)in_sizes; (void)n_in; (void)out_size;
    typedef const __nv_bfloat16* bp;
    bp x = (bp)d_in[0], lam_re = (bp)d_in[1], lam_im = (bp)d_in[2], B_re = (bp)d_in[3], B_im = (bp)d_in[4];
    bp C_re = (bp)d_in[5], C_im = (bp)d_in[6], log_dt = (bp)d_in[7], dskip = (bp)d_in[8];
    bp w1 = (bp)d_in[10], b1 = (bp)d_in[11], w2 = (bp)d_in[12], b2 = (bp)d_in[13], gate_w = (bp)d_in[14];

    static EncodeFn fn = nullptr;
    static Scratch* ps = nullptr;
    if (!fn) {
        void* f = nullptr;
        cudaDriverEntryPointQueryResult qr;
        cudaGetDriverEntryPoint("cuTensorMapEncodeTiled", &f, cudaEnableDefault, &qr);
        fn = (EncodeFn)f;
        cudaGetSymbolAddress((void**)&ps, g_s);
        cudaFuncSetAttribute(fused_kernel, cudaFuncAttributeMaxDynamicSharedMemorySize, kSmemBytes);
    }
    cudaStream_t stream = cudaStreamPerThread;

    Params p;
    p.x = x; p.lam_re = lam_re; p.lam_im = lam_im; p.log_dt = log_dt; p.dskip = dskip; p.b1 = b1; p.b2 = b2;
    p.gate_w = gate_w; p.b_re = B_re; p.b_im = B_im; p.out = (float*)d_out; p.s = ps;
    char* const pHs = (char*)ps + offsetof(Scratch, Hs);
    char* const pHf = (char*)ps + offsetof(Scratch, Hf);
    char* const pBc = (char*)ps + offsetof(Scratch, Bcopy);

    const char* lo = (const char*)B_re; const char* hi = (const char*)B_im;
    p.swap = 0;
    if (hi < lo) { const char* t = lo; lo = hi; hi = t; p.swap = 1; }
    unsigned long long diff = (unsigned long long)(hi - lo);
    if (diff >= (1ull << 40) || (diff & 15) || diff == 0) {
        cudaMemcpyAsync(pBc, B_re, 2u << 20, cudaMemcpyDeviceToDevice, stream);
        cudaMemcpyAsync((char*)pBc + (2u << 20), B_im, 2u << 20, cudaMemcpyDeviceToDevice, stream);
        lo = (const char*)pBc; diff = 2u << 20; p.swap = 0;
    }

    CUtensorMap mB, mXs, mXf, mW1a, mW1b, mHs, mHf, mCre, mCim, mW2, mW2n;
    bool ok = true;
    { cuuint64_t d[4] = {1024, 8, 2, 128}, s[3] = {2048, diff, 16384}; cuuint32_t b[4] = {64, 8, 2, 8};
      ok &= encode(fn, &mB, lo, 4, d, s, b); }
    { cuuint64_t d[5] = {1024, 2, 4, 32, 8}, s[4] = {2048, 64 * 2048, 2 * 2048, 256 * 2048}; cuuint32_t b[5] = {64, 2, 4, 16, 1};
      ok &= encode(fn, &mXs, x, 5, d, s, b); }
    { cuuint64_t d[5] = {1024, 8, 4, 8, 8}, s[4] = {2048, 64 * 2048, 8 * 2048, 256 * 2048}; cuuint32_t b[5] = {64, 8, 4, 4, 1};
      ok &= encode(fn, &mXf, x, 5, d, s, b); }
    { cuuint64_t d[3] = {64, 1024, 56}, s[2] = {7168, 128}; cuuint32_t ba[3] = {64, 32, 4}, bb[3] = {64, 32, 3};
      ok &= encode(fn, &mW1a, w1, 3, d, s, ba); ok &= encode(fn, &mW1b, w1, 3, d, s, bb); }
    { cuuint64_t d[3] = {64, 2048, 32}, s[2] = {4096, 128}; cuuint32_t b[3] = {64, 64, 2};
      ok &= encode(fn, &mHs, pHs, 3, d, s, b); }
    { cuuint64_t d[2] = {3584, 2048}, s[1] = {7168}; cuuint32_t b[2] = {64, 128};
      ok &= encode(fn, &mHf, pHf, 2, d, s, b); }
    { cuuint64_t d[2] = {1024, 1024}, s[1] = {2048}; cuuint32_t b[2] = {64, 128};
      ok &= encode(fn, &mCre, C_re, 2, d, s, b); ok &= encode(fn, &mCim, C_im, 2, d, s, b); }
    { cuuint64_t d[5] = {64, 2, 448, 4, 16}, s[4] = {2048, 8 * 2048, 2 * 2048, 128}; cuuint32_t b[5] = {64, 2, 4, 4, 2};
      ok &= encode(fn, &mW2, w2, 5, d, s, b); }
    { cuuint64_t d[3] = {64, 3584, 16}, s[2] = {2048, 128}; cuuint32_t b[3] = {64, 32, 2};
      ok &= encode(fn, &mW2n, w2, 3, d, s, b); }
    if (!ok) return;

    fused_kernel<<<128, 384, kSmemBytes, stream>>>(mB, mXs, mXf, mW1b, mW1a, mHs, mHf, mCre, mCim, mW2, mW2n, p);
}
```

```cpp
#include <cuda_runtime.h>
#include <cuda_bf16.h>
#include <cuda_fp16.h>
#include <cuda.h>
#include <stdint.h>
#include <stddef.h>

#define XLDKB 40
#define PF0LINES 1
#define ETKB 60
#define PFKB 80
#define RXT 2
#define MC0 0
#define PFTOP 0
#define INITW 0
#define PRODCOND warp >= 8
#define ORDER 0

namespace {

constexpr int kD = 1024, kF = 3584;
constexpr int kStages = 4;
constexpr int kStageBytes = 49152;
constexpr int kABytes = 16384;
constexpr int kXOff = kStages * kStageBytes;
constexpr int kTabOff = kXOff + 2048;
constexpr int kGateOff = kXOff + 32768;
constexpr int kBiasOff = kGateOff + 4 * 72 * 2;
constexpr int kBarOff = kBiasOff + 88 * 16;
constexpr int kSmemBytes = 232448;
static_assert(kBarOff + 160 <= kSmemBytes, "smem");
constexpr int kXBytes = 33792;
constexpr uint32_t kSmemOrg = 1024;
constexpr unsigned kSpinLimit = 1u << 18;
constexpr int kTotal = 90;

__host__ __device__ constexpr int pass2_kb(int s) {
    return s < 2 ? 6 : s < 8 ? 7 : s < 12 ? 8 : s < 18 ? 9 : s < 22 ? 10 : s < 28 ? 11 : s < 32 ? 12 : s < 38 ? 13 : s < 42 ? 14 : s < 48 ? 15 : s < 56 ? 16 : 17;
}

struct Scratch {
    unsigned claim[64];
    unsigned epoch, pad0[31];
    unsigned done, pad1[31];
    unsigned cnt[40 * 32];
    uint2 gate[2048];
    uint4 agg[8 * 1024];
    __align__(1024) uint8_t X[128 * kXBytes];
    __align__(1024) __nv_bfloat16 Hs[2048 * 2048];
    __align__(1024) __nv_bfloat16 Hf[2048 * 3584];
    __align__(1024) __nv_bfloat16 Bcopy[2 * 1024 * 1024];
};
__device__ Scratch g_s;

#define TRAP() break
#define PIN_F(x) asm volatile("" : "+f"(x))
#define PIN_R(x) asm volatile("" : "+r"(x))
#define UNDEF_F(x) asm volatile("" : "=f"(x))
#define UNDEF_R(x) asm volatile("" : "=r"(x))
#define RESPIN()
__device__ __forceinline__ uint32_t smem_u32(const void* p) { return (uint32_t)__cvta_generic_to_shared(p); }
__device__ __forceinline__ void mbar_init(uint32_t bar, uint32_t count) {
    asm volatile("mbarrier.init.shared::cta.b64 [%0], %1;" ::"r"(bar), "r"(count) : "memory");
}
__device__ __forceinline__ void mbar_expect_tx(uint32_t bar, uint32_t bytes) {
    asm volatile("mbarrier.arrive.expect_tx.shared::cta.b64 _, [%0], %1;" ::"r"(bar), "r"(bytes) : "memory");
}
__device__ __forceinline__ void mbar_wait(uint32_t bar, uint32_t parity) {
    asm volatile(
        "{\n.reg .pred p;\n.reg .u32 n;\n"
        "mbarrier.try_wait.parity.shared::cta.b64 p, [%0], %1;\n"
        "@p bra DONE;\n"
        "mov.u32 n, 0;\n"
        "LOOP:\n"
        "mbarrier.try_wait.parity.shared::cta.b64 p, [%0], %1;\n"
        "@p bra DONE;\n"
        "add.u32 n, n, 1;\n"
        "setp.lt.u32 p, n, %2;\n"
        "@p bra LOOP;\n"
        "DONE:\n}\n"
        ::"r"(bar), "r"(parity), "n"(kSpinLimit) : "memory");
}
__device__ __forceinline__ void sched_fence(uint32_t nonzero) {
    asm volatile("{\n.reg .pred p;\n.reg .u32 n;\nsetp.ne.u32 p, %0, 0;\n@p bra DONE;\nLOOP:\nmov.u32 n, %%clock;\n"
                 "setp.eq.u32 p, n, 0;\n@p bra LOOP;\nDONE:\n}\n" ::"r"(nonzero) : "memory");
}
__device__ __forceinline__ void mbar_arrive_local(uint32_t bar) {
    asm volatile("mbarrier.arrive.shared::cta.b64 _, [%0];" ::"r"(bar) : "memory");
}
__device__ __forceinline__ void mbar_arrive_cluster(uint32_t cluster_addr) {
    asm volatile("mbarrier.arrive.shared::cluster.b64 _, [%0];" ::"r"(cluster_addr) : "memory");
}
__device__ __forceinline__ uint32_t mapa(uint32_t addr, uint32_t rank) {
    uint32_t r;
    asm("mapa.shared::cluster.u32 %0, %1, %2;" : "=r"(r) : "r"(addr), "r"(rank));
    return r;
}
__device__ __forceinline__ void cluster_arrive() { asm volatile("barrier.cluster.arrive.relaxed.aligned;" ::: "memory"); }
__device__ __forceinline__ void cluster_wait() { asm volatile("barrier.cluster.wait.acquire.aligned;" ::: "memory"); }
__device__ __forceinline__ void bar_sync(int id, int n) { asm volatile("bar.sync %0, %1;" ::"r"(id), "r"(n) : "memory"); }
__device__ __forceinline__ void bar_arrive(int id, int n) { asm volatile("bar.arrive %0, %1;" ::"r"(id), "r"(n) : "memory"); }
__device__ __forceinline__ bool elect_one() {
    uint32_t p;
    asm volatile("{\n.reg .pred P;\nelect.sync _|P, 0xffffffff;\nselp.u32 %0, 1, 0, P;\n}\n" : "=r"(p));
    return p != 0;
}

__device__ __forceinline__ void tma2(uint32_t dst, const CUtensorMap* m, uint32_t bar, int c0, int c1) {
    asm volatile("cp.async.bulk.tensor.2d.shared::cluster.global.mbarrier::complete_tx::bytes [%0], [%1, {%3, %4}], [%2];"
                 ::"r"(dst), "l"(m), "r"(bar), "r"(c0), "r"(c1) : "memory");
}
__device__ __forceinline__ void tma3(uint32_t dst, const CUtensorMap* m, uint32_t bar, int c0, int c1, int c2) {
    asm volatile("cp.async.bulk.tensor.3d.shared::cluster.global.mbarrier::complete_tx::bytes [%0], [%1, {%3, %4, %5}], [%2];"
                 ::"r"(dst), "l"(m), "r"(bar), "r"(c0), "r"(c1), "r"(c2) : "memory");
}
__device__ __forceinline__ void tma4(uint32_t dst, const CUtensorMap* m, uint32_t bar, int c0, int c1, int c2, int c3) {
    asm volatile("cp.async.bulk.tensor.4d.shared::cluster.global.mbarrier::complete_tx::bytes [%0], [%1, {%3, %4, %5, %6}], [%2];"
                 ::"r"(dst), "l"(m), "r"(bar), "r"(c0), "r"(c1), "r"(c2), "r"(c3) : "memory");
}
__device__ __forceinline__ void tma5(uint32_t dst, const CUtensorMap* m, uint32_t bar, int c0, int c1, int c2, int c3, int c4) {
    asm volatile("cp.async.bulk.tensor.5d.shared::cluster.global.mbarrier::complete_tx::bytes [%0], [%1, {%3, %4, %5, %6, %7}], [%2];"
                 ::"r"(dst), "l"(m), "r"(bar), "r"(c0), "r"(c1), "r"(c2), "r"(c3), "r"(c4) : "memory");
}
__device__ __forceinline__ void tma2_mc(uint32_t dst, const CUtensorMap* m, uint32_t bar, int c0, int c1) {
    asm volatile("cp.async.bulk.tensor.2d.shared::cluster.global.mbarrier::complete_tx::bytes.multicast::cluster [%0], [%1, {%3, %4}], [%2], %5;"
                 ::"r"(dst), "l"(m), "r"(bar), "r"(c0), "r"(c1), "h"((uint16_t)3) : "memory");
}
__device__ __forceinline__ void tma3_mc(uint32_t dst, const CUtensorMap* m, uint32_t bar, int c0, int c1, int c2) {
    asm volatile("cp.async.bulk.tensor.3d.shared::cluster.global.mbarrier::complete_tx::bytes.multicast::cluster [%0], [%1, {%3, %4, %5}], [%2], %6;"
                 ::"r"(dst), "l"(m), "r"(bar), "r"(c0), "r"(c1), "r"(c2), "h"((uint16_t)3) : "memory");
}
__device__ __forceinline__ void tma5_mc(uint32_t dst, const CUtensorMap* m, uint32_t bar, int c0, int c1, int c2, int c3, int c4) {
    asm volatile("cp.async.bulk.tensor.5d.shared::cluster.global.mbarrier::complete_tx::bytes.multicast::cluster [%0], [%1, {%3, %4, %5, %6, %7}], [%2], %8;"
                 ::"r"(dst), "l"(m), "r"(bar), "r"(c0), "r"(c1), "r"(c2), "r"(c3), "r"(c4), "h"((uint16_t)3) : "memory");
}
__device__ __forceinline__ void tma3_pf(const CUtensorMap* m, int c0, int c1, int c2) {
    asm volatile("cp.async.bulk.prefetch.tensor.3d.L2.global [%0, {%1, %2, %3}];" ::"l"(m), "r"(c0), "r"(c1), "r"(c2) : "memory");
}
__device__ __forceinline__ void bulk_store(void* dst, uint32_t src, uint32_t bytes) {
    asm volatile("cp.async.bulk.global.shared::cta.bulk_group [%0], [%1], %2;" ::"l"(dst), "r"(src), "r"(bytes) : "memory");
}
__device__ __forceinline__ void bulk_load(uint32_t dst, const void* src, uint32_t bytes, uint32_t bar) {
    asm volatile("cp.async.bulk.shared::cluster.global.mbarrier::complete_tx::bytes [%0], [%1], %2, [%3];"
                 ::"r"(dst), "l"(src), "r"(bytes), "r"(bar) : "memory");
}
__device__ __forceinline__ unsigned atom_exch(unsigned* p, unsigned v) {
    unsigned r;
    asm volatile("atom.relaxed.gpu.global.exch.b32 %0, [%1], %2;" : "=r"(r) : "l"(p), "r"(v) : "memory");
    return r;
}
__device__ __forceinline__ void st_async32(uint32_t a, uint32_t v, uint32_t bar) {
    asm volatile("st.async.shared::cluster.mbarrier::complete_tx::bytes.u32 [%0], %1, [%2];" ::"r"(a), "r"(v), "r"(bar) : "memory");
}
__device__ __forceinline__ void sts128f(uint32_t a, float x, float y, float z, float w) {
    asm volatile("st.shared.v4.f32 [%0], {%1, %2, %3, %4};" ::"r"(a), "f"(x), "f"(y), "f"(z), "f"(w) : "memory");
}
__device__ __forceinline__ void prefetch_map(const CUtensorMap* m) {
    asm volatile("prefetch.tensormap [%0];" ::"l"(m) : "memory");
}

__device__ __forceinline__ void prefetch_l2(const void* p, uint32_t bytes) {
    asm volatile("cp.async.bulk.prefetch.L2.global [%0], %1;" ::"l"(p), "r"(bytes) : "memory");
}

__device__ __forceinline__ void wgmma_fence() { asm volatile("wgmma.fence.sync.aligned;" ::: "memory"); }
__device__ __forceinline__ void wgmma_commit() { asm volatile("wgmma.commit_group.sync.aligned;" ::: "memory"); }
template <int N>
__device__ __forceinline__ void wgmma_wait() { asm volatile("wgmma.wait_group.sync.aligned %0;" ::"n"(N) : "memory"); }

__device__ __forceinline__ uint32_t pack_bf16(float lo, float hi) {
    uint32_t r;
    asm("cvt.rn.bf16x2.f32 %0, %1, %2;" : "=r"(r) : "f"(hi), "f"(lo));
    return r;
}
__device__ __forceinline__ uint32_t pack_f16(float lo, float hi) {
    uint32_t r;
    asm("cvt.rn.f16x2.f32 %0, %1, %2;" : "=r"(r) : "f"(hi), "f"(lo));
    return r;
}
__device__ __forceinline__ uint32_t pack_bf16_v(float lo, float hi) {
    uint32_t r;
    asm volatile("cvt.rn.bf16x2.f32 %0, %1, %2;" : "=r"(r) : "f"(hi), "f"(lo));
    return r;
}
template <int LUT>
__device__ __forceinline__ uint32_t lop3(uint32_t a, uint32_t b, uint32_t c) {
    uint32_t r;
    asm("lop3.b32 %0, %1, %2, %3, %4;" : "=r"(r) : "r"(a), "r"(b), "r"(c), "n"(LUT));
    return r;
}
__device__ __forceinline__ void xor_swap(uint32_t& a, uint32_t& b) {
    asm volatile("xor.b32 %0, %0, %1;\nxor.b32 %1, %0, %1;\nxor.b32 %0, %0, %1;" : "+r"(a), "+r"(b));
}
__device__ __forceinline__ float bf_lo(uint32_t v) { return __uint_as_float(v << 16); }
__device__ __forceinline__ float bf_hi(uint32_t v) { return __uint_as_float(v & 0xffff0000u); }
__device__ __forceinline__ float bf16_round(float v) { return __bfloat162float(__float2bfloat16_rn(v)); }
__device__ __forceinline__ uint32_t bf2_mul(uint32_t a, uint32_t b) {
    uint32_t r;
    asm("mul.rn.bf16x2 %0, %1, %2;" : "=r"(r) : "r"(a), "r"(b));
    return r;
}
__device__ __forceinline__ uint32_t bf2_add_relu(uint32_t a, uint32_t b) {
    uint32_t r;
    asm("fma.rn.relu.bf16x2 %0, %1, %2, %3;" : "=r"(r) : "r"(a), "r"(0x3f803f80u), "r"(b));
    return r;
}
__device__ __forceinline__ uint4 ldg128(const void* p) {
    uint4 v;
    asm volatile("ld.global.nc.v4.u32 {%0, %1, %2, %3}, [%4];" : "=r"(v.x), "=r"(v.y), "=r"(v.z), "=r"(v.w) : "l"(p));
    return v;
}
__device__ __forceinline__ uint32_t ldg32(const void* p) {
    uint32_t v;
    asm volatile("ld.global.nc.u32 %0, [%1];" : "=r"(v) : "l"(p));
    return v;
}
__device__ __forceinline__ uint32_t ldg32na(const void* p) {
    uint32_t v;
    asm volatile("ld.global.nc.L1::no_allocate.u32 %0, [%1];" : "=r"(v) : "l"(p));
    return v;
}
__device__ __forceinline__ uint32_t ldg16(const __nv_bfloat16* p) {
    uint32_t v;
    asm volatile("ld.global.nc.u16 %0, [%1];" : "=r"(v) : "l"(p));
    return v;
}
__device__ __forceinline__ uint4 ld_relaxed128(const void* p) {
    uint4 v;
    asm volatile("ld.relaxed.gpu.global.v4.u32 {%0, %1, %2, %3}, [%4];" : "=r"(v.x), "=r"(v.y), "=r"(v.z), "=r"(v.w) : "l"(p) : "memory");
    return v;
}
__device__ __forceinline__ uint2 ld_relaxed64(const void* p) {
    unsigned long long v;
    asm volatile("ld.relaxed.gpu.global.u64 %0, [%1];" : "=l"(v) : "l"(p) : "memory");
    return make_uint2((uint32_t)v, (uint32_t)(v >> 32));
}
__device__ __forceinline__ void st_relaxed64(void* p, uint32_t lo, uint32_t hi) {
    unsigned long long v = ((unsigned long long)hi << 32) | lo;
    asm volatile("st.relaxed.gpu.global.u64 [%0], %1;" ::"l"(p), "l"(v) : "memory");
}
__device__ __forceinline__ void st_relaxed2x64(void* p, uint32_t a, uint32_t b, uint32_t c, uint32_t d) {
    unsigned long long v0 = ((unsigned long long)b << 32) | a, v1 = ((unsigned long long)d << 32) | c;
    asm volatile("st.relaxed.gpu.global.v2.u64 [%0], {%1, %2};" ::"l"(p), "l"(v0), "l"(v1) : "memory");
}
__device__ __forceinline__ uint4 ld_relaxed2x64(const void* p) {
    unsigned long long v0, v1;
    asm volatile("ld.relaxed.gpu.global.v2.u64 {%0, %1}, [%2];" : "=l"(v0), "=l"(v1) : "l"(p) : "memory");
    return make_uint4((uint32_t)v0, (uint32_t)(v0 >> 32), (uint32_t)v1, (uint32_t)(v1 >> 32));
}
__device__ __forceinline__ void stg128(void* p, uint32_t a, uint32_t b, uint32_t c, uint32_t d) {
    asm volatile("st.global.v4.u32 [%0], {%1, %2, %3, %4};" ::"l"(p), "r"(a), "r"(b), "r"(c), "r"(d) : "memory");
}
__device__ __forceinline__ void stg64f(void* p, float a, float b) {
    asm volatile("st.global.v2.f32 [%0], {%1, %2};" ::"l"(p), "f"(a), "f"(b) : "memory");
}
__device__ __forceinline__ uint4 lds128(uint32_t a) {
    uint4 v;
    asm volatile("ld.shared.v4.u32 {%0, %1, %2, %3}, [%4];" : "=r"(v.x), "=r"(v.y), "=r"(v.z), "=r"(v.w) : "r"(a) : "memory");
    return v;
}
__device__ __forceinline__ uint2 lds64(uint32_t a) {
    uint2 v;
    asm volatile("ld.shared.v2.u32 {%0, %1}, [%2];" : "=r"(v.x), "=r"(v.y) : "r"(a) : "memory");
    return v;
}
__device__ __forceinline__ uint4 ldsm4(uint32_t a) {
    uint4 v;
    asm volatile("ldmatrix.sync.aligned.m8n8.x4.shared.b16 {%0, %1, %2, %3}, [%4];" : "=r"(v.x), "=r"(v.y), "=r"(v.z), "=r"(v.w) : "r"(a) : "memory");
    return v;
}
__device__ __forceinline__ uint32_t lds16(uint32_t a) {
    uint32_t v;
    asm volatile("ld.shared.u16 %0, [%1];" : "=r"(v) : "r"(a) : "memory");
    return v;
}
__device__ __forceinline__ void sts16(uint32_t a, uint32_t x) {
    asm volatile("st.shared.u16 [%0], %1;" ::"r"(a), "h"((uint16_t)x) : "memory");
}
__device__ __forceinline__ void st_relaxed32(void* p, uint32_t v) {
    asm volatile("st.relaxed.gpu.global.u32 [%0], %1;" ::"l"(p), "r"(v) : "memory");
}
__device__ __forceinline__ float lds32f(uint32_t a) {
    float v;
    asm volatile("ld.shared.f32 %0, [%1];" : "=f"(v) : "r"(a) : "memory");
    return v;
}
__device__ __forceinline__ void sts128(uint32_t a, uint32_t x, uint32_t y, uint32_t z, uint32_t w) {
    asm volatile("st.shared.v4.u32 [%0], {%1, %2, %3, %4};" ::"r"(a), "r"(x), "r"(y), "r"(z), "r"(w) : "memory");
}
__device__ __forceinline__ void sts64f(uint32_t a, float x, float y) {
    asm volatile("st.shared.v2.f32 [%0], {%1, %2};" ::"r"(a), "f"(x), "f"(y) : "memory");
}
__device__ __forceinline__ float4 lds128f(uint32_t a) {
    float4 v;
    asm volatile("ld.shared.v4.f32 {%0, %1, %2, %3}, [%4];" : "=f"(v.x), "=f"(v.y), "=f"(v.z), "=f"(v.w) : "r"(a) : "memory");
    return v;
}
__device__ __forceinline__ uint32_t lds32(uint32_t a) {
    uint32_t v;
    asm volatile("ld.shared.u32 %0, [%1];" : "=r"(v) : "r"(a) : "memory");
    return v;
}
__device__ __forceinline__ void sts32(uint32_t a, uint32_t x) {
    asm volatile("st.shared.u32 [%0], %1;" ::"r"(a), "r"(x) : "memory");
}
__device__ __forceinline__ void stg128f(void* p, float a, float b, float c, float d) {
    asm volatile("st.global.v4.f32 [%0], {%1, %2, %3, %4};" ::"l"(p), "f"(a), "f"(b), "f"(c), "f"(d) : "memory");
}
__device__ __forceinline__ unsigned ld_relaxed32(const unsigned* p) {
    unsigned v;
    asm volatile("ld.relaxed.gpu.global.u32 %0, [%1];" : "=r"(v) : "l"(p) : "memory");
    return v;
}
__device__ __forceinline__ void wait_counter(const unsigned* p, unsigned target) {
    unsigned n = 0, v;
    while (true) {
        asm volatile("ld.acquire.gpu.global.u32 %0, [%1];" : "=r"(v) : "l"(p) : "memory");
        if ((int)(v - target) >= 0) break;
        if (++n > kSpinLimit) TRAP();
        __nanosleep(32);
    }
}
#define KT(IT, W) do { } while (0)
#define STAMP(cond, slot) do { } while (0)
#define STAMPA(cond, slot) STAMP(cond, slot)
#define STAMPB(cond, slot) do { } while (0)

template <int TA, int TB>
__device__ __forceinline__ void wgmma_n256(float (&d)[128], uint64_t da, uint64_t db, int keep) {
    asm volatile(
        "{\n.reg .pred p;\nsetp.ne.b32 p, %132, 0;\n"
        "wgmma.mma_async.sync.aligned.m64n256k16.f32.bf16.bf16 "
        "{%0, %1, %2, %3, %4, %5, %6, %7, %8, %9, %10, %11, %12, %13, %14, %15, "
        "%16, %17, %18, %19, %20, %21, %22, %23, %24, %25, %26, %27, %28, %29, %30, %31, "
        "%32, %33, %34, %35, %36, %37, %38, %39, %40, %41, %42, %43, %44, %45, %46, %47, "
        "%48, %49, %50, %51, %52, %53, %54, %55, %56, %57, %58, %59, %60, %61, %62, %63, "
        "%64, %65, %66, %67, %68, %69, %70, %71, %72, %73, %74, %75, %76, %77, %78, %79, "
        "%80, %81, %82, %83, %84, %85, %86, %87, %88, %89, %90, %91, %92, %93, %94, %95, "
        "%96, %97, %98, %99, %100, %101, %102, %103, %104, %105, %106, %107, %108, %109, %110, %111, "
        "%112, %113, %114, %115, %116, %117, %118, %119, %120, %121, %122, %123, %124, %125, %126, %127}, "
        "%128, %129, p, 1, 1, %130, %131;\n}\n"
        : "+f"(d[0]), "+f"(d[1]), "+f"(d[2]), "+f"(d[3]), "+f"(d[4]), "+f"(d[5]), "+f"(d[6]), "+f"(d[7]),
          "+f"(d[8]), "+f"(d[9]), "+f"(d[10]), "+f"(d[11]), "+f"(d[12]), "+f"(d[13]), "+f"(d[14]), "+f"(d[15]),
          "+f"(d[16]), "+f"(d[17]), "+f"(d[18]), "+f"(d[19]), "+f"(d[20]), "+f"(d[21]), "+f"(d[22]), "+f"(d[23]),
          "+f"(d[24]), "+f"(d[25]), "+f"(d[26]), "+f"(d[27]), "+f"(d[28]), "+f"(d[29]), "+f"(d[30]), "+f"(d[31]),
          "+f"(d[32]), "+f"(d[33]), "+f"(d[34]), "+f"(d[35]), "+f"(d[36]), "+f"(d[37]), "+f"(d[38]), "+f"(d[39]),
          "+f"(d[40]), "+f"(d[41]), "+f"(d[42]), "+f"(d[43]), "+f"(d[44]), "+f"(d[45]), "+f"(d[46]), "+f"(d[47]),
          "+f"(d[48]), "+f"(d[49]), "+f"(d[50]), "+f"(d[51]), "+f"(d[52]), "+f"(d[53]), "+f"(d[54]), "+f"(d[55]),
          "+f"(d[56]), "+f"(d[57]), "+f"(d[58]), "+f"(d[59]), "+f"(d[60]), "+f"(d[61]), "+f"(d[62]), "+f"(d[63]),
          "+f"(d[64]), "+f"(d[65]), "+f"(d[66]), "+f"(d[67]), "+f"(d[68]), "+f"(d[69]), "+f"(d[70]), "+f"(d[71]),
          "+f"(d[72]), "+f"(d[73]), "+f"(d[74]), "+f"(d[75]), "+f"(d[76]), "+f"(d[77]), "+f"(d[78]), "+f"(d[79]),
          "+f"(d[80]), "+f"(d[81]), "+f"(d[82]), "+f"(d[83]), "+f"(d[84]), "+f"(d[85]), "+f"(d[86]), "+f"(d[87]),
          "+f"(d[88]), "+f"(d[89]), "+f"(d[90]), "+f"(d[91]), "+f"(d[92]), "+f"(d[93]), "+f"(d[94]), "+f"(d[95]),
          "+f"(d[96]), "+f"(d[97]), "+f"(d[98]), "+f"(d[99]), "+f"(d[100]), "+f"(d[101]), "+f"(d[102]), "+f"(d[103]),
          "+f"(d[104]), "+f"(d[105]), "+f"(d[106]), "+f"(d[107]), "+f"(d[108]), "+f"(d[109]), "+f"(d[110]), "+f"(d[111]),
          "+f"(d[112]), "+f"(d[113]), "+f"(d[114]), "+f"(d[115]), "+f"(d[116]), "+f"(d[117]), "+f"(d[118]), "+f"(d[119]),
          "+f"(d[120]), "+f"(d[121]), "+f"(d[122]), "+f"(d[123]), "+f"(d[124]), "+f"(d[125]), "+f"(d[126]), "+f"(d[127])
        : "l"(da), "l"(db), "n"(TA), "n"(TB), "r"(keep));
}
template <int TA, int TB>
__device__ __forceinline__ void wgmma_n192(float (&d)[128], uint64_t da, uint64_t db, int keep) {
    asm volatile(
        "{\n.reg .pred p;\nsetp.ne.b32 p, %100, 0;\n"
        "wgmma.mma_async.sync.aligned.m64n192k16.f32.bf16.bf16 "
        "{%0, %1, %2, %3, %4, %5, %6, %7, %8, %9, %10, %11, %12, %13, %14, %15, "
        "%16, %17, %18, %19, %20, %21, %22, %23, %24, %25, %26, %27, %28, %29, %30, %31, "
        "%32, %33, %34, %35, %36, %37, %38, %39, %40, %41, %42, %43, %44, %45, %46, %47, "
        "%48, %49, %50, %51, %52, %53, %54, %55, %56, %57, %58, %59, %60, %61, %62, %63, "
        "%64, %65, %66, %67, %68, %69, %70, %71, %72, %73, %74, %75, %76, %77, %78, %79, "
        "%80, %81, %82, %83, %84, %85, %86, %87, %88, %89, %90, %91, %92, %93, %94, %95}, "
        "%96, %97, p, 1, 1, %98, %99;\n}\n"
        : "+f"(d[0]), "+f"(d[1]), "+f"(d[2]), "+f"(d[3]), "+f"(d[4]), "+f"(d[5]), "+f"(d[6]), "+f"(d[7]),
          "+f"(d[8]), "+f"(d[9]), "+f"(d[10]), "+f"(d[11]), "+f"(d[12]), "+f"(d[13]), "+f"(d[14]), "+f"(d[15]),
          "+f"(d[16]), "+f"(d[17]), "+f"(d[18]), "+f"(d[19]), "+f"(d[20]), "+f"(d[21]), "+f"(d[22]), "+f"(d[23]),
          "+f"(d[24]), "+f"(d[25]), "+f"(d[26]), "+f"(d[27]), "+f"(d[28]), "+f"(d[29]), "+f"(d[30]), "+f"(d[31]),
          "+f"(d[32]), "+f"(d[33]), "+f"(d[34]), "+f"(d[35]), "+f"(d[36]), "+f"(d[37]), "+f"(d[38]), "+f"(d[39]),
          "+f"(d[40]), "+f"(d[41]), "+f"(d[42]), "+f"(d[43]), "+f"(d[44]), "+f"(d[45]), "+f"(d[46]), "+f"(d[47]),
          "+f"(d[48]), "+f"(d[49]), "+f"(d[50]), "+f"(d[51]), "+f"(d[52]), "+f"(d[53]), "+f"(d[54]), "+f"(d[55]),
          "+f"(d[56]), "+f"(d[57]), "+f"(d[58]), "+f"(d[59]), "+f"(d[60]), "+f"(d[61]), "+f"(d[62]), "+f"(d[63]),
          "+f"(d[64]), "+f"(d[65]), "+f"(d[66]), "+f"(d[67]), "+f"(d[68]), "+f"(d[69]), "+f"(d[70]), "+f"(d[71]),
          "+f"(d[72]), "+f"(d[73]), "+f"(d[74]), "+f"(d[75]), "+f"(d[76]), "+f"(d[77]), "+f"(d[78]), "+f"(d[79]),
          "+f"(d[80]), "+f"(d[81]), "+f"(d[82]), "+f"(d[83]), "+f"(d[84]), "+f"(d[85]), "+f"(d[86]), "+f"(d[87]),
          "+f"(d[88]), "+f"(d[89]), "+f"(d[90]), "+f"(d[91]), "+f"(d[92]), "+f"(d[93]), "+f"(d[94]), "+f"(d[95])
        : "l"(da), "l"(db), "n"(TA), "n"(TB), "r"(keep));
}
template <int O>
__device__ __forceinline__ void wgmma_n64_rs(float (&d)[128], uint32_t a0, uint32_t a1, uint32_t a2, uint32_t a3, uint64_t db) {
    asm volatile(
        "{\n.reg .pred p;\nsetp.ne.b32 p, 1, 0;\n"
        "wgmma.mma_async.sync.aligned.m64n64k16.f32.bf16.bf16 "
        "{%0, %1, %2, %3, %4, %5, %6, %7, %8, %9, %10, %11, %12, %13, %14, %15, "
        "%16, %17, %18, %19, %20, %21, %22, %23, %24, %25, %26, %27, %28, %29, %30, %31}, "
        "{%32, %33, %34, %35}, %36, p, 1, 1, 1;\n}\n"
        : "+f"(d[O + 0]), "+f"(d[O + 1]), "+f"(d[O + 2]), "+f"(d[O + 3]), "+f"(d[O + 4]), "+f"(d[O + 5]), "+f"(d[O + 6]), "+f"(d[O + 7]),
          "+f"(d[O + 8]), "+f"(d[O + 9]), "+f"(d[O + 10]), "+f"(d[O + 11]), "+f"(d[O + 12]), "+f"(d[O + 13]), "+f"(d[O + 14]), "+f"(d[O + 15]),
          "+f"(d[O + 16]), "+f"(d[O + 17]), "+f"(d[O + 18]), "+f"(d[O + 19]), "+f"(d[O + 20]), "+f"(d[O + 21]), "+f"(d[O + 22]), "+f"(d[O + 23]),
          "+f"(d[O + 24]), "+f"(d[O + 25]), "+f"(d[O + 26]), "+f"(d[O + 27]), "+f"(d[O + 28]), "+f"(d[O + 29]), "+f"(d[O + 30]), "+f"(d[O + 31])
        : "r"(a0), "r"(a1), "r"(a2), "r"(a3), "l"(db));
}

constexpr uint64_t kDescHi = (uint64_t)(64u | 0x40000000u) << 32;
template <int MODE>
__device__ __forceinline__ void mma_kblock(float (&acc)[128], uint32_t a_lo, uint32_t b_lo, int keep) {
    constexpr uint32_t HALF = (MODE == 1) ? 12288u : 16384u;
    constexpr bool BN = (MODE == 1 || MODE == 2);
#pragma unroll
    for (int kk = 0; kk < 4; ++kk) {
        const uint32_t ao = (MODE == 3) ? kk * 2048u : kk * 32u;
        const uint32_t bo = BN ? ((kk >> 1) * HALF + (kk & 1) * 2048u) : kk * 32u;
        const uint64_t da = kDescHi | (uint64_t)(a_lo + (ao >> 4) + (1u << 16));
        const uint64_t db = kDescHi | (uint64_t)(b_lo + (bo >> 4) + (BN ? (256u << 16) : (1u << 16)));
        if (MODE == 1) wgmma_n192<0, 1>(acc, da, db, kk == 0 ? keep : 1);
        else wgmma_n256<(MODE == 3), BN>(acc, da, db, kk == 0 ? keep : 1);
    }
}

struct Params {
    Scratch* s;
    const __nv_bfloat16* x;
    const __nv_bfloat16* b_re;
    const __nv_bfloat16* b_im;
    const __nv_bfloat16* gate_w;
    const __nv_bfloat16* lam_re;
    const __nv_bfloat16* lam_im;
    const __nv_bfloat16* log_dt;
    const __nv_bfloat16* dskip;
    const __nv_bfloat16* b1;
    const __nv_bfloat16* b2;
    float* out;
    int swap;
};

#define CMUL(rr, ri, ar, ai, br, bi) do { float _r = (ar) * (br) - (ai) * (bi); float _i = (ar) * (bi) + (ai) * (br); rr = _r; ri = _i; } while (0)
#define CFMA(rr, ri, ar, ai, br, bi) do { float _r = fmaf(-(ai), (bi), fmaf((ar), (br), rr)); float _i = fmaf((ai), (br), fmaf((ar), (bi), ri)); rr = _r; ri = _i; } while (0)

#define KB_OPEN(IT, LAST)                                                                        \
    KT(IT, 0);                                                                                   \
    if (ORDER && (LAST) && wg == 1) bar_sync(7, 256);                                            \
    mbar_wait(bar_full + 8 * ((IT) & 3), ((IT) >> 2) & 1);                                \
    KT(IT, 1);
#define KB_CLOSE(IT, LAST, REL)                                                                  \
    if (ORDER && (LAST) && wg == 0) bar_arrive(7, 256);                                          \
    wgmma_wait<1>();                                                                             \
    if (lane < 2 && (REL)) mbar_arrive_cluster(rel_addr + 8 * (((IT) - 1) & 3));
#define KBLOCK(MODE, IT, FIRST, LAST)                                                            \
    {                                                                                            \
        const uint32_t so = ((IT) & 3) * (kStageBytes >> 4);                                     \
        KB_OPEN(IT, LAST);                                                                       \
        wgmma_fence();                                                                           \
        mma_kblock<MODE>(acc, a_lo + so, b_lo + so, !(FIRST));                                   \
        wgmma_commit();                                                                          \
        KB_CLOSE(IT, LAST, !(FIRST));                                                            \
    }
#define TILE_END() do { wgmma_wait<0>(); if (lane < 2) mbar_arrive_cluster(rel_addr + 24); } while (0)

__global__ void __cluster_dims__(2, 1, 1) __launch_bounds__(384, 1)
fused_kernel(const __grid_constant__ CUtensorMap mB, const __grid_constant__ CUtensorMap mXs, const __grid_constant__ CUtensorMap mXf,
             const __grid_constant__ CUtensorMap mW1b, const __grid_constant__ CUtensorMap mW1a, const __grid_constant__ CUtensorMap mHs,
             const __grid_constant__ CUtensorMap mHf, const __grid_constant__ CUtensorMap mCre, const __grid_constant__ CUtensorMap mCim,
             const __grid_constant__ CUtensorMap mW2, const __grid_constant__ CUtensorMap mW2n, const Params p) {
    extern __shared__ __align__(1024) uint8_t smem_raw[];
    if (PFTOP) { prefetch_map(&mB); prefetch_map(&mXs); }
    const uint32_t sbase = smem_u32(smem_raw);
    if ((sbase & 0x3ffffu) != kSmemOrg) return;
    const uint32_t bar_full = sbase + kBarOff, bar_empty = bar_full + 32, bar_dep = bar_full + 64;
    const uint32_t bar_x = bar_full + 88, bar_c = bar_full + 96, role_s = bar_full + 104, bar_role = bar_full + 120, tag_s = bar_full + 112 + (threadIdx.x & 1) * 4;

    const int tid = threadIdx.x, lane = tid & 31;
    const int warp = __shfl_sync(0xffffffffu, tid >> 5, 0);
    const uint32_t rank = blockIdx.x & 1;

    int pref;
    {
        unsigned smid;
        asm("mov.u32 %0, %%smid;" : "=r"(smid));
        const int t = smid >> 1, u = t - 32, d = (u * 37) >> 8;
        pref = (t < 32) ? (t & 7) * 8 + (t >> 3) : (t < 60) ? (1 + u - 7 * d) * 8 + 4 + d : ((t - 58) & 7);
    }
    STAMP(tid == 0, 0);
    int role = pref;
#define ROLE_VARS()                                                                                               \
    const int c = role >> 3;                                                             \
    const int j8 = role & 7;                                                        \
    const int cb = j8 * 2 + (int)rank;                                             \
    const int rb = 2 * c + (int)rank;                                               \
    const int kh = j8 >> 2;                 \
    const int colK = (j8 & 3) * 256 + kh * 128, colS = colK ^ 128;    \
    (void)cb; (void)rb; (void)colS;

#define INIT_ALL()                                                                                    \
    if (warp == INITW && elect_one()) {                                                               \
        if (!PFTOP) { prefetch_map(&mB); prefetch_map(&mXs); }                                        \
        _Pragma("unroll") for (int s = 0; s < kStages; ++s) {                                         \
            mbar_init(bar_full + 8 * s, 1);                                                           \
            mbar_init(bar_empty + 8 * s, 16);                                                         \
            mbar_init(bar_dep + 8 * s, 1);                                \
        }                                                                                             \
        mbar_init(bar_c, 96);                                                                         \
        mbar_init(bar_role, 1);                                                                       \
        asm volatile("fence.mbarrier_init.release.cluster;\nfence.proxy.async.shared::cta;" ::: "memory"); \
        mbar_expect_tx(bar_full, 49152);            \
        tma4(sbase, &mB, bar_full, 0, 0, 0, ((pref & 7) * 2 + (int)rank) * 8);                        \
        if (!MC0) {                                                                                   \
        tma5(sbase + kABytes, &mXs, bar_full, 0, 0, 0, 0, pref >> 3);                                 \
        tma5(sbase + kABytes + 16384, &mXs, bar_full, 0, 0, 0, 16, pref >> 3);                        \
        }                                                                                             \
        mbar_expect_tx(bar_x, 2048);                                                                  \
        bulk_load(sbase + kXOff, p.gate_w, 2048, bar_x);                                              \
        mbar_expect_tx(bar_role, 8);                                                                  \
    }
    if (PRODCOND) {
        asm volatile("setmaxnreg.dec.sync.aligned.u32 24;");
        unsigned taken = 0;
        if (tid == 352 && rank == 0) {
            taken = atom_exch(&p.s->claim[pref], 1u);
        }
        __syncwarp();
        cluster_arrive();
        cluster_wait();
        if (warp > 8) {
            if (tid == 352) {
#pragma unroll 1
                for (int i = 0; taken != 0 && i < 64; ++i) { role = i + 256; taken = atom_exch(&p.s->claim[i], 1u); }
                st_async32(mapa(role_s + 4 * rank, 0), role, mapa(bar_role, 0));
                st_async32(mapa(role_s + 4 * rank, 1), role, mapa(bar_role, 1));
            }
            __syncwarp();
            mbar_wait(bar_role, 0);
            role = __shfl_sync(0xffffffffu, (int)lds32(role_s), 0) & 63;
            ROLE_VARS();
            if (warp == 11) {
                if (lane < 9) prefetch_map(&mXf + lane);
#pragma unroll 1
                for (int en = lane; en < 88; en += 32) {
                    const int J = en >> 2;
                    const __nv_bfloat16* src = ((J < 14) ? p.b1 : (J < 18) ? p.dskip : p.b2) + 32 * J + 2 * (en & 3) +
                                               ((J < 6) ? 2048 + 192 * j8 : (J < 14) ? 256 * j8 - 192 : colK - ((J < 18) ? 448 : 576));
                    sts128(sbase + kBiasOff + en * 16, ldg32(src), ldg32(src + 8), ldg32(src + 16), ldg32(src + 24));
                }
                mbar_arrive_local(bar_c);
            } else {
                {
                    sts32(tag_s, ld_relaxed32(&p.s->epoch) + 1);
                    const int ch = cb * 64 + (tid - 288);
                    const uint32_t t_s = sbase + kTabOff + (tid - 288) * 64;
                    const float Lr = bf_lo(ldg16(p.lam_re + ch)), Li = bf_lo(ldg16(p.lam_im + ch));
                    const float dt = bf16_round(expf(bf_lo(ldg16(p.log_dt + ch))));
                    const float ea = expf(dt * Lr);
                    float lr, li;
                    sincospif((dt * Li) * 0.31830988618379067f, &li, &lr);
                    lr *= ea; li *= ea;
                    const float nr = lr - 1.0f, ni = li;
                    const bool big = fabsf(Lr) >= fabsf(Li);
                    const float u = big ? Lr : Li, v = big ? Li : Lr;
                    const float t = v / u, d = 2.0f / fmaf(v, t, u);
                    const float cr = (big ? fmaf(ni, t, nr) : fmaf(nr, t, ni)) * d, ci = (big ? fmaf(-nr, t, ni) : fmaf(ni, t, -nr)) * d;
                    if (p.swap) li = -li;
                    const float m00 = p.swap ? -ci : cr, m01 = p.swap ? cr : -ci, m10 = p.swap ? -cr : -ci, m11 = p.swap ? -ci : -cr;
#pragma unroll
                    for (int q = 0; q < 4; ++q) {
                        sts128f(t_s + q * 16, lr, li, m00, m01);
                        sts128f(t_s + 12288 + q * 16, 0.f, 0.f, 0.f, 0.f);
                    }
#pragma unroll 1
                    for (int i = 0; i < 6; ++i) CMUL(lr, li, lr, li, lr, li);
                    float ar, ai, br, bi;
                    CMUL(ar, ai, lr, li, lr, li);
                    CMUL(br, bi, ar, ai, lr, li);
                    sts128f(t_s + 4096, m10, m11, 0.f, 0.f);
#pragma unroll
                    for (int q = 1; q < 4; ++q) sts128f(t_s + 4096 + q * 16, m10, m11, lr, li);
                    sts128f(t_s + 8192, 0.f, 0.f, 1.f, 0.f);
                    sts128f(t_s + 8192 + 16, 0.f, 0.f, lr, li);
                    sts128f(t_s + 8192 + 32, ar, ai, ar, ai);
                    sts128f(t_s + 8192 + 48, ar, ai, br, bi);
                    CMUL(ar, ai, ar, ai, ar, ai);
                    br = 1.f; bi = 0.f;
#pragma unroll 1
                    for (int k = c - 1; k >= 0; --k) {
                        sts64f(t_s + 12288 + (k & 3) * 16 + (k >> 2) * 8, br, bi);
                        CMUL(br, bi, br, bi, ar, ai);
                    }
                    mbar_arrive_local(bar_c);
                }
                if (warp == 9) {
#pragma unroll 1
                    for (int ev = 0; ev < 3; ++ev) {
                        if (ev == 2) {
                            uint8_t* box = p.s->X + (size_t)(role * 2 + rank) * kXBytes + lane * 16;
#pragma unroll 1
                            for (int i = 0; i < kXBytes; i += 512) stg128(box + i, 0, 0, 0, 0);
                        }
                        bar_sync(3 + ev, 288);
                        if (lane == 0) {
                            unsigned* cnt = &p.s->cnt[(ev == 0 ? c : 16 * ev - 8 + rb) * 32];
                            asm volatile("fence.acq_rel.gpu;\nfence.proxy.async.global;" ::: "memory");
                            asm volatile("red.relaxed.gpu.global.add.u32 [%0], 1;" ::"l"(cnt) : "memory");
                        }
                        __syncwarp();
                    }
                } else if (lane == 0) {
                    const unsigned tag = lds32(tag_s);
#pragma unroll 1
                    for (int ev = 0; ev < 3; ++ev) {
                        wait_counter(&p.s->cnt[(ev == 0 ? c : 16 * ev - 8 + rb) * 32], tag * (ev == 0 ? 16u : 8u));
                        mbar_arrive_local(bar_dep + 8 * ev);
                        if (ev == 0 && atomicInc(&p.s->done, 127u) == 127u) {
                            st_relaxed32(&p.s->epoch, tag);
#pragma unroll 1
                            for (int i = 0; i < 64; i += 4) stg128(&p.s->claim[i], 0, 0, 0, 0);
                        }
                    }
                }
            }
        } else if (elect_one()) {
            int it = 1, again = 15;
            if (MC0) tma5_mc(sbase + kABytes + rank * 16384, &mXs, bar_full, 0, 0, 0, rank * 16, role >> 3);
#define ACQUIRE(BYTES)                                                   \
    const uint32_t st = sbase + (it & 3) * kStageBytes, fb = bar_full + 8 * (it & 3); \
    mbar_wait(bar_empty + 8 * (it & 3), ((it >> 2) & 1) ^ 1);     \
    mbar_expect_tx(fb, BYTES);
#pragma unroll 1
            for (; it < 16; ++it) {
                ACQUIRE(49152);
                tma4(st, &mB, fb, it * 64, 0, 0, ((role & 7) * 2 + (int)rank) * 8);
                tma5_mc(st + kABytes + rank * 16384, &mXs, fb, it * 64, 0, 0, rank * 16, role >> 3);
                if (it == again) {
                    mbar_wait(bar_role, 0);
                    const uint2 fin = lds64(role_s);
                    role = fin.x & 63;
                    if (fin.x != fin.y) { it = -1; again = 16; }
                }
            }
            ROLE_VARS();
#pragma unroll 1
            for (; it < 48; ++it) {
                const bool t1 = it < 32;
                const int k0 = (it & 15) * 64;
                ACQUIRE(t1 ? 40960 : 49152);
                tma5(st, &mXf, fb, k0, 0, 0, rank * 4, c);
                tma3_mc(st + kABytes + rank * (t1 ? 12288 : 16384), t1 ? &mW1b : &mW1a, fb, 0, k0 + rank * 32, t1 ? 32 + 3 * j8 : 4 * j8);
                if ((it & ~2) == XLDKB) {
                    const int h = (it >> 1) & 1;
                    if (h == 0) mbar_expect_tx(bar_x, 32768);
                    tma5(sbase + kXOff + h * 16384, &mXf, bar_x, colK + h * 64, 0, 0, rank * 4, c);
                }
            }
            STAMPA(true, 8);
            mbar_wait(bar_dep, 0);
            asm volatile("fence.proxy.async.global;" ::: "memory");
            STAMPA(true, 9);
#pragma unroll 1
            for (; it < 64; ++it) {
                const int k0 = (it & 15) * 64;
                ACQUIRE(49152);
                tma3(st, &mHs, fb, 0, kh * 1024 + k0, rb * 2);
                tma2_mc(st + kABytes + rank * 16384, kh ? &mCim : &mCre, fb, k0, rank ? colS : colK);
            }
            int f0 = 2048 + 896 * kh;
#pragma unroll 1
            for (; it < kTotal - 4; ++it, f0 += 64) {
                if (it == 64 || it == 74) {
                    mbar_wait(bar_dep + (it == 64 ? 8 : 16), 0);
                    asm volatile("fence.proxy.async.global;" ::: "memory");
                    if (it == 74) f0 = 1024 * kh;
                }
                if (f0 == 256 * j8) f0 += 256;
                ACQUIRE(49152);
                tma2(st, &mHf, fb, f0, rb * 128);
                tma5_mc(st + kABytes + rank * 16384, &mW2, fb, 0, 0, (f0 >> 3) + 4 * rank, 0, colK >> 6);
                tma5_mc(st + kABytes + rank * 16384 + 8192, &mW2, fb, 0, 0, (f0 >> 3) + 4 * rank, 0, colS >> 6);
            }
#pragma unroll 1
            for (int kb = 0; it < kTotal; ++it) {
                ACQUIRE(49152);
#pragma unroll 1
                for (int t = 0; t < 3; ++t, ++kb)
                    tma3_mc(st + t * 16384 + rank * 8192, &mW2n, fb, 0,
                            ((kb & 4) ? 2688 : 256 * (j8 ^ (kb >> 1 & 4))) + (kb & 3) * 64 + 32 * rank, colK >> 6);
            }
        }
    } else {
        INIT_ALL();
        if (warp >= 8 - PF0LINES) {
            const int row = blockIdx.x * 32 + lane;
            const __nv_bfloat16* src = (row < 2048) ? p.x : (row < 3072) ? p.b_re - 2048 * kD : p.b_im - 3072 * kD;
            asm volatile("prefetch.global.L2 [%0];" ::"l"(src + row * kD + (7 - warp) * 64) : "memory");
        }
        __syncwarp();
        cluster_arrive();
        asm volatile("setmaxnreg.inc.sync.aligned.u32 240;");
        const int wg = warp >> 2, w = warp & 3, r = lane >> 2, q = lane & 3, tw = tid & 127;
        uint32_t a_lo = (kSmemOrg + wg * 8192) >> 4;
        constexpr uint32_t b_lo = (kSmemOrg + kABytes) >> 4;
        const uint32_t rel_addr = mapa(bar_empty, (uint32_t)(lane & 1));
        const uint32_t gate_s = sbase + kGateOff;
        float acc[128];
        uint32_t pk[64];
        unsigned tag;
        UNDEF_R(tag);

#pragma unroll
        for (int i = 0; i < 128; ++i) UNDEF_F(acc[i]);
        float gs = 0.f;
        {
            const uint32_t gx_s = sbase + kABytes + (16 * rank + 2 * warp + (lane >> 4)) * 128 +
                                  ((((lane & 15) >> 1) ^ (2 * w + (lane >> 4))) << 4) + (lane & 1) * 8;
            const uint32_t gw_s = sbase + kXOff + (lane & 15) * 8;
            uint32_t again = 15;
            cluster_wait();
#pragma unroll 1
            for (uint32_t it = 0; it < 16; ++it) {
                const uint32_t so = (it & 3) * (kStageBytes >> 4);
                KB_OPEN(it, it == 15);
                wgmma_fence();
                mma_kblock<0>(acc, a_lo + so, b_lo + so, it != 0);
                wgmma_commit();
                KB_CLOSE(it, it == 15, it + again != 15);
                STAMPA(tid == 0 && it == 0, 1);
                mbar_wait(bar_x, 0);
                const uint2 xa = lds64(gx_s + (role & 7) * 4096 + (it & 3) * kStageBytes), wa = lds64(gw_s + it * 128);
                const uint32_t pa = bf2_mul(xa.x, wa.x), pb = bf2_mul(xa.y, wa.y);
                gs += (bf_lo(pa) + bf_hi(pa)) + (bf_lo(pb) + bf_hi(pb));
                if (it == again) {
                    mbar_wait(bar_c, 0);
                    const uint2 fin = lds64(role_s);
                    role = fin.x & 63;
                    if (__shfl_sync(0xffffffffu, fin.x != fin.y, 0)) { it = -1; again = 16; gs = 0.f; }
                }
            }
        }
        role = __shfl_sync(0xffffffffu, role, 0);
        ROLE_VARS();
        {
            tag = lds32(tag_s);
#pragma unroll
            for (int o = 8; o > 0; o >>= 1) gs += __shfl_xor_sync(0xffffffffu, gs, o);
            const float g = bf16_round(__frcp_rn(1.0f + expf(-bf16_round(gs))));
            if ((lane & 15) == 0) st_relaxed64(&p.s->gate[c * 256 + (lane >> 4) + 64 * w + 4 * cb + 2 * wg], __float_as_uint(g), tag);
        }
        const uint32_t tab_s = sbase + kTabOff + tid * 16;
        const float4 k0 = lds128f(tab_s);
        TILE_END();
        STAMPA(tid == 0, 2);
#pragma unroll
        for (int s = 0; s < 64; ++s) pk[s] = pack_bf16_v(acc[4 * (s >> 1) + (s & 1)], acc[4 * (s >> 1) + 2 + (s & 1)]);
#pragma unroll
        for (int i = 0; i < 96; ++i) UNDEF_F(acc[i]);

        const float lr = k0.x, li = k0.y, m00 = k0.z, m01 = k0.w;
        float m10, m11, hr = 0.f, hi = 0.f;
        uint32_t gg[4], orr[4], oii[4];
        const int ch = cb * 64 + warp * 8 + r;
        __nv_bfloat16* hs = p.s->Hs + (size_t)ch * 2048 + c * 256 + q * 8;
#define PASS2(KB)                                                                                      \
    _Pragma("unroll") for (int s = 0; s < 64; s += 2) {                                                \
        if (pass2_kb(s) != (KB)) continue;                                                             \
        if ((s & 7) == 0) {                                                                            \
            const uint4 ga = lds128(gate_s + (q * 72 + s) * 2);                                        \
            gg[0] = ga.x; gg[1] = ga.y; gg[2] = ga.z; gg[3] = ga.w;                                    \
        }                                                                                              \
        float o0[2], o1[2];                                                                            \
        _Pragma("unroll") for (int k = 0; k < 2; ++k) {                                                \
            PIN_R(pk[s + k]);                                                                          \
            float nr = bf_lo(pk[s + k]), ni = bf_hi(pk[s + k]);                                        \
            CFMA(nr, ni, lr, li, hr, hi);                                                              \
            hr = nr; hi = ni;                                                                          \
            o0[k] = fmaf(m00, hr, m01 * hi);                                                           \
            o1[k] = fmaf(m10, hr, m11 * hi);                                                           \
        }                                                                                              \
        orr[(s >> 1) & 3] = bf2_mul(pack_bf16(o0[0], o0[1]), gg[(s >> 1) & 3]);                        \
        oii[(s >> 1) & 3] = bf2_mul(pack_bf16(o1[0], o1[1]), gg[(s >> 1) & 3]);                        \
        if ((s & 7) == 6) {                                                                            \
            stg128(hs + 32 * (s >> 3), orr[0], orr[1], orr[2], orr[3]);                                \
            stg128(hs + 1024 * 2048 + 32 * (s >> 3), oii[0], oii[1], oii[2], oii[3]);                  \
        }                                                                                              \
    }                                                                                                  \
    PIN_F(hr); PIN_F(hi);
        {
            uint4 av0, av1, gv;
            float lqr, lqi;
#pragma unroll
            for (int kb = 0; kb < 16; ++kb) {
                PIN_R(a_lo);
                KBLOCK(1, 16 + kb, kb == 0, kb == 15);
                if (kb < 4) {
#pragma unroll
                    for (int s = kb * 16; s < kb * 16 + 16; ++s) {
                        float nr = bf_lo(pk[s]), ni = bf_hi(pk[s]);
                        CFMA(nr, ni, lr, li, hr, hi);
                        hr = nr; hi = ni;
                    }
                    PIN_F(hr); PIN_F(hi);
                }
                if (kb == 2) gv = ld_relaxed2x64(&p.s->gate[c * 256 + 2 * tw]);
                if (kb == 3) {
                    const float4 k1 = lds128f(tab_s + 4096), k2 = lds128f(tab_s + 8192);
                    m10 = k1.x; m11 = k1.y; lqr = k2.z; lqi = k2.w;
                    float tr = __shfl_up_sync(0xffffffffu, hr, 1, 4), ti = __shfl_up_sync(0xffffffffu, hi, 1, 4);
                    if (q >= 1) CFMA(hr, hi, k1.z, k1.w, tr, ti);
                    tr = __shfl_up_sync(0xffffffffu, hr, 2, 4); ti = __shfl_up_sync(0xffffffffu, hi, 2, 4);
                    if (q >= 2) CFMA(hr, hi, k2.x, k2.y, tr, ti);
                    if (q == 3) st_relaxed2x64(&p.s->agg[c * 1024 + ch], __float_as_uint(hr), tag, __float_as_uint(hi), tag);
                    tr = __shfl_up_sync(0xffffffffu, hr, 1, 4); ti = __shfl_up_sync(0xffffffffu, hi, 1, 4);
                    hr = (q >= 1) ? tr : 0.f; hi = (q >= 1) ? ti : 0.f;
                }
                if (kb == 4) {
                    unsigned spins = 0;
                    while (__any_sync(0xffffffffu, gv.y != tag || gv.w != tag)) {
                        if (++spins > kSpinLimit) break;
                        gv = ld_relaxed2x64(&p.s->gate[c * 256 + 2 * tw]);
                    }
                    sts32(gate_s + ((tw >> 5) * 72 + 2 * lane) * 2, __byte_perm(gv.x, gv.z, 0x7632));
                }
                if (kb == 5) {
                    av0 = make_uint4(0, tag, 0, tag); av1 = av0;
                    if (q < c) av0 = ld_relaxed2x64(&p.s->agg[q * 1024 + ch]);
                    if (q + 4 < c) av1 = ld_relaxed2x64(&p.s->agg[(q + 4) * 1024 + ch]);
                    bar_sync(1 + wg, 128);
                }
                if (kb == 6) {
                    const float4 k3 = lds128f(tab_s + 12288);
                    unsigned spins = 0;
                    while (__any_sync(0xffffffffu, av0.y != tag || av0.w != tag || av1.y != tag || av1.w != tag)) {
                        if (++spins > kSpinLimit) break;
                        if (q < c) av0 = ld_relaxed2x64(&p.s->agg[q * 1024 + ch]);
                        if (q + 4 < c) av1 = ld_relaxed2x64(&p.s->agg[(q + 4) * 1024 + ch]);
                    }
                    float vr, vi;
                    CMUL(vr, vi, k3.x, k3.y, __uint_as_float(av0.x), __uint_as_float(av0.z));
                    CFMA(vr, vi, k3.z, k3.w, __uint_as_float(av1.x), __uint_as_float(av1.z));
                    vr += __shfl_xor_sync(0xffffffffu, vr, 1); vi += __shfl_xor_sync(0xffffffffu, vi, 1);
                    vr += __shfl_xor_sync(0xffffffffu, vr, 2); vi += __shfl_xor_sync(0xffffffffu, vi, 2);
                    CFMA(hr, hi, lqr, lqi, vr, vi);
                }
                if (kb >= 6) { PASS2(kb); }
            }
            TILE_END();
        }
        STAMPA(tid == 0, 3);
#pragma unroll
        for (int i = 0; i < 48; ++i) pk[i] = pack_bf16_v(acc[2 * i], acc[2 * i + 1]);
#pragma unroll
        for (int i = 0; i < 128; ++i) UNDEF_F(acc[i]);

        PIN_R(a_lo);
        KBLOCK(2, 32, true, false);
        PASS2(16);
        PIN_R(a_lo);
        KBLOCK(2, 33, false, false);
        PASS2(17);
        bar_arrive(3, 288);
        const uint32_t gate_row = gate_s + ((2 * (w & 1)) * 72 + 8 * (4 * rank + 2 * wg + (w >> 1)) + r) * 2;
        uint32_t om0, om1;
        {
            const float a = 1.0f - bf_lo(lds16(gate_row)), b = 1.0f - bf_lo(lds16(gate_row + 72 * 2));
            om0 = pack_bf16(a, a); om1 = pack_bf16(b, b);
        }
        __nv_bfloat16* hf = p.s->Hf + (size_t)(rb * 128 + wg * 64 + w * 16 + r) * kF + q * 8 + 2048 + 192 * j8;
        uint32_t bias_s = sbase + kBiasOff + q * 16;
#define FFN_SLICE(J)                                                                                   \
    {                                                                                                  \
        const uint4 bv = lds128(bias_s + (J) * 64);                                                    \
        const uint32_t bb[4] = {bv.x, bv.y, bv.z, bv.w};                                               \
        _Pragma("unroll") for (int jj = 0; jj < 4; ++jj) {                                             \
            const uint32_t r0 = bf2_add_relu(pk[8 * (J) + 2 * jj], bb[jj]), r1 = bf2_add_relu(pk[8 * (J) + 2 * jj + 1], bb[jj]); \
            pk[8 * (J) + 2 * jj] = bf2_mul(bf2_mul(r0, r0), om0);                                      \
            pk[8 * (J) + 2 * jj + 1] = bf2_mul(bf2_mul(r1, r1), om1);                                  \
        }                                                                                              \
        stg128(hf + 32 * (J), pk[8 * (J)], pk[8 * (J) + 2], pk[8 * (J) + 4], pk[8 * (J) + 6]);         \
        stg128(hf + 8 * kF + 32 * (J), pk[8 * (J) + 1], pk[8 * (J) + 3], pk[8 * (J) + 5], pk[8 * (J) + 7]); \
    }
        const uint32_t x_s = sbase + kXOff + (wg * 64 + w * 16 + (lane & 15)) * 128 + (((lane >> 4) ^ (lane & 7)) << 4);
        {
            uint32_t j = 0, nsl = 6;
#pragma unroll 1
            for (uint32_t it = 34; it < 86; ++it, ++j) {
                const uint32_t so = (it & 3) * (kStageBytes >> 4);
                if (wg == 1 && (it == 84 || (ORDER && it == 47))) bar_sync(7, 256);
                KB_OPEN(it, false);
                if ((it & ~15u) == 48) {
                    wgmma_fence();
                    mma_kblock<3>(acc, a_lo + so, b_lo + so, it != 48);
                    wgmma_commit();
                } else {
                    wgmma_fence();
                    mma_kblock<2>(acc, a_lo + so, b_lo + so, 1);
                    wgmma_commit();
                }
                if (wg == 0 && (it == 85 || (ORDER && it == 47))) bar_arrive(7, 256);
                KB_CLOSE(it, false, it != 48);
                if (j < nsl) {
                    if (j & 4) {
                        if (j & 2) { if (j & 1) FFN_SLICE(7) else FFN_SLICE(6) } else { if (j & 1) FFN_SLICE(5) else FFN_SLICE(4) }
                    } else {
                        if (j & 2) { if (j & 1) FFN_SLICE(3) else FFN_SLICE(2) } else { if (j & 1) FFN_SLICE(1) else FFN_SLICE(0) }
                    }
                    if (j + 1 == nsl) bar_arrive(1 + (nsl >> 1), 288);
                } else if (it == 47) {
                    hf += 64 * j8 - 2048;
                    bias_s += 6 * 64;
                    j = -1; nsl = 8;
                    TILE_END();
                    STAMPA(tid == 0, 4);
#pragma unroll
                    for (int i = 0; i < 64; ++i) pk[i] = pack_bf16_v(acc[2 * i], acc[2 * i + 1]);
                } else if ((it >> 2) == ETKB / 4) {
                    mbar_wait(bar_x, 1);
                    const uint32_t xa_s = (x_s ^ ((it & 1) << 6)) + (it & 2) * 8192;
                    const float g0 = bf_lo(lds16(gate_row)), g1 = bf_lo(lds16(gate_row + 72 * 2));
                    const float o0f = bf_lo(om0), o1f = bf_lo(om1);
                    const uint4 dq = lds128(bias_s + (8 + (it & 3)) * 64), bq = lds128(bias_s + (12 + (it & 3)) * 64);
                    const uint4 xa = ldsm4(xa_s), xb = ldsm4(xa_s ^ 32);
                    const uint32_t dv[4] = {dq.x, dq.y, dq.z, dq.w}, bv2[4] = {bq.x, bq.y, bq.z, bq.w};
                    uint32_t xv[8] = {xa.x, xa.y, xa.z, xa.w, xb.x, xb.y, xb.z, xb.w};
#pragma unroll
                    for (int jj = 0; jj < 4; ++jj) {
                        const uint32_t x0 = bf2_mul(xv[2 * jj], dv[jj]), x1 = bf2_mul(xv[2 * jj + 1], dv[jj]);
                        const float bl = bf_lo(bv2[jj]), bh = bf_hi(bv2[jj]);
                        xv[2 * jj] = pack_bf16(fmaf(g0, bf_lo(x0), o0f * bl), fmaf(g0, bf_hi(x0), o0f * bh));
                        xv[2 * jj + 1] = pack_bf16(fmaf(g1, bf_lo(x1), o1f * bl), fmaf(g1, bf_hi(x1), o1f * bh));
                    }
                    sts128(xa_s, xv[0], xv[1], xv[2], xv[3]);
                    sts128(xa_s ^ 32, xv[4], xv[5], xv[6], xv[7]);
                }
            }
        }
        constexpr uint64_t kDescHi2 = (uint64_t)(128u | 0x40000000u) << 32;
#define TAIL_B(KB) ((kSmemOrg + ((2 + (KB) / 3) & 3) * kStageBytes + ((KB) % 3) * 16384) >> 4)
#define LOAD_A(A)                                                                                      \
    asm volatile("" : "+l"(hf));                                                                       \
    _Pragma("unroll") for (int J = 0; J < 16; ++J) {                                                   \
        const uint4 u = ld_relaxed128(hf + (J & 1) * 8 * kF + 32 * (J >> 1));                          \
        A[4 * J] = u.x; A[4 * J + 1] = u.y; A[4 * J + 2] = u.z; A[4 * J + 3] = u.w;                    \
    }
#define SWAP_A(A)                                                                                      \
    _Pragma("unroll") for (int J = 0; J < 16; ++J) xor_swap(A[8 * (J >> 1) + 1 + 2 * (J & 1)], A[8 * (J >> 1) + 4 + 2 * (J & 1)]);
#define HALF_MMA(H, A, KB0)                                                                            \
    _Pragma("unroll") for (int i = 0; i < 16; ++i)                                                     \
        wgmma_n64_rs<32 * (H)>(acc, A[4 * i], A[4 * i + 1], A[4 * i + 2], A[4 * i + 3],                \
                               kDescHi2 | (uint64_t)(TAIL_B((KB0) + (i >> 2)) + ((((i >> 1) & 1) * 8192 + (i & 1) * 1024 + (H) * 4096) >> 4) + (256u << 16)));
#define OWN_MMA(H)                                                                                     \
    wgmma_fence();                                                                                     \
    _Pragma("unroll") for (int i = 0; i < 16; ++i)                                                     \
        wgmma_n64_rs<32 * (H)>(acc, pk[4 * i], pk[4 * i + 1], pk[4 * i + 2], pk[4 * i + 3],            \
                               kDescHi | (uint64_t)(TAIL_B(i >> 2) + ((((i >> 1) & 1) * 8192 + (i & 1) * 2048 + (H) * 4096) >> 4) + (256u << 16))); \
    wgmma_commit();
#define LOAD_E(H) _Pragma("unroll") for (int u = 0; u < 4; ++u) rx[u] = lds128((x_s ^ (u << 5)) + (H) * 16384);
#define ADD_E(H)                                                                                       \
    _Pragma("unroll") for (int u = 0; u < 4; ++u) {                                                    \
        const uint32_t ee[4] = {rx[u].x, rx[u].y, rx[u].z, rx[u].w};                                   \
        _Pragma("unroll") for (int k = 0; k < 4; ++k) {                                                \
            const int v = 32 * (H) + 8 * u + 2 * k;                                                    \
            acc[v] += bf_lo(ee[k]); acc[v + 1] += bf_hi(ee[k]);                                        \
            PIN_F(acc[v]); PIN_F(acc[v + 1]);                                                          \
        }                                                                                              \
    }
#define RXLOAD(H)                                                                                      \
    {                                                                                                  \
        if ((H) == 0) rs = ld_relaxed32((const unsigned*)(xi + 32768 - tid * 12));                     \
        _Pragma("unroll") for (int u = 0; u < 4; ++u) rx[u] = ld_relaxed2x64(xi + (4 * (H) + u) * 4096); \
    }
#define RXCHECK(H)                                                                                     \
    {                                                                                                  \
        unsigned spins = 0;                                                                            \
        _Pragma("unroll 1") while (true) {                                                             \
            uint32_t ok = rs != 0;                                                                     \
            _Pragma("unroll") for (int u = 0; u < 4; ++u) ok &= rx[u].x & rx[u].z;                     \
            if (__all_sync(0xffffffffu, ok) || ++spins > kSpinLimit) break;                            \
            RXLOAD(H);                                                                                 \
            RESPIN();                                                                                  \
        }                                                                                              \
    }
#define SUM(U)                                                                                         \
    {                                                                                                  \
        const uint32_t rr[4] = {rx[U].x, rx[U].y, rx[U].z, rx[U].w};                                   \
        _Pragma("unroll") for (int k = 0; k < 4; ++k) {                                                \
            const float2 f = __half22float2(*reinterpret_cast<const __half2*>(&rr[k]));                \
            ex[8 * (U) + 2 * k] = f.x; ex[8 * (U) + 2 * k + 1] = f.y;                                  \
            PIN_F(ex[8 * (U) + 2 * k]); PIN_F(ex[8 * (U) + 2 * k + 1]);                                \
        }                                                                                              \
    }
#define PUT(H, U)                                                                                      \
    _Pragma("unroll") for (int h = 0; h < 2; ++h) {                                                    \
        const int ea = 8 * (U) + 2 * h, va = 32 * (H) + ea, vb = va + 4;                               \
        PIN_F(acc[va]); PIN_F(acc[va + 1]); PIN_F(acc[vb]); PIN_F(acc[vb + 1]);                        \
        const float a0 = fmaf(ex[ea], xsc, acc[va]), a1 = fmaf(ex[ea + 1], xsc, acc[va + 1]);          \
        const float b0 = fmaf(ex[ea + 4], xsc, acc[vb]), b1 = fmaf(ex[ea + 5], xsc, acc[vb + 1]);      \
        const float t0 = __shfl_xor_sync(0xffffffffu, odd ? a0 : b0, 1), t1 = __shfl_xor_sync(0xffffffffu, odd ? a1 : b1, 1); \
        stg128f(o0 + h * 64 * kD + 64 * (H) + 16 * (U), odd ? t0 : a0, odd ? t1 : a1, odd ? b0 : t0, odd ? b1 : t1); \
    }
        mbar_wait(bar_dep + 16, 0);
        wgmma_wait<0>();
        if (lane < 2) mbar_arrive_cluster(rel_addr + 8);
        sched_fence(a_lo);
        {
            const uint8_t* xi = p.s->X + (size_t)(role * 2 + rank) * kXBytes + tid * 16;
            uint8_t* xo = const_cast<uint8_t*>(xi) + (kh ? -8 * kXBytes : 8 * kXBytes);
            uint4 rx[4];
            uint32_t rs, a1[64];
            LOAD_E(0);
            {
                STAMP(tid == 0, 15); STAMPB(tid == 128, 1);
                float m[4] = {0.f, 0.f, 0.f, 0.f};
#pragma unroll
                for (int i = 64; i < 128; ++i) m[i & 3] = fmaxf(m[i & 3], fabsf(acc[i]));
                const uint32_t eb = max(__float_as_uint(fmaxf(fmaxf(m[0], m[1]), fmaxf(m[2], m[3]))) >> 23, 15u);
                const float xsc = __uint_as_float((268u - eb) << 23);
                st_relaxed32(xo + 32768 - tid * 12, (eb - 14u) << 23);
#pragma unroll
                for (int u = 0; u < 8; ++u) {
                    const int v = 64 + 8 * u;
                    st_relaxed2x64(xo + u * 4096, pack_f16(acc[v] * xsc, acc[v + 1] * xsc) | 1, pack_f16(acc[v + 2] * xsc, acc[v + 3] * xsc),
                                   pack_f16(acc[v + 4] * xsc, acc[v + 5] * xsc) | 1, pack_f16(acc[v + 6] * xsc, acc[v + 7] * xsc));
                }
                STAMP(tid == 0, 12); STAMPB(tid == 128, 2);
            }
            ADD_E(0);
            LOAD_E(1);
            hf += 2688 - 256 * j8;
            mbar_wait(bar_full + 16, 1);
            mbar_wait(bar_full + 24, 1);
            OWN_MMA(0);
            sched_fence(a_lo);
            ADD_E(1);
            sched_fence(a_lo);
            OWN_MMA(1);
            if (wg == 1) bar_arrive(8, 256);
            LOAD_A(a1);
            sched_fence(a_lo);
            wgmma_wait<0>();
            sched_fence(a_lo);
            hf += 256 * (j8 ^ 4) - 2688;
            LOAD_A(pk);
            SWAP_A(a1);
            mbar_wait(bar_full, 0);
            bar_sync(8 + wg, 256);
            STAMPB(tid == 0, 9); STAMPB(tid == 128, 3);
            RXLOAD(0);
            wgmma_fence();
            HALF_MMA(0, a1, 4);
            wgmma_commit();
            SWAP_A(pk);
            mbar_wait(bar_full + 8, 0);
            wgmma_fence();
            HALF_MMA(0, pk, 8);
            wgmma_commit();
            if (wg == 0) bar_arrive(9, 256);
            sched_fence(a_lo);
            STAMPB(tid == 0, 10);
            const bool odd = q & 1;
            const int tb = c * 256 + 128 * (w & 1) + 8 * (4 * rank + 2 * wg + (w >> 1));
            float* o0 = p.out + (size_t)(tb + r) * kD + colK + (odd ? 2 * q + 6 : 2 * q);
            RXCHECK(0);
            STAMP(tid == 0, 13);
            const float xsc = __uint_as_float(rs);
            float ex[32];
            wgmma_wait<0>();
            STAMPB(tid == 0, 11);
            SUM(0); PUT(0, 0); SUM(1); PUT(0, 1); SUM(2); PUT(0, 2); SUM(3); PUT(0, 3);
            STAMP(tid == 0, 14); STAMPB(tid == 128, 8);
            RXLOAD(1);
            sched_fence(a_lo);
            wgmma_fence();
            HALF_MMA(1, a1, 4);
            HALF_MMA(1, pk, 8);
            wgmma_commit();
            sched_fence(a_lo);
            RXCHECK(1);
            SUM(0); SUM(1); SUM(2); SUM(3);
            sched_fence(a_lo);
            wgmma_wait<0>();
            STAMP(tid == 0, 6); STAMPB(tid == 128, 4);
            PUT(1, 0); PUT(1, 1); PUT(1, 2); PUT(1, 3);
        }
        STAMP(tid == 0, 7);
        STAMP(tid == 128, 5);
    }
}

typedef CUresult (*EncodeFn)(CUtensorMap*, CUtensorMapDataType, cuuint32_t, void*, const cuuint64_t*, const cuuint64_t*,
                             const cuuint32_t*, const cuuint32_t*, CUtensorMapInterleave, CUtensorMapSwizzle,
                             CUtensorMapL2promotion, CUtensorMapFloatOOBfill);

bool encode(EncodeFn fn, CUtensorMap* m, const void* base, int rank, const cuuint64_t* dims, const cuuint64_t* strides,
            const cuuint32_t* box) {
    cuuint32_t es[5] = {1, 1, 1, 1, 1};
    return fn(m, CU_TENSOR_MAP_DATA_TYPE_BFLOAT16, rank, const_cast<void*>(base), dims, strides, box, es,
              CU_TENSOR_MAP_INTERLEAVE_NONE, CU_TENSOR_MAP_SWIZZLE_128B, CU_TENSOR_MAP_L2_PROMOTION_L2_256B,
              CU_TENSOR_MAP_FLOAT_OOB_FILL_NONE) == CUDA_SUCCESS;
}

}

extern "C" void kernel_launch(void* const* d_in, const int* in_sizes, int n_in, void* d_out, int out_size) {
    (void)in_sizes; (void)n_in; (void)out_size;
    typedef const __nv_bfloat16* bp;
    bp x = (bp)d_in[0], lam_re = (bp)d_in[1], lam_im = (bp)d_in[2], B_re = (bp)d_in[3], B_im = (bp)d_in[4];
    bp C_re = (bp)d_in[5], C_im = (bp)d_in[6], log_dt = (bp)d_in[7], dskip = (bp)d_in[8];
    bp w1 = (bp)d_in[10], b1 = (bp)d_in[11], w2 = (bp)d_in[12], b2 = (bp)d_in[13], gate_w = (bp)d_in[14];

    static EncodeFn fn = nullptr;
    static Scratch* ps = nullptr;
    if (!fn) {
        void* f = nullptr;
        cudaDriverEntryPointQueryResult qr;
        cudaGetDriverEntryPoint("cuTensorMapEncodeTiled", &f, cudaEnableDefault, &qr);
        fn = (EncodeFn)f;
        cudaGetSymbolAddress((void**)&ps, g_s);
        cudaFuncSetAttribute(fused_kernel, cudaFuncAttributeMaxDynamicSharedMemorySize, kSmemBytes);
    }
    cudaStream_t stream = cudaStreamPerThread;

    Params p;
    p.x = x; p.lam_re = lam_re; p.lam_im = lam_im; p.log_dt = log_dt; p.dskip = dskip; p.b1 = b1; p.b2 = b2;
    p.gate_w = gate_w; p.b_re = B_re; p.b_im = B_im; p.out = (float*)d_out; p.s = ps;
    char* const pHs = (char*)ps + offsetof(Scratch, Hs);
    char* const pHf = (char*)ps + offsetof(Scratch, Hf);
    char* const pBc = (char*)ps + offsetof(Scratch, Bcopy);

    const char* lo = (const char*)B_re; const char* hi = (const char*)B_im;
    p.swap = 0;
    if (hi < lo) { const char* t = lo; lo = hi; hi = t; p.swap = 1; }
    unsigned long long diff = (unsigned long long)(hi - lo);
    if (diff >= (1ull << 40) || (diff & 15) || diff == 0) {
        cudaMemcpyAsync(pBc, B_re, 2u << 20, cudaMemcpyDeviceToDevice, stream);
        cudaMemcpyAsync((char*)pBc + (2u << 20), B_im, 2u << 20, cudaMemcpyDeviceToDevice, stream);
        lo = (const char*)pBc; diff = 2u << 20; p.swap = 0;
    }

    CUtensorMap mB, mXs, mXf, mW1a, mW1b, mHs, mHf, mCre, mCim, mW2, mW2n;
    bool ok = true;
    { cuuint64_t d[4] = {1024, 8, 2, 128}, s[3] = {2048, diff, 16384}; cuuint32_t b[4] = {64, 8, 2, 8};
      ok &= encode(fn, &mB, lo, 4, d, s, b); }
    { cuuint64_t d[5] = {1024, 2, 4, 32, 8}, s[4] = {2048, 64 * 2048, 2 * 2048, 256 * 2048}; cuuint32_t b[5] = {64, 2, 4, 16, 1};
      ok &= encode(fn, &mXs, x, 5, d, s, b); }
    { cuuint64_t d[5] = {1024, 8, 4, 8, 8}, s[4] = {2048, 64 * 2048, 8 * 2048, 256 * 2048}; cuuint32_t b[5] = {64, 8, 4, 4, 1};
      ok &= encode(fn, &mXf, x, 5, d, s, b); }
    { cuuint64_t d[3] = {64, 1024, 56}, s[2] = {7168, 128}; cuuint32_t ba[3] = {64, 32, 4}, bb[3] = {64, 32, 3};
      ok &= encode(fn, &mW1a, w1, 3, d, s, ba); ok &= encode(fn, &mW1b, w1, 3, d, s, bb); }
    { cuuint64_t d[3] = {64, 2048, 32}, s[2] = {4096, 128}; cuuint32_t b[3] = {64, 64, 2};
      ok &= encode(fn, &mHs, pHs, 3, d, s, b); }
    { cuuint64_t d[2] = {3584, 2048}, s[1] = {7168}; cuuint32_t b[2] = {64, 128};
      ok &= encode(fn, &mHf, pHf, 2, d, s, b); }
    { cuuint64_t d[2] = {1024, 1024}, s[1] = {2048}; cuuint32_t b[2] = {64, 128};
      ok &= encode(fn, &mCre, C_re, 2, d, s, b); ok &= encode(fn, &mCim, C_im, 2, d, s, b); }
    { cuuint64_t d[5] = {64, 2, 448, 4, 16}, s[4] = {2048, 8 * 2048, 2 * 2048, 128}; cuuint32_t b[5] = {64, 2, 4, 4, 2};
      ok &= encode(fn, &mW2, w2, 5, d, s, b); }
    { cuuint64_t d[3] = {64, 3584, 16}, s[2] = {2048, 128}; cuuint32_t b[3] = {64, 32, 2};
      ok &= encode(fn, &mW2n, w2, 3, d, s, b); }
    if (!ok) return;

    fused_kernel<<<128, 384, kSmemBytes, stream>>>(mB, mXs, mXf, mW1b, mW1a, mHs, mHf, mCre, mCim, mW2, mW2n, p);
}
```

```cpp
#include <cuda_runtime.h>
#include <cuda_bf16.h>
#include <cuda_fp16.h>
#include <cuda.h>
#include <stdint.h>
#include <stddef.h>

#define XLDKB 40
#define PF0LINES 1
#define ETKB 60
#define PFKB 80
#define RXT 2
#define MC0 0
#define PFTOP 0
#define INITW 0
#define PRODCOND warp >= 8
#define ORDER 0

namespace {

constexpr int kD = 1024, kF = 3584;
constexpr int kStages = 4;
constexpr int kStageBytes = 49152;
constexpr int kABytes = 16384;
constexpr int kXOff = kStages * kStageBytes;
constexpr int kTabOff = kXOff + 2048;
constexpr int kGateOff = kXOff + 32768;
constexpr int kBiasOff = kGateOff + 4 * 72 * 2;
constexpr int kBarOff = kBiasOff + 88 * 16;
constexpr int kSmemBytes = 232448;
static_assert(kBarOff + 160 <= kSmemBytes, "smem");
constexpr int kXBytes = 33792;
constexpr uint32_t kSmemOrg = 1024;
constexpr unsigned kSpinLimit = 1u << 18;
constexpr int kTotal = 92;

__host__ __device__ constexpr int pass2_kb(int s) {
    return s < 2 ? 6 : s < 8 ? 7 : s < 12 ? 8 : s < 18 ? 9 : s < 22 ? 10 : s < 28 ? 11 : s < 32 ? 12 : s < 38 ? 13 : s < 42 ? 14 : s < 48 ? 15 : s < 56 ? 16 : 17;
}

struct Scratch {
    unsigned claim[64];
    unsigned epoch, pad0[31];
    unsigned done, pad1[31];
    unsigned cnt[40 * 32];
    uint2 gate[2048];
    uint4 agg[8 * 1024];
    __align__(1024) uint8_t X[128 * kXBytes];
    __align__(1024) __nv_bfloat16 Hs[2048 * 2048];
    __align__(1024) __nv_bfloat16 Hf[2048 * 3584];
    __align__(1024) __nv_bfloat16 Bcopy[2 * 1024 * 1024];
};
__device__ Scratch g_s;

#define TRAP() break
#define PIN_F(x) asm volatile("" : "+f"(x))
#define PIN_R(x) asm volatile("" : "+r"(x))
#define UNDEF_F(x) asm volatile("" : "=f"(x))
#define UNDEF_R(x) asm volatile("" : "=r"(x))
#define RESPIN()
__device__ __forceinline__ uint32_t smem_u32(const void* p) { return (uint32_t)__cvta_generic_to_shared(p); }
__device__ __forceinline__ void mbar_init(uint32_t bar, uint32_t count) {
    asm volatile("mbarrier.init.shared::cta.b64 [%0], %1;" ::"r"(bar), "r"(count) : "memory");
}
__device__ __forceinline__ void mbar_expect_tx(uint32_t bar, uint32_t bytes) {
    asm volatile("mbarrier.arrive.expect_tx.shared::cta.b64 _, [%0], %1;" ::"r"(bar), "r"(bytes) : "memory");
}
__device__ __forceinline__ void mbar_wait(uint32_t bar, uint32_t parity) {
    asm volatile(
        "{\n.reg .pred p;\n.reg .u32 n;\n"
        "mbarrier.try_wait.parity.shared::cta.b64 p, [%0], %1;\n"
        "@p bra DONE;\n"
        "mov.u32 n, 0;\n"
        "LOOP:\n"
        "mbarrier.try_wait.parity.shared::cta.b64 p, [%0], %1;\n"
        "@p bra DONE;\n"
        "add.u32 n, n, 1;\n"
        "setp.lt.u32 p, n, %2;\n"
        "@p bra LOOP;\n"
        "DONE:\n}\n"
        ::"r"(bar), "r"(parity), "n"(kSpinLimit) : "memory");
}
__device__ __forceinline__ void sched_fence(uint32_t nonzero) {
    asm volatile("{\n.reg .pred p;\n.reg .u32 n;\nsetp.ne.u32 p, %0, 0;\n@p bra DONE;\nLOOP:\nmov.u32 n, %%clock;\n"
                 "setp.eq.u32 p, n, 0;\n@p bra LOOP;\nDONE:\n}\n" ::"r"(nonzero) : "memory");
}
__device__ __forceinline__ void mbar_arrive_local(uint32_t bar) {
    asm volatile("mbarrier.arrive.shared::cta.b64 _, [%0];" ::"r"(bar) : "memory");
}
__device__ __forceinline__ void mbar_arrive_cluster(uint32_t cluster_addr) {
    asm volatile("mbarrier.arrive.shared::cluster.b64 _, [%0];" ::"r"(cluster_addr) : "memory");
}
__device__ __forceinline__ uint32_t mapa(uint32_t addr, uint32_t rank) {
    uint32_t r;
    asm("mapa.shared::cluster.u32 %0, %1, %2;" : "=r"(r) : "r"(addr), "r"(rank));
    return r;
}
__device__ __forceinline__ void cluster_arrive() { asm volatile("barrier.cluster.arrive.relaxed.aligned;" ::: "memory"); }
__device__ __forceinline__ void cluster_wait() { asm volatile("barrier.cluster.wait.acquire.aligned;" ::: "memory"); }
__device__ __forceinline__ void bar_sync(int id, int n) { asm volatile("bar.sync %0, %1;" ::"r"(id), "r"(n) : "memory"); }
__device__ __forceinline__ void bar_arrive(int id, int n) { asm volatile("bar.arrive %0, %1;" ::"r"(id), "r"(n) : "memory"); }
__device__ __forceinline__ bool elect_one() {
    uint32_t p;
    asm volatile("{\n.reg .pred P;\nelect.sync _|P, 0xffffffff;\nselp.u32 %0, 1, 0, P;\n}\n" : "=r"(p));
    return p != 0;
}

__device__ __forceinline__ void tma2(uint32_t dst, const CUtensorMap* m, uint32_t bar, int c0, int c1) {
    asm volatile("cp.async.bulk.tensor.2d.shared::cluster.global.mbarrier::complete_tx::bytes [%0], [%1, {%3, %4}], [%2];"
                 ::"r"(dst), "l"(m), "r"(bar), "r"(c0), "r"(c1) : "memory");
}
__device__ __forceinline__ void tma3(uint32_t dst, const CUtensorMap* m, uint32_t bar, int c0, int c1, int c2) {
    asm volatile("cp.async.bulk.tensor.3d.shared::cluster.global.mbarrier::complete_tx::bytes [%0], [%1, {%3, %4, %5}], [%2];"
                 ::"r"(dst), "l"(m), "r"(bar), "r"(c0), "r"(c1), "r"(c2) : "memory");
}
__device__ __forceinline__ void tma4(uint32_t dst, const CUtensorMap* m, uint32_t bar, int c0, int c1, int c2, int c3) {
    asm volatile("cp.async.bulk.tensor.4d.shared::cluster.global.mbarrier::complete_tx::bytes [%0], [%1, {%3, %4, %5, %6}], [%2];"
                 ::"r"(dst), "l"(m), "r"(bar), "r"(c0), "r"(c1), "r"(c2), "r"(c3) : "memory");
}
__device__ __forceinline__ void tma5(uint32_t dst, const CUtensorMap* m, uint32_t bar, int c0, int c1, int c2, int c3, int c4) {
    asm volatile("cp.async.bulk.tensor.5d.shared::cluster.global.mbarrier::complete_tx::bytes [%0], [%1, {%3, %4, %5, %6, %7}], [%2];"
                 ::"r"(dst), "l"(m), "r"(bar), "r"(c0), "r"(c1), "r"(c2), "r"(c3), "r"(c4) : "memory");
}
__device__ __forceinline__ void tma2_mc(uint32_t dst, const CUtensorMap* m, uint32_t bar, int c0, int c1) {
    asm volatile("cp.async.bulk.tensor.2d.shared::cluster.global.mbarrier::complete_tx::bytes.multicast::cluster [%0], [%1, {%3, %4}], [%2], %5;"
                 ::"r"(dst), "l"(m), "r"(bar), "r"(c0), "r"(c1), "h"((uint16_t)3) : "memory");
}
__device__ __forceinline__ void tma3_mc(uint32_t dst, const CUtensorMap* m, uint32_t bar, int c0, int c1, int c2) {
    asm volatile("cp.async.bulk.tensor.3d.shared::cluster.global.mbarrier::complete_tx::bytes.multicast::cluster [%0], [%1, {%3, %4, %5}], [%2], %6;"
                 ::"r"(dst), "l"(m), "r"(bar), "r"(c0), "r"(c1), "r"(c2), "h"((uint16_t)3) : "memory");
}
__device__ __forceinline__ void tma5_mc(uint32_t dst, const CUtensorMap* m, uint32_t bar, int c0, int c1, int c2, int c3, int c4) {
    asm volatile("cp.async.bulk.tensor.5d.shared::cluster.global.mbarrier::complete_tx::bytes.multicast::cluster [%0], [%1, {%3, %4, %5, %6, %7}], [%2], %8;"
                 ::"r"(dst), "l"(m), "r"(bar), "r"(c0), "r"(c1), "r"(c2), "r"(c3), "r"(c4), "h"((uint16_t)3) : "memory");
}
__device__ __forceinline__ void tma3_pf(const CUtensorMap* m, int c0, int c1, int c2) {
    asm volatile("cp.async.bulk.prefetch.tensor.3d.L2.global [%0, {%1, %2, %3}];" ::"l"(m), "r"(c0), "r"(c1), "r"(c2) : "memory");
}
__device__ __forceinline__ void bulk_store(void* dst, uint32_t src, uint32_t bytes) {
    asm volatile("cp.async.bulk.global.shared::cta.bulk_group [%0], [%1], %2;" ::"l"(dst), "r"(src), "r"(bytes) : "memory");
}
__device__ __forceinline__ void bulk_load(uint32_t dst, const void* src, uint32_t bytes, uint32_t bar) {
    asm volatile("cp.async.bulk.shared::cluster.global.mbarrier::complete_tx::bytes [%0], [%1], %2, [%3];"
                 ::"r"(dst), "l"(src), "r"(bytes), "r"(bar) : "memory");
}
__device__ __forceinline__ unsigned atom_exch(unsigned* p, unsigned v) {
    unsigned r;
    asm volatile("atom.relaxed.gpu.global.exch.b32 %0, [%1], %2;" : "=r"(r) : "l"(p), "r"(v) : "memory");
    return r;
}
__device__ __forceinline__ void st_async32(uint32_t a, uint32_t v, uint32_t bar) {
    asm volatile("st.async.shared::cluster.mbarrier::complete_tx::bytes.u32 [%0], %1, [%2];" ::"r"(a), "r"(v), "r"(bar) : "memory");
}
__device__ __forceinline__ void sts128f(uint32_t a, float x, float y, float z, float w) {
    asm volatile("st.shared.v4.f32 [%0], {%1, %2, %3, %4};" ::"r"(a), "f"(x), "f"(y), "f"(z), "f"(w) : "memory");
}
__device__ __forceinline__ void prefetch_map(const CUtensorMap* m) {
    asm volatile("prefetch.tensormap [%0];" ::"l"(m) : "memory");
}

__device__ __forceinline__ void prefetch_l2(const void* p, uint32_t bytes) {
    asm volatile("cp.async.bulk.prefetch.L2.global [%0], %1;" ::"l"(p), "r"(bytes) : "memory");
}

__device__ __forceinline__ void wgmma_fence() { asm volatile("wgmma.fence.sync.aligned;" ::: "memory"); }
__device__ __forceinline__ void wgmma_commit() { asm volatile("wgmma.commit_group.sync.aligned;" ::: "memory"); }
template <int N>
__device__ __forceinline__ void wgmma_wait() { asm volatile("wgmma.wait_group.sync.aligned %0;" ::"n"(N) : "memory"); }

__device__ __forceinline__ uint32_t pack_bf16(float lo, float hi) {
    uint32_t r;
    asm("cvt.rn.bf16x2.f32 %0, %1, %2;" : "=r"(r) : "f"(hi), "f"(lo));
    return r;
}
__device__ __forceinline__ uint32_t pack_f16(float lo, float hi) {
    uint32_t r;
    asm("cvt.rn.f16x2.f32 %0, %1, %2;" : "=r"(r) : "f"(hi), "f"(lo));
    return r;
}
__device__ __forceinline__ uint32_t pack_bf16_v(float lo, float hi) {
    uint32_t r;
    asm volatile("cvt.rn.bf16x2.f32 %0, %1, %2;" : "=r"(r) : "f"(hi), "f"(lo));
    return r;
}
template <int LUT>
__device__ __forceinline__ uint32_t lop3(uint32_t a, uint32_t b, uint32_t c) {
    uint32_t r;
    asm("lop3.b32 %0, %1, %2, %3, %4;" : "=r"(r) : "r"(a), "r"(b), "r"(c), "n"(LUT));
    return r;
}
__device__ __forceinline__ float bf_lo(uint32_t v) { return __uint_as_float(v << 16); }
__device__ __forceinline__ float bf_hi(uint32_t v) { return __uint_as_float(v & 0xffff0000u); }
__device__ __forceinline__ float bf16_round(float v) { return __bfloat162float(__float2bfloat16_rn(v)); }
__device__ __forceinline__ uint32_t bf2_mul(uint32_t a, uint32_t b) {
    uint32_t r;
    asm("mul.rn.bf16x2 %0, %1, %2;" : "=r"(r) : "r"(a), "r"(b));
    return r;
}
__device__ __forceinline__ uint32_t bf2_add_relu(uint32_t a, uint32_t b) {
    uint32_t r;
    asm("fma.rn.relu.bf16x2 %0, %1, %2, %3;" : "=r"(r) : "r"(a), "r"(0x3f803f80u), "r"(b));
    return r;
}
__device__ __forceinline__ uint4 ldg128(const void* p) {
    uint4 v;
    asm volatile("ld.global.nc.v4.u32 {%0, %1, %2, %3}, [%4];" : "=r"(v.x), "=r"(v.y), "=r"(v.z), "=r"(v.w) : "l"(p));
    return v;
}
__device__ __forceinline__ uint32_t ldg32(const void* p) {
    uint32_t v;
    asm volatile("ld.global.nc.u32 %0, [%1];" : "=r"(v) : "l"(p));
    return v;
}
__device__ __forceinline__ uint32_t ldg32na(const void* p) {
    uint32_t v;
    asm volatile("ld.global.nc.L1::no_allocate.u32 %0, [%1];" : "=r"(v) : "l"(p));
    return v;
}
__device__ __forceinline__ uint32_t ldg16(const __nv_bfloat16* p) {
    uint32_t v;
    asm volatile("ld.global.nc.u16 %0, [%1];" : "=r"(v) : "l"(p));
    return v;
}
__device__ __forceinline__ uint4 ld_relaxed128(const void* p) {
    uint4 v;
    asm volatile("ld.relaxed.gpu.global.v4.u32 {%0, %1, %2, %3}, [%4];" : "=r"(v.x), "=r"(v.y), "=r"(v.z), "=r"(v.w) : "l"(p) : "memory");
    return v;
}
__device__ __forceinline__ uint2 ld_relaxed64(const void* p) {
    unsigned long long v;
    asm volatile("ld.relaxed.gpu.global.u64 %0, [%1];" : "=l"(v) : "l"(p) : "memory");
    return make_uint2((uint32_t)v, (uint32_t)(v >> 32));
}
__device__ __forceinline__ void st_relaxed64(void* p, uint32_t lo, uint32_t hi) {
    unsigned long long v = ((unsigned long long)hi << 32) | lo;
    asm volatile("st.relaxed.gpu.global.u64 [%0], %1;" ::"l"(p), "l"(v) : "memory");
}
__device__ __forceinline__ void st_relaxed2x64(void* p, uint32_t a, uint32_t b, uint32_t c, uint32_t d) {
    unsigned long long v0 = ((unsigned long long)b << 32) | a, v1 = ((unsigned long long)d << 32) | c;
    asm volatile("st.relaxed.gpu.global.v2.u64 [%0], {%1, %2};" ::"l"(p), "l"(v0), "l"(v1) : "memory");
}
__device__ __forceinline__ uint4 ld_relaxed2x64(const void* p) {
    unsigned long long v0, v1;
    asm volatile("ld.relaxed.gpu.global.v2.u64 {%0, %1}, [%2];" : "=l"(v0), "=l"(v1) : "l"(p) : "memory");
    return make_uint4((uint32_t)v0, (uint32_t)(v0 >> 32), (uint32_t)v1, (uint32_t)(v1 >> 32));
}
__device__ __forceinline__ void stg128(void* p, uint32_t a, uint32_t b, uint32_t c, uint32_t d) {
    asm volatile("st.global.v4.u32 [%0], {%1, %2, %3, %4};" ::"l"(p), "r"(a), "r"(b), "r"(c), "r"(d) : "memory");
}
__device__ __forceinline__ void stg64f(void* p, float a, float b) {
    asm volatile("st.global.v2.f32 [%0], {%1, %2};" ::"l"(p), "f"(a), "f"(b) : "memory");
}
__device__ __forceinline__ uint4 lds128(uint32_t a) {
    uint4 v;
    asm volatile("ld.shared.v4.u32 {%0, %1, %2, %3}, [%4];" : "=r"(v.x), "=r"(v.y), "=r"(v.z), "=r"(v.w) : "r"(a) : "memory");
    return v;
}
__device__ __forceinline__ uint2 lds64(uint32_t a) {
    uint2 v;
    asm volatile("ld.shared.v2.u32 {%0, %1}, [%2];" : "=r"(v.x), "=r"(v.y) : "r"(a) : "memory");
    return v;
}
__device__ __forceinline__ uint4 ldsm4(uint32_t a) {
    uint4 v;
    asm volatile("ldmatrix.sync.aligned.m8n8.x4.shared.b16 {%0, %1, %2, %3}, [%4];" : "=r"(v.x), "=r"(v.y), "=r"(v.z), "=r"(v.w) : "r"(a) : "memory");
    return v;
}
__device__ __forceinline__ uint32_t lds16(uint32_t a) {
    uint32_t v;
    asm volatile("ld.shared.u16 %0, [%1];" : "=r"(v) : "r"(a) : "memory");
    return v;
}
__device__ __forceinline__ void sts16(uint32_t a, uint32_t x) {
    asm volatile("st.shared.u16 [%0], %1;" ::"r"(a), "h"((uint16_t)x) : "memory");
}
__device__ __forceinline__ void st_relaxed32(void* p, uint32_t v) {
    asm volatile("st.relaxed.gpu.global.u32 [%0], %1;" ::"l"(p), "r"(v) : "memory");
}
__device__ __forceinline__ float lds32f(uint32_t a) {
    float v;
    asm volatile("ld.shared.f32 %0, [%1];" : "=f"(v) : "r"(a) : "memory");
    return v;
}
__device__ __forceinline__ void sts128(uint32_t a, uint32_t x, uint32_t y, uint32_t z, uint32_t w) {
    asm volatile("st.shared.v4.u32 [%0], {%1, %2, %3, %4};" ::"r"(a), "r"(x), "r"(y), "r"(z), "r"(w) : "memory");
}
__device__ __forceinline__ void sts64f(uint32_t a, float x, float y) {
    asm volatile("st.shared.v2.f32 [%0], {%1, %2};" ::"r"(a), "f"(x), "f"(y) : "memory");
}
__device__ __forceinline__ float4 lds128f(uint32_t a) {
    float4 v;
    asm volatile("ld.shared.v4.f32 {%0, %1, %2, %3}, [%4];" : "=f"(v.x), "=f"(v.y), "=f"(v.z), "=f"(v.w) : "r"(a) : "memory");
    return v;
}
__device__ __forceinline__ uint32_t lds32(uint32_t a) {
    uint32_t v;
    asm volatile("ld.shared.u32 %0, [%1];" : "=r"(v) : "r"(a) : "memory");
    return v;
}
__device__ __forceinline__ void sts32(uint32_t a, uint32_t x) {
    asm volatile("st.shared.u32 [%0], %1;" ::"r"(a), "r"(x) : "memory");
}
__device__ __forceinline__ void stg128f(void* p, float a, float b, float c, float d) {
    asm volatile("st.global.v4.f32 [%0], {%1, %2, %3, %4};" ::"l"(p), "f"(a), "f"(b), "f"(c), "f"(d) : "memory");
}
__device__ __forceinline__ unsigned ld_relaxed32(const unsigned* p) {
    unsigned v;
    asm volatile("ld.relaxed.gpu.global.u32 %0, [%1];" : "=r"(v) : "l"(p) : "memory");
    return v;
}
__device__ __forceinline__ void wait_counter(const unsigned* p, unsigned target) {
    unsigned n = 0, v;
    while (true) {
        asm volatile("ld.acquire.gpu.global.u32 %0, [%1];" : "=r"(v) : "l"(p) : "memory");
        if ((int)(v - target) >= 0) break;
        if (++n > kSpinLimit) TRAP();
        __nanosleep(32);
    }
}
#define KT(IT, W) do { } while (0)
#define STAMP(cond, slot) do { } while (0)
#define STAMPA(cond, slot) STAMP(cond, slot)
#define STAMPB(cond, slot) do { } while (0)

template <int TA, int TB>
__device__ __forceinline__ void wgmma_n256(float (&d)[128], uint64_t da, uint64_t db, int keep) {
    asm volatile(
        "{\n.reg .pred p;\nsetp.ne.b32 p, %132, 0;\n"
        "wgmma.mma_async.sync.aligned.m64n256k16.f32.bf16.bf16 "
        "{%0, %1, %2, %3, %4, %5, %6, %7, %8, %9, %10, %11, %12, %13, %14, %15, "
        "%16, %17, %18, %19, %20, %21, %22, %23, %24, %25, %26, %27, %28, %29, %30, %31, "
        "%32, %33, %34, %35, %36, %37, %38, %39, %40, %41, %42, %43, %44, %45, %46, %47, "
        "%48, %49, %50, %51, %52, %53, %54, %55, %56, %57, %58, %59, %60, %61, %62, %63, "
        "%64, %65, %66, %67, %68, %69, %70, %71, %72, %73, %74, %75, %76, %77, %78, %79, "
        "%80, %81, %82, %83, %84, %85, %86, %87, %88, %89, %90, %91, %92, %93, %94, %95, "
        "%96, %97, %98, %99, %100, %101, %102, %103, %104, %105, %106, %107, %108, %109, %110, %111, "
        "%112, %113, %114, %115, %116, %117, %118, %119, %120, %121, %122, %123, %124, %125, %126, %127}, "
        "%128, %129, p, 1, 1, %130, %131;\n}\n"
        : "+f"(d[0]), "+f"(d[1]), "+f"(d[2]), "+f"(d[3]), "+f"(d[4]), "+f"(d[5]), "+f"(d[6]), "+f"(d[7]),
          "+f"(d[8]), "+f"(d[9]), "+f"(d[10]), "+f"(d[11]), "+f"(d[12]), "+f"(d[13]), "+f"(d[14]), "+f"(d[15]),
          "+f"(d[16]), "+f"(d[17]), "+f"(d[18]), "+f"(d[19]), "+f"(d[20]), "+f"(d[21]), "+f"(d[22]), "+f"(d[23]),
          "+f"(d[24]), "+f"(d[25]), "+f"(d[26]), "+f"(d[27]), "+f"(d[28]), "+f"(d[29]), "+f"(d[30]), "+f"(d[31]),
          "+f"(d[32]), "+f"(d[33]), "+f"(d[34]), "+f"(d[35]), "+f"(d[36]), "+f"(d[37]), "+f"(d[38]), "+f"(d[39]),
          "+f"(d[40]), "+f"(d[41]), "+f"(d[42]), "+f"(d[43]), "+f"(d[44]), "+f"(d[45]), "+f"(d[46]), "+f"(d[47]),
          "+f"(d[48]), "+f"(d[49]), "+f"(d[50]), "+f"(d[51]), "+f"(d[52]), "+f"(d[53]), "+f"(d[54]), "+f"(d[55]),
          "+f"(d[56]), "+f"(d[57]), "+f"(d[58]), "+f"(d[59]), "+f"(d[60]), "+f"(d[61]), "+f"(d[62]), "+f"(d[63]),
          "+f"(d[64]), "+f"(d[65]), "+f"(d[66]), "+f"(d[67]), "+f"(d[68]), "+f"(d[69]), "+f"(d[70]), "+f"(d[71]),
          "+f"(d[72]), "+f"(d[73]), "+f"(d[74]), "+f"(d[75]), "+f"(d[76]), "+f"(d[77]), "+f"(d[78]), "+f"(d[79]),
          "+f"(d[80]), "+f"(d[81]), "+f"(d[82]), "+f"(d[83]), "+f"(d[84]), "+f"(d[85]), "+f"(d[86]), "+f"(d[87]),
          "+f"(d[88]), "+f"(d[89]), "+f"(d[90]), "+f"(d[91]), "+f"(d[92]), "+f"(d[93]), "+f"(d[94]), "+f"(d[95]),
          "+f"(d[96]), "+f"(d[97]), "+f"(d[98]), "+f"(d[99]), "+f"(d[100]), "+f"(d[101]), "+f"(d[102]), "+f"(d[103]),
          "+f"(d[104]), "+f"(d[105]), "+f"(d[106]), "+f"(d[107]), "+f"(d[108]), "+f"(d[109]), "+f"(d[110]), "+f"(d[111]),
          "+f"(d[112]), "+f"(d[113]), "+f"(d[114]), "+f"(d[115]), "+f"(d[116]), "+f"(d[117]), "+f"(d[118]), "+f"(d[119]),
          "+f"(d[120]), "+f"(d[121]), "+f"(d[122]), "+f"(d[123]), "+f"(d[124]), "+f"(d[125]), "+f"(d[126]), "+f"(d[127])
        : "l"(da), "l"(db), "n"(TA), "n"(TB), "r"(keep));
}
template <int TA, int TB>
__device__ __forceinline__ void wgmma_n192(float (&d)[128], uint64_t da, uint64_t db, int keep) {
    asm volatile(
        "{\n.reg .pred p;\nsetp.ne.b32 p, %100, 0;\n"
        "wgmma.mma_async.sync.aligned.m64n192k16.f32.bf16.bf16 "
        "{%0, %1, %2, %3, %4, %5, %6, %7, %8, %9, %10, %11, %12, %13, %14, %15, "
        "%16, %17, %18, %19, %20, %21, %22, %23, %24, %25, %26, %27, %28, %29, %30, %31, "
        "%32, %33, %34, %35, %36, %37, %38, %39, %40, %41, %42, %43, %44, %45, %46, %47, "
        "%48, %49, %50, %51, %52, %53, %54, %55, %56, %57, %58, %59, %60, %61, %62, %63, "
        "%64, %65, %66, %67, %68, %69, %70, %71, %72, %73, %74, %75, %76, %77, %78, %79, "
        "%80, %81, %82, %83, %84, %85, %86, %87, %88, %89, %90, %91, %92, %93, %94, %95}, "
        "%96, %97, p, 1, 1, %98, %99;\n}\n"
        : "+f"(d[0]), "+f"(d[1]), "+f"(d[2]), "+f"(d[3]), "+f"(d[4]), "+f"(d[5]), "+f"(d[6]), "+f"(d[7]),
          "+f"(d[8]), "+f"(d[9]), "+f"(d[10]), "+f"(d[11]), "+f"(d[12]), "+f"(d[13]), "+f"(d[14]), "+f"(d[15]),
          "+f"(d[16]), "+f"(d[17]), "+f"(d[18]), "+f"(d[19]), "+f"(d[20]), "+f"(d[21]), "+f"(d[22]), "+f"(d[23]),
          "+f"(d[24]), "+f"(d[25]), "+f"(d[26]), "+f"(d[27]), "+f"(d[28]), "+f"(d[29]), "+f"(d[30]), "+f"(d[31]),
          "+f"(d[32]), "+f"(d[33]), "+f"(d[34]), "+f"(d[35]), "+f"(d[36]), "+f"(d[37]), "+f"(d[38]), "+f"(d[39]),
          "+f"(d[40]), "+f"(d[41]), "+f"(d[42]), "+f"(d[43]), "+f"(d[44]), "+f"(d[45]), "+f"(d[46]), "+f"(d[47]),
          "+f"(d[48]), "+f"(d[49]), "+f"(d[50]), "+f"(d[51]), "+f"(d[52]), "+f"(d[53]), "+f"(d[54]), "+f"(d[55]),
          "+f"(d[56]), "+f"(d[57]), "+f"(d[58]), "+f"(d[59]), "+f"(d[60]), "+f"(d[61]), "+f"(d[62]), "+f"(d[63]),
          "+f"(d[64]), "+f"(d[65]), "+f"(d[66]), "+f"(d[67]), "+f"(d[68]), "+f"(d[69]), "+f"(d[70]), "+f"(d[71]),
          "+f"(d[72]), "+f"(d[73]), "+f"(d[74]), "+f"(d[75]), "+f"(d[76]), "+f"(d[77]), "+f"(d[78]), "+f"(d[79]),
          "+f"(d[80]), "+f"(d[81]), "+f"(d[82]), "+f"(d[83]), "+f"(d[84]), "+f"(d[85]), "+f"(d[86]), "+f"(d[87]),
          "+f"(d[88]), "+f"(d[89]), "+f"(d[90]), "+f"(d[91]), "+f"(d[92]), "+f"(d[93]), "+f"(d[94]), "+f"(d[95])
        : "l"(da), "l"(db), "n"(TA), "n"(TB), "r"(keep));
}
template <int TA, int TB>
__device__ __forceinline__ void wgmma_n128(float (&d)[128], uint64_t da, uint64_t db, int keep) {
    asm volatile(
        "{\n.reg .pred p;\nsetp.ne.b32 p, %68, 0;\n"
        "wgmma.mma_async.sync.aligned.m64n128k16.f32.bf16.bf16 "
        "{%0, %1, %2, %3, %4, %5, %6, %7, %8, %9, %10, %11, %12, %13, %14, %15, "
        "%16, %17, %18, %19, %20, %21, %22, %23, %24, %25, %26, %27, %28, %29, %30, %31, "
        "%32, %33, %34, %35, %36, %37, %38, %39, %40, %41, %42, %43, %44, %45, %46, %47, "
        "%48, %49, %50, %51, %52, %53, %54, %55, %56, %57, %58, %59, %60, %61, %62, %63}, "
        "%64, %65, p, 1, 1, %66, %67;\n}\n"
        : "+f"(d[0]), "+f"(d[1]), "+f"(d[2]), "+f"(d[3]), "+f"(d[4]), "+f"(d[5]), "+f"(d[6]), "+f"(d[7]),
          "+f"(d[8]), "+f"(d[9]), "+f"(d[10]), "+f"(d[11]), "+f"(d[12]), "+f"(d[13]), "+f"(d[14]), "+f"(d[15]),
          "+f"(d[16]), "+f"(d[17]), "+f"(d[18]), "+f"(d[19]), "+f"(d[20]), "+f"(d[21]), "+f"(d[22]), "+f"(d[23]),
          "+f"(d[24]), "+f"(d[25]), "+f"(d[26]), "+f"(d[27]), "+f"(d[28]), "+f"(d[29]), "+f"(d[30]), "+f"(d[31]),
          "+f"(d[32]), "+f"(d[33]), "+f"(d[34]), "+f"(d[35]), "+f"(d[36]), "+f"(d[37]), "+f"(d[38]), "+f"(d[39]),
          "+f"(d[40]), "+f"(d[41]), "+f"(d[42]), "+f"(d[43]), "+f"(d[44]), "+f"(d[45]), "+f"(d[46]), "+f"(d[47]),
          "+f"(d[48]), "+f"(d[49]), "+f"(d[50]), "+f"(d[51]), "+f"(d[52]), "+f"(d[53]), "+f"(d[54]), "+f"(d[55]),
          "+f"(d[56]), "+f"(d[57]), "+f"(d[58]), "+f"(d[59]), "+f"(d[60]), "+f"(d[61]), "+f"(d[62]), "+f"(d[63])
        : "l"(da), "l"(db), "n"(TA), "n"(TB), "r"(keep));
}
__device__ __forceinline__ void wgmma_n128_rs(float (&d)[128], uint32_t a0, uint32_t a1, uint32_t a2, uint32_t a3, uint64_t db) {
    asm volatile(
        "{\n.reg .pred p;\nsetp.ne.b32 p, 1, 0;\n"
        "wgmma.mma_async.sync.aligned.m64n128k16.f32.bf16.bf16 "
        "{%0, %1, %2, %3, %4, %5, %6, %7, %8, %9, %10, %11, %12, %13, %14, %15, "
        "%16, %17, %18, %19, %20, %21, %22, %23, %24, %25, %26, %27, %28, %29, %30, %31, "
        "%32, %33, %34, %35, %36, %37, %38, %39, %40, %41, %42, %43, %44, %45, %46, %47, "
        "%48, %49, %50, %51, %52, %53, %54, %55, %56, %57, %58, %59, %60, %61, %62, %63}, "
        "{%64, %65, %66, %67}, %68, p, 1, 1, 1;\n}\n"
        : "+f"(d[0]), "+f"(d[1]), "+f"(d[2]), "+f"(d[3]), "+f"(d[4]), "+f"(d[5]), "+f"(d[6]), "+f"(d[7]),
          "+f"(d[8]), "+f"(d[9]), "+f"(d[10]), "+f"(d[11]), "+f"(d[12]), "+f"(d[13]), "+f"(d[14]), "+f"(d[15]),
          "+f"(d[16]), "+f"(d[17]), "+f"(d[18]), "+f"(d[19]), "+f"(d[20]), "+f"(d[21]), "+f"(d[22]), "+f"(d[23]),
          "+f"(d[24]), "+f"(d[25]), "+f"(d[26]), "+f"(d[27]), "+f"(d[28]), "+f"(d[29]), "+f"(d[30]), "+f"(d[31]),
          "+f"(d[32]), "+f"(d[33]), "+f"(d[34]), "+f"(d[35]), "+f"(d[36]), "+f"(d[37]), "+f"(d[38]), "+f"(d[39]),
          "+f"(d[40]), "+f"(d[41]), "+f"(d[42]), "+f"(d[43]), "+f"(d[44]), "+f"(d[45]), "+f"(d[46]), "+f"(d[47]),
          "+f"(d[48]), "+f"(d[49]), "+f"(d[50]), "+f"(d[51]), "+f"(d[52]), "+f"(d[53]), "+f"(d[54]), "+f"(d[55]),
          "+f"(d[56]), "+f"(d[57]), "+f"(d[58]), "+f"(d[59]), "+f"(d[60]), "+f"(d[61]), "+f"(d[62]), "+f"(d[63])
        : "r"(a0), "r"(a1), "r"(a2), "r"(a3), "l"(db));
}

constexpr uint64_t kDescHi = (uint64_t)(64u | 0x40000000u) << 32;
template <int MODE>
__device__ __forceinline__ void mma_kblock(float (&acc)[128], uint32_t a_lo, uint32_t b_lo, int keep) {
    constexpr uint32_t HALF = (MODE == 1) ? 12288u : 16384u;
    constexpr bool BN = (MODE == 1 || MODE == 2 || MODE == 4);
#pragma unroll
    for (int kk = 0; kk < 4; ++kk) {
        const uint32_t ao = (MODE == 3) ? kk * 2048u : kk * 32u;
        const uint32_t bo = BN ? ((kk >> 1) * HALF + (kk & 1) * 2048u) : kk * 32u;
        const uint64_t da = kDescHi | (uint64_t)(a_lo + (ao >> 4) + (1u << 16));
        const uint64_t db = kDescHi | (uint64_t)(b_lo + (bo >> 4) + (BN ? (256u << 16) : (1u << 16)));
        if (MODE == 1) wgmma_n192<0, 1>(acc, da, db, kk == 0 ? keep : 1);
        else if (MODE == 4) wgmma_n128<0, 1>(acc, da, db, 1);
        else wgmma_n256<(MODE == 3), BN>(acc, da, db, kk == 0 ? keep : 1);
    }
}

struct Params {
    Scratch* s;
    const __nv_bfloat16* x;
    const __nv_bfloat16* b_re;
    const __nv_bfloat16* b_im;
    const __nv_bfloat16* gate_w;
    const __nv_bfloat16* lam_re;
    const __nv_bfloat16* lam_im;
    const __nv_bfloat16* log_dt;
    const __nv_bfloat16* dskip;
    const __nv_bfloat16* b1;
    const __nv_bfloat16* b2;
    float* out;
    int swap;
};

#define CMUL(rr, ri, ar, ai, br, bi) do { float _r = (ar) * (br) - (ai) * (bi); float _i = (ar) * (bi) + (ai) * (br); rr = _r; ri = _i; } while (0)
#define CFMA(rr, ri, ar, ai, br, bi) do { float _r = fmaf(-(ai), (bi), fmaf((ar), (br), rr)); float _i = fmaf((ai), (br), fmaf((ar), (bi), ri)); rr = _r; ri = _i; } while (0)

#define KB_OPEN(IT, LAST)                                                                        \
    KT(IT, 0);                                                                                   \
    if (ORDER && (LAST) && wg == 1) bar_sync(7, 256);                                            \
    mbar_wait(bar_full + 8 * ((IT) & 3), ((IT) >> 2) & 1);                                \
    KT(IT, 1);
#define KB_CLOSE(IT, LAST, REL)                                                                  \
    if (ORDER && (LAST) && wg == 0) bar_arrive(7, 256);                                          \
    wgmma_wait<1>();                                                                             \
    if (lane < 2 && (REL)) mbar_arrive_cluster(rel_addr + 8 * (((IT) - 1) & 3));
#define KBLOCK(MODE, IT, FIRST, LAST)                                                            \
    {                                                                                            \
        const uint32_t so = ((IT) & 3) * (kStageBytes >> 4);                                     \
        KB_OPEN(IT, LAST);                                                                       \
        wgmma_fence();                                                                           \
        mma_kblock<MODE>(acc, a_lo + so, b_lo + so, !(FIRST));                                   \
        wgmma_commit();                                                                          \
        KB_CLOSE(IT, LAST, !(FIRST));                                                            \
    }
#define TILE_END() do { wgmma_wait<0>(); if (lane < 2) mbar_arrive_cluster(rel_addr + 24); } while (0)

__global__ void __cluster_dims__(2, 1, 1) __launch_bounds__(384, 1)
fused_kernel(const __grid_constant__ CUtensorMap mB, const __grid_constant__ CUtensorMap mXs, const __grid_constant__ CUtensorMap mXf,
             const __grid_constant__ CUtensorMap mW1b, const __grid_constant__ CUtensorMap mW1a, const __grid_constant__ CUtensorMap mHs,
             const __grid_constant__ CUtensorMap mHf, const __grid_constant__ CUtensorMap mCre, const __grid_constant__ CUtensorMap mCim,
             const __grid_constant__ CUtensorMap mW2, const __grid_constant__ CUtensorMap mW2n, const Params p) {
    extern __shared__ __align__(1024) uint8_t smem_raw[];
    if (PFTOP) { prefetch_map(&mB); prefetch_map(&mXs); }
    const uint32_t sbase = smem_u32(smem_raw);
    if ((sbase & 0x3ffffu) != kSmemOrg) return;
    const uint32_t bar_full = sbase + kBarOff, bar_empty = bar_full + 32, bar_dep = bar_full + 64;
    const uint32_t bar_x = bar_full + 88, bar_c = bar_full + 96, role_s = bar_full + 104, bar_role = bar_full + 120, tag_s = bar_full + 112 + (threadIdx.x & 1) * 4;

    const int tid = threadIdx.x, lane = tid & 31;
    const int warp = __shfl_sync(0xffffffffu, tid >> 5, 0);
    const uint32_t rank = blockIdx.x & 1;

    int pref;
    {
        unsigned smid;
        asm("mov.u32 %0, %%smid;" : "=r"(smid));
        const int t = smid >> 1, u = t - 32, d = (u * 37) >> 8;
        pref = (t < 32) ? (t & 7) * 8 + (t >> 3) : (t < 60) ? (1 + u - 7 * d) * 8 + 4 + d : ((t - 58) & 7);
    }
    STAMP(tid == 0, 0);
    int role = pref;
#define ROLE_VARS()                                                                                               \
    const int c = role >> 3;                                                             \
    const int j8 = role & 7;                                                        \
    const int cb = j8 * 2 + (int)rank;                                             \
    const int rb = 2 * c + (int)rank;                                               \
    const int kh = j8 >> 2;                 \
    const int colK = (j8 & 3) * 256 + kh * 128, colS = colK ^ 128;    \
    (void)cb; (void)rb; (void)colS;

#define INIT_ALL()                                                                                    \
    if (warp == INITW && elect_one()) {                                                               \
        if (!PFTOP) { prefetch_map(&mB); prefetch_map(&mXs); }                                        \
        _Pragma("unroll") for (int s = 0; s < kStages; ++s) {                                         \
            mbar_init(bar_full + 8 * s, 1);                                                           \
            mbar_init(bar_empty + 8 * s, 16);                                                         \
            mbar_init(bar_dep + 8 * s, 1);                                \
        }                                                                                             \
        mbar_init(bar_c, 96);                                                                         \
        mbar_init(bar_role, 1);                                                                       \
        asm volatile("fence.mbarrier_init.release.cluster;\nfence.proxy.async.shared::cta;" ::: "memory"); \
        mbar_expect_tx(bar_full, 49152);            \
        tma4(sbase, &mB, bar_full, 0, 0, 0, ((pref & 7) * 2 + (int)rank) * 8);                        \
        if (!MC0) {                                                                                   \
        tma5(sbase + kABytes, &mXs, bar_full, 0, 0, 0, 0, pref >> 3);                                 \
        tma5(sbase + kABytes + 16384, &mXs, bar_full, 0, 0, 0, 16, pref >> 3);                        \
        }                                                                                             \
        mbar_expect_tx(bar_x, 2048);                                                                  \
        bulk_load(sbase + kXOff, p.gate_w, 2048, bar_x);                                              \
        mbar_expect_tx(bar_role, 8);                                                                  \
    }
    if (PRODCOND) {
        asm volatile("setmaxnreg.dec.sync.aligned.u32 24;");
        unsigned taken = 0;
        if (tid == 352 && rank == 0) {
            taken = atom_exch(&p.s->claim[pref], 1u);
        }
        __syncwarp();
        cluster_arrive();
        cluster_wait();
        if (warp > 8) {
            if (tid == 352) {
#pragma unroll 1
                for (int i = 0; taken != 0 && i < 64; ++i) { role = i + 256; taken = atom_exch(&p.s->claim[i], 1u); }
                st_async32(mapa(role_s + 4 * rank, 0), role, mapa(bar_role, 0));
                st_async32(mapa(role_s + 4 * rank, 1), role, mapa(bar_role, 1));
            }
            __syncwarp();
            mbar_wait(bar_role, 0);
            role = __shfl_sync(0xffffffffu, (int)lds32(role_s), 0) & 63;
            ROLE_VARS();
            if (warp == 11) {
                if (lane < 9) prefetch_map(&mXf + lane);
#pragma unroll 1
                for (int en = lane; en < 88; en += 32) {
                    const int J = en >> 2;
                    const __nv_bfloat16* src = ((J < 14) ? p.b1 : (J < 18) ? p.dskip : p.b2) + 32 * J + 2 * (en & 3) +
                                               ((J < 6) ? 2048 + 192 * j8 : (J < 14) ? 256 * j8 - 192 : colK - ((J < 18) ? 448 : 576));
                    sts128(sbase + kBiasOff + en * 16, ldg32(src), ldg32(src + 8), ldg32(src + 16), ldg32(src + 24));
                }
                mbar_arrive_local(bar_c);
            } else {
                {
                    sts32(tag_s, ld_relaxed32(&p.s->epoch) + 1);
                    const int ch = cb * 64 + (tid - 288);
                    const uint32_t t_s = sbase + kTabOff + (tid - 288) * 64;
                    const float Lr = bf_lo(ldg16(p.lam_re + ch)), Li = bf_lo(ldg16(p.lam_im + ch));
                    const float dt = bf16_round(expf(bf_lo(ldg16(p.log_dt + ch))));
                    const float ea = expf(dt * Lr);
                    float lr, li;
                    sincospif((dt * Li) * 0.31830988618379067f, &li, &lr);
                    lr *= ea; li *= ea;
                    const float nr = lr - 1.0f, ni = li;
                    const bool big = fabsf(Lr) >= fabsf(Li);
                    const float u = big ? Lr : Li, v = big ? Li : Lr;
                    const float t = v / u, d = 2.0f / fmaf(v, t, u);
                    const float cr = (big ? fmaf(ni, t, nr) : fmaf(nr, t, ni)) * d, ci = (big ? fmaf(-nr, t, ni) : fmaf(ni, t, -nr)) * d;
                    if (p.swap) li = -li;
                    const float m00 = p.swap ? -ci : cr, m01 = p.swap ? cr : -ci, m10 = p.swap ? -cr : -ci, m11 = p.swap ? -ci : -cr;
#pragma unroll
                    for (int q = 0; q < 4; ++q) {
                        sts128f(t_s + q * 16, lr, li, m00, m01);
                        sts128f(t_s + 12288 + q * 16, 0.f, 0.f, 0.f, 0.f);
                    }
#pragma unroll 1
                    for (int i = 0; i < 6; ++i) CMUL(lr, li, lr, li, lr, li);
                    float ar, ai, br, bi;
                    CMUL(ar, ai, lr, li, lr, li);
                    CMUL(br, bi, ar, ai, lr, li);
                    sts128f(t_s + 4096, m10, m11, 0.f, 0.f);
#pragma unroll
                    for (int q = 1; q < 4; ++q) sts128f(t_s + 4096 + q * 16, m10, m11, lr, li);
                    sts128f(t_s + 8192, 0.f, 0.f, 1.f, 0.f);
                    sts128f(t_s + 8192 + 16, 0.f, 0.f, lr, li);
                    sts128f(t_s + 8192 + 32, ar, ai, ar, ai);
                    sts128f(t_s + 8192 + 48, ar, ai, br, bi);
                    CMUL(ar, ai, ar, ai, ar, ai);
                    br = 1.f; bi = 0.f;
#pragma unroll 1
                    for (int k = c - 1; k >= 0; --k) {
                        sts64f(t_s + 12288 + (k & 3) * 16 + (k >> 2) * 8, br, bi);
                        CMUL(br, bi, br, bi, ar, ai);
                    }
                    mbar_arrive_local(bar_c);
                }
                if (warp == 9) {
#pragma unroll 1
                    for (int ev = 0; ev < 3; ++ev) {
                        if (ev == 2) {
                            uint8_t* box = p.s->X + (size_t)(role * 2 + rank) * kXBytes + lane * 16;
#pragma unroll 1
                            for (int i = 0; i < kXBytes; i += 512) stg128(box + i, 0, 0, 0, 0);
                        }
                        bar_sync(3 + ev, 288);
                        if (lane == 0) {
                            unsigned* cnt = &p.s->cnt[(ev == 0 ? c : 16 * ev - 8 + rb) * 32];
                            asm volatile("fence.acq_rel.gpu;\nfence.proxy.async.global;" ::: "memory");
                            asm volatile("red.relaxed.gpu.global.add.u32 [%0], 1;" ::"l"(cnt) : "memory");
                        }
                        __syncwarp();
                    }
                } else if (lane == 0) {
                    const unsigned tag = lds32(tag_s);
#pragma unroll 1
                    for (int ev = 0; ev < 3; ++ev) {
                        wait_counter(&p.s->cnt[(ev == 0 ? c : 16 * ev - 8 + rb) * 32], tag * (ev == 0 ? 16u : 8u));
                        mbar_arrive_local(bar_dep + 8 * ev);
                        if (ev == 0 && atomicInc(&p.s->done, 127u) == 127u) {
                            st_relaxed32(&p.s->epoch, tag);
#pragma unroll 1
                            for (int i = 0; i < 64; i += 4) stg128(&p.s->claim[i], 0, 0, 0, 0);
                        }
                    }
                }
            }
        } else if (elect_one()) {
            int it = 1, again = 15;
            if (MC0) tma5_mc(sbase + kABytes + rank * 16384, &mXs, bar_full, 0, 0, 0, rank * 16, role >> 3);
#define ACQUIRE(BYTES)                                                   \
    const uint32_t st = sbase + (it & 3) * kStageBytes, fb = bar_full + 8 * (it & 3); \
    mbar_wait(bar_empty + 8 * (it & 3), ((it >> 2) & 1) ^ 1);     \
    mbar_expect_tx(fb, BYTES);
#pragma unroll 1
            for (; it < 16; ++it) {
                ACQUIRE(49152);
                tma4(st, &mB, fb, it * 64, 0, 0, ((role & 7) * 2 + (int)rank) * 8);
                tma5_mc(st + kABytes + rank * 16384, &mXs, fb, it * 64, 0, 0, rank * 16, role >> 3);
                if (it == again) {
                    mbar_wait(bar_role, 0);
                    const uint2 fin = lds64(role_s);
                    role = fin.x & 63;
                    if (fin.x != fin.y) { it = -1; again = 16; }
                }
            }
            ROLE_VARS();
#pragma unroll 1
            for (; it < 48; ++it) {
                const bool t1 = it < 32;
                const int k0 = (it & 15) * 64;
                ACQUIRE(t1 ? 40960 : 49152);
                tma5(st, &mXf, fb, k0, 0, 0, rank * 4, c);
                tma3_mc(st + kABytes + rank * (t1 ? 12288 : 16384), t1 ? &mW1b : &mW1a, fb, 0, k0 + rank * 32, t1 ? 32 + 3 * j8 : 4 * j8);
                if ((it & ~2) == XLDKB) {
                    const int h = (it >> 1) & 1;
                    if (h == 0) mbar_expect_tx(bar_x, 32768);
                    tma5(sbase + kXOff + h * 16384, &mXf, bar_x, colK + h * 64, 0, 0, rank * 4, c);
                }
            }
            STAMPA(true, 8);
            mbar_wait(bar_dep, 0);
            asm volatile("fence.proxy.async.global;" ::: "memory");
            STAMPA(true, 9);
#pragma unroll 1
            for (; it < 64; ++it) {
                const int k0 = (it & 15) * 64;
                ACQUIRE(49152);
                tma3(st, &mHs, fb, 0, kh * 1024 + k0, rb * 2);
                tma2_mc(st + kABytes + rank * 16384, kh ? &mCim : &mCre, fb, k0, rank ? colS : colK);
            }
            int f0 = 2048 + 768 * kh;
#pragma unroll 1
            for (; it < kTotal; ++it, f0 += 64) {
                if (it == 64 || it == 76) {
                    mbar_wait(bar_dep + (it == 64 ? 8 : 16), 0);
                    asm volatile("fence.proxy.async.global;" ::: "memory");
                    if (it == 76) f0 = 1024 * kh;
                }
                if (f0 == 256 * j8) f0 += 256;
                if (it == 88) f0 = 256 * (j8 ^ 4);
                ACQUIRE(49152);
                tma2(st, &mHf, fb, f0, rb * 128);
                tma5_mc(st + kABytes + rank * 16384, &mW2, fb, 0, 0, (f0 >> 3) + 4 * rank, 0, colK >> 6);
                if (it < 88) tma5_mc(st + kABytes + rank * 16384 + 8192, &mW2, fb, 0, 0, (f0 >> 3) + 4 * rank, 0, colS >> 6);
                else tma3_mc(st + kABytes + rank * 16384 + 8192, &mW2n, fb, 0, (f0 ^ 1024) + 32 * rank, colK >> 6);
                if ((it >> 3) == PFKB / 8) tma3_pf(&mW2n, 0, 256 * (j8 & 3) + (it & 4) * 256 + (it & 3) * 64 + 32 * rank, colK >> 6);
            }
        }
    } else {
        INIT_ALL();
        if (warp >= 8 - PF0LINES) {
            const int row = blockIdx.x * 32 + lane;
            const __nv_bfloat16* src = (row < 2048) ? p.x : (row < 3072) ? p.b_re - 2048 * kD : p.b_im - 3072 * kD;
            asm volatile("prefetch.global.L2 [%0];" ::"l"(src + row * kD + (7 - warp) * 64) : "memory");
        }
        __syncwarp();
        cluster_arrive();
        asm volatile("setmaxnreg.inc.sync.aligned.u32 240;");
        const int wg = warp >> 2, w = warp & 3, r = lane >> 2, q = lane & 3, tw = tid & 127;
        uint32_t a_lo = (kSmemOrg + wg * 8192) >> 4;
        constexpr uint32_t b_lo = (kSmemOrg + kABytes) >> 4;
        const uint32_t rel_addr = mapa(bar_empty, (uint32_t)(lane & 1));
        const uint32_t gate_s = sbase + kGateOff;
        float acc[128];
        uint32_t pk[64];
        unsigned tag;
        UNDEF_R(tag);

#pragma unroll
        for (int i = 0; i < 128; ++i) UNDEF_F(acc[i]);
        float gs = 0.f;
        {
            const uint32_t gx_s = sbase + kABytes + (16 * rank + 2 * warp + (lane >> 4)) * 128 +
                                  ((((lane & 15) >> 1) ^ (2 * w + (lane >> 4))) << 4) + (lane & 1) * 8;
            const uint32_t gw_s = sbase + kXOff + (lane & 15) * 8;
            uint32_t again = 15;
            cluster_wait();
#pragma unroll 1
            for (uint32_t it = 0; it < 16; ++it) {
                const uint32_t so = (it & 3) * (kStageBytes >> 4);
                KB_OPEN(it, it == 15);
                wgmma_fence();
                mma_kblock<0>(acc, a_lo + so, b_lo + so, it != 0);
                wgmma_commit();
                KB_CLOSE(it, it == 15, it + again != 15);
                STAMPA(tid == 0 && it == 0, 1);
                mbar_wait(bar_x, 0);
                const uint2 xa = lds64(gx_s + (role & 7) * 4096 + (it & 3) * kStageBytes), wa = lds64(gw_s + it * 128);
                const uint32_t pa = bf2_mul(xa.x, wa.x), pb = bf2_mul(xa.y, wa.y);
                gs += (bf_lo(pa) + bf_hi(pa)) + (bf_lo(pb) + bf_hi(pb));
                if (it == again) {
                    mbar_wait(bar_c, 0);
                    const uint2 fin = lds64(role_s);
                    role = fin.x & 63;
                    if (__shfl_sync(0xffffffffu, fin.x != fin.y, 0)) { it = -1; again = 16; gs = 0.f; }
                }
            }
        }
        role = __shfl_sync(0xffffffffu, role, 0);
        ROLE_VARS();
        {
            tag = lds32(tag_s);
#pragma unroll
            for (int o = 8; o > 0; o >>= 1) gs += __shfl_xor_sync(0xffffffffu, gs, o);
            const float g = bf16_round(__frcp_rn(1.0f + expf(-bf16_round(gs))));
            if ((lane & 15) == 0) st_relaxed64(&p.s->gate[c * 256 + (lane >> 4) + 64 * w + 4 * cb + 2 * wg], __float_as_uint(g), tag);
        }
        const uint32_t tab_s = sbase + kTabOff + tid * 16;
        const float4 k0 = lds128f(tab_s);
        TILE_END();
        STAMPA(tid == 0, 2);
#pragma unroll
        for (int s = 0; s < 64; ++s) pk[s] = pack_bf16_v(acc[4 * (s >> 1) + (s & 1)], acc[4 * (s >> 1) + 2 + (s & 1)]);
#pragma unroll
        for (int i = 0; i < 96; ++i) UNDEF_F(acc[i]);

        const float lr = k0.x, li = k0.y, m00 = k0.z, m01 = k0.w;
        float m10, m11, hr = 0.f, hi = 0.f;
        uint32_t gg[4], orr[4], oii[4];
        const int ch = cb * 64 + warp * 8 + r;
        __nv_bfloat16* hs = p.s->Hs + (size_t)ch * 2048 + c * 256 + q * 8;
#define PASS2(KB)                                                                                      \
    _Pragma("unroll") for (int s = 0; s < 64; s += 2) {                                                \
        if (pass2_kb(s) != (KB)) continue;                                                             \
        if ((s & 7) == 0) {                                                                            \
            const uint4 ga = lds128(gate_s + (q * 72 + s) * 2);                                        \
            gg[0] = ga.x; gg[1] = ga.y; gg[2] = ga.z; gg[3] = ga.w;                                    \
        }                                                                                              \
        float o0[2], o1[2];                                                                            \
        _Pragma("unroll") for (int k = 0; k < 2; ++k) {                                                \
            PIN_R(pk[s + k]);                                                                          \
            float nr = bf_lo(pk[s + k]), ni = bf_hi(pk[s + k]);                                        \
            CFMA(nr, ni, lr, li, hr, hi);                                                              \
            hr = nr; hi = ni;                                                                          \
            o0[k] = fmaf(m00, hr, m01 * hi);                                                           \
            o1[k] = fmaf(m10, hr, m11 * hi);                                                           \
        }                                                                                              \
        orr[(s >> 1) & 3] = bf2_mul(pack_bf16(o0[0], o0[1]), gg[(s >> 1) & 3]);                        \
        oii[(s >> 1) & 3] = bf2_mul(pack_bf16(o1[0], o1[1]), gg[(s >> 1) & 3]);                        \
        if ((s & 7) == 6) {                                                                            \
            stg128(hs + 32 * (s >> 3), orr[0], orr[1], orr[2], orr[3]);                                \
            stg128(hs + 1024 * 2048 + 32 * (s >> 3), oii[0], oii[1], oii[2], oii[3]);                  \
        }                                                                                              \
    }                                                                                                  \
    PIN_F(hr); PIN_F(hi);
        {
            uint4 av0, av1, gv;
            float lqr, lqi;
#pragma unroll
            for (int kb = 0; kb < 16; ++kb) {
                PIN_R(a_lo);
                KBLOCK(1, 16 + kb, kb == 0, kb == 15);
                if (kb < 4) {
#pragma unroll
                    for (int s = kb * 16; s < kb * 16 + 16; ++s) {
                        float nr = bf_lo(pk[s]), ni = bf_hi(pk[s]);
                        CFMA(nr, ni, lr, li, hr, hi);
                        hr = nr; hi = ni;
                    }
                    PIN_F(hr); PIN_F(hi);
                }
                if (kb == 2) gv = ld_relaxed2x64(&p.s->gate[c * 256 + 2 * tw]);
                if (kb == 3) {
                    const float4 k1 = lds128f(tab_s + 4096), k2 = lds128f(tab_s + 8192);
                    m10 = k1.x; m11 = k1.y; lqr = k2.z; lqi = k2.w;
                    float tr = __shfl_up_sync(0xffffffffu, hr, 1, 4), ti = __shfl_up_sync(0xffffffffu, hi, 1, 4);
                    if (q >= 1) CFMA(hr, hi, k1.z, k1.w, tr, ti);
                    tr = __shfl_up_sync(0xffffffffu, hr, 2, 4); ti = __shfl_up_sync(0xffffffffu, hi, 2, 4);
                    if (q >= 2) CFMA(hr, hi, k2.x, k2.y, tr, ti);
                    if (q == 3) st_relaxed2x64(&p.s->agg[c * 1024 + ch], __float_as_uint(hr), tag, __float_as_uint(hi), tag);
                    tr = __shfl_up_sync(0xffffffffu, hr, 1, 4); ti = __shfl_up_sync(0xffffffffu, hi, 1, 4);
                    hr = (q >= 1) ? tr : 0.f; hi = (q >= 1) ? ti : 0.f;
                }
                if (kb == 4) {
                    unsigned spins = 0;
                    while (__any_sync(0xffffffffu, gv.y != tag || gv.w != tag)) {
                        if (++spins > kSpinLimit) break;
                        gv = ld_relaxed2x64(&p.s->gate[c * 256 + 2 * tw]);
                    }
                    sts32(gate_s + ((tw >> 5) * 72 + 2 * lane) * 2, __byte_perm(gv.x, gv.z, 0x7632));
                }
                if (kb == 5) {
                    av0 = make_uint4(0, tag, 0, tag); av1 = av0;
                    if (q < c) av0 = ld_relaxed2x64(&p.s->agg[q * 1024 + ch]);
                    if (q + 4 < c) av1 = ld_relaxed2x64(&p.s->agg[(q + 4) * 1024 + ch]);
                    bar_sync(1 + wg, 128);
                }
                if (kb == 6) {
                    const float4 k3 = lds128f(tab_s + 12288);
                    unsigned spins = 0;
                    while (__any_sync(0xffffffffu, av0.y != tag || av0.w != tag || av1.y != tag || av1.w != tag)) {
                        if (++spins > kSpinLimit) break;
                        if (q < c) av0 = ld_relaxed2x64(&p.s->agg[q * 1024 + ch]);
                        if (q + 4 < c) av1 = ld_relaxed2x64(&p.s->agg[(q + 4) * 1024 + ch]);
                    }
                    float vr, vi;
                    CMUL(vr, vi, k3.x, k3.y, __uint_as_float(av0.x), __uint_as_float(av0.z));
                    CFMA(vr, vi, k3.z, k3.w, __uint_as_float(av1.x), __uint_as_float(av1.z));
                    vr += __shfl_xor_sync(0xffffffffu, vr, 1); vi += __shfl_xor_sync(0xffffffffu, vi, 1);
                    vr += __shfl_xor_sync(0xffffffffu, vr, 2); vi += __shfl_xor_sync(0xffffffffu, vi, 2);
                    CFMA(hr, hi, lqr, lqi, vr, vi);
                }
                if (kb >= 6) { PASS2(kb); }
            }
            TILE_END();
        }
        STAMPA(tid == 0, 3);
#pragma unroll
        for (int i = 0; i < 48; ++i) pk[i] = pack_bf16_v(acc[2 * i], acc[2 * i + 1]);
#pragma unroll
        for (int i = 0; i < 128; ++i) UNDEF_F(acc[i]);

        PIN_R(a_lo);
        KBLOCK(2, 32, true, false);
        PASS2(16);
        PIN_R(a_lo);
        KBLOCK(2, 33, false, false);
        PASS2(17);
        bar_arrive(3, 288);
        const uint32_t gate_row = gate_s + ((2 * (w & 1)) * 72 + 8 * (4 * rank + 2 * wg + (w >> 1)) + r) * 2;
        uint32_t om0, om1;
        {
            const float a = 1.0f - bf_lo(lds16(gate_row)), b = 1.0f - bf_lo(lds16(gate_row + 72 * 2));
            om0 = pack_bf16(a, a); om1 = pack_bf16(b, b);
        }
        __nv_bfloat16* hf = p.s->Hf + (size_t)(rb * 128 + wg * 64 + w * 16 + r) * kF + q * 8 + 2048 + 192 * j8;
        uint32_t bias_s = sbase + kBiasOff + q * 16;
#define FFN_SLICE(J)                                                                                   \
    {                                                                                                  \
        const uint4 bv = lds128(bias_s + (J) * 64);                                                    \
        const uint32_t bb[4] = {bv.x, bv.y, bv.z, bv.w};                                               \
        _Pragma("unroll") for (int jj = 0; jj < 4; ++jj) {                                             \
            const uint32_t r0 = bf2_add_relu(pk[8 * (J) + 2 * jj], bb[jj]), r1 = bf2_add_relu(pk[8 * (J) + 2 * jj + 1], bb[jj]); \
            pk[8 * (J) + 2 * jj] = bf2_mul(bf2_mul(r0, r0), om0);                                      \
            pk[8 * (J) + 2 * jj + 1] = bf2_mul(bf2_mul(r1, r1), om1);                                  \
        }                                                                                              \
        stg128(hf + 32 * (J), pk[8 * (J)], pk[8 * (J) + 2], pk[8 * (J) + 4], pk[8 * (J) + 6]);         \
        stg128(hf + 8 * kF + 32 * (J), pk[8 * (J) + 1], pk[8 * (J) + 3], pk[8 * (J) + 5], pk[8 * (J) + 7]); \
    }
        const uint32_t x_s = sbase + kXOff + (wg * 64 + w * 16 + (lane & 15)) * 128 + (((lane >> 4) ^ (lane & 7)) << 4);
        {
            uint32_t j = 0, nsl = 6;
#pragma unroll 1
            for (uint32_t it = 34; it < 88; ++it, ++j) {
                const uint32_t so = (it & 3) * (kStageBytes >> 4);
                if (wg == 1 && (it == 86 || (ORDER && it == 47))) bar_sync(7, 256);
                KB_OPEN(it, false);
                if ((it & ~15u) == 48) {
                    wgmma_fence();
                    mma_kblock<3>(acc, a_lo + so, b_lo + so, it != 48);
                    wgmma_commit();
                } else {
                    wgmma_fence();
                    mma_kblock<2>(acc, a_lo + so, b_lo + so, 1);
                    wgmma_commit();
                }
                if (wg == 0 && (it == 87 || (ORDER && it == 47))) bar_arrive(7, 256);
                KB_CLOSE(it, false, it != 48);
                if (j < nsl) {
                    if (j & 4) {
                        if (j & 2) { if (j & 1) FFN_SLICE(7) else FFN_SLICE(6) } else { if (j & 1) FFN_SLICE(5) else FFN_SLICE(4) }
                    } else {
                        if (j & 2) { if (j & 1) FFN_SLICE(3) else FFN_SLICE(2) } else { if (j & 1) FFN_SLICE(1) else FFN_SLICE(0) }
                    }
                    if (j + 1 == nsl) bar_arrive(1 + (nsl >> 1), 288);
                } else if (it == 47) {
                    hf += 64 * j8 - 2048;
                    bias_s += 6 * 64;
                    j = -1; nsl = 8;
                    TILE_END();
                    STAMPA(tid == 0, 4);
#pragma unroll
                    for (int i = 0; i < 64; ++i) pk[i] = pack_bf16_v(acc[2 * i], acc[2 * i + 1]);
                } else if ((it >> 2) == ETKB / 4) {
                    mbar_wait(bar_x, 1);
                    const uint32_t xa_s = (x_s ^ ((it & 1) << 6)) + (it & 2) * 8192;
                    const float g0 = bf_lo(lds16(gate_row)), g1 = bf_lo(lds16(gate_row + 72 * 2));
                    const float o0f = bf_lo(om0), o1f = bf_lo(om1);
                    const uint4 dq = lds128(bias_s + (8 + (it & 3)) * 64), bq = lds128(bias_s + (12 + (it & 3)) * 64);
                    const uint4 xa = ldsm4(xa_s), xb = ldsm4(xa_s ^ 32);
                    const uint32_t dv[4] = {dq.x, dq.y, dq.z, dq.w}, bv2[4] = {bq.x, bq.y, bq.z, bq.w};
                    uint32_t xv[8] = {xa.x, xa.y, xa.z, xa.w, xb.x, xb.y, xb.z, xb.w};
#pragma unroll
                    for (int jj = 0; jj < 4; ++jj) {
                        const uint32_t x0 = bf2_mul(xv[2 * jj], dv[jj]), x1 = bf2_mul(xv[2 * jj + 1], dv[jj]);
                        const float bl = bf_lo(bv2[jj]), bh = bf_hi(bv2[jj]);
                        xv[2 * jj] = pack_bf16(fmaf(g0, bf_lo(x0), o0f * bl), fmaf(g0, bf_hi(x0), o0f * bh));
                        xv[2 * jj + 1] = pack_bf16(fmaf(g1, bf_lo(x1), o1f * bl), fmaf(g1, bf_hi(x1), o1f * bh));
                    }
                    sts128(xa_s, xv[0], xv[1], xv[2], xv[3]);
                    sts128(xa_s ^ 32, xv[4], xv[5], xv[6], xv[7]);
                }
            }
        }
#define TAIL_MMA(T)                                                                                    \
    {                                                                                                  \
        PIN_R(a_lo);                                                                                   \
        wgmma_fence();                                                                                 \
        mma_kblock<4>(acc, a_lo + (T) * (kStageBytes >> 4), b_lo + (T) * (kStageBytes >> 4), 1);       \
        _Pragma("unroll") for (int kk = 0; kk < 4; ++kk)                                               \
            wgmma_n128_rs(acc, pk[16 * (T) + 4 * kk], pk[16 * (T) + 4 * kk + 1], pk[16 * (T) + 4 * kk + 2], pk[16 * (T) + 4 * kk + 3], \
                          kDescHi | (uint64_t)(b_lo + (((T) * kStageBytes + 8192 + (kk >> 1) * 16384 + (kk & 1) * 2048) >> 4) + (256u << 16))); \
        wgmma_commit();                                                                                \
    }
        TILE_END();
        sched_fence(a_lo);
        {
            const uint8_t* xi = p.s->X + (size_t)(role * 2 + rank) * kXBytes + tid * 16;
            uint8_t* xo = const_cast<uint8_t*>(xi) + (kh ? -8 * kXBytes : 8 * kXBytes);
            uint4 rx[8], ev[8];
            uint32_t rs;
#define RXLOAD()                                                                                       \
    {                                                                                                  \
        rs = ld_relaxed32((const unsigned*)(xi + 32768 - tid * 12));                                   \
        _Pragma("unroll") for (int u = 0; u < 8; ++u) rx[u] = ld_relaxed2x64(xi + u * 4096);           \
    }
            {
                STAMP(tid == 0, 15); STAMPB(tid == 128, 1);
                float m[4] = {0.f, 0.f, 0.f, 0.f};
#pragma unroll
                for (int i = 64; i < 128; ++i) m[i & 3] = fmaxf(m[i & 3], fabsf(acc[i]));
                const uint32_t eb = max(__float_as_uint(fmaxf(fmaxf(m[0], m[1]), fmaxf(m[2], m[3]))) >> 23, 15u);
                const float xsc = __uint_as_float((268u - eb) << 23);
                st_relaxed32(xo + 32768 - tid * 12, (eb - 14u) << 23);
#pragma unroll
                for (int u = 0; u < 8; ++u) {
                    const int v = 64 + 8 * u;
                    st_relaxed2x64(xo + u * 4096, pack_f16(acc[v] * xsc, acc[v + 1] * xsc) | 1, pack_f16(acc[v + 2] * xsc, acc[v + 3] * xsc),
                                   pack_f16(acc[v + 4] * xsc, acc[v + 5] * xsc) | 1, pack_f16(acc[v + 6] * xsc, acc[v + 7] * xsc));
                }
                STAMP(tid == 0, 12); STAMPB(tid == 128, 2);
            }
            mbar_wait(bar_full, 0);
            TAIL_MMA(0);
            mbar_wait(bar_full + 8, 0);
            TAIL_MMA(1);
            if (wg == 1) bar_arrive(8, 256);
#pragma unroll
            for (int u = 0; u < 8; ++u) ev[u] = lds128((x_s ^ ((u & 3) << 5)) + (u >> 2) * 16384);
            if (wg == 1) mbar_wait(bar_full + 24, 0);
            bar_sync(8 + wg, 256);
            STAMPB(tid == 0, 9);
            RXLOAD();
            mbar_wait(bar_full + 16, 0);
            STAMPB(tid == 0, 10);
            STAMPB(tid == 128, 3);
            TAIL_MMA(2);
            if (wg == 0) mbar_wait(bar_full + 24, 0);
            STAMPB(tid == 0, 11);
            TAIL_MMA(3);
            if (wg == 0) bar_arrive(9, 256);
            sched_fence(a_lo);
            unsigned spins = 0;
#pragma unroll 1
            while (true) {
                uint32_t ok = rs != 0;
#pragma unroll
                for (int u = 0; u < 8; ++u) ok &= rx[u].x & rx[u].z;
                if (__all_sync(0xffffffffu, ok) || ++spins > kSpinLimit) break;
                RXLOAD();
                RESPIN();
            }
            STAMP(tid == 0, 13);
            const float xsc = __uint_as_float(rs);
#pragma unroll
            for (int u = 0; u < 8; ++u) {
                const uint32_t rr[4] = {rx[u].x, rx[u].y, rx[u].z, rx[u].w}, ee[4] = {ev[u].x, ev[u].y, ev[u].z, ev[u].w};
#pragma unroll
                for (int k = 0; k < 4; ++k) {
                    const int v = 64 + 8 * u + 2 * k;
                    const float2 f = __half22float2(*reinterpret_cast<const __half2*>(&rr[k]));
                    acc[v] = fmaf(f.x, xsc, bf_lo(ee[k])); acc[v + 1] = fmaf(f.y, xsc, bf_hi(ee[k]));
                    PIN_F(acc[v]); PIN_F(acc[v + 1]);
                }
            }
            sched_fence(a_lo);
            STAMP(tid == 0, 14);
        }
        wgmma_wait<0>();
        STAMP(tid == 0, 6); STAMPB(tid == 128, 4);
        {
            const bool odd = q & 1;
            const int tb = c * 256 + 128 * (w & 1) + 8 * (4 * rank + 2 * wg + (w >> 1));
            float* o0 = p.out + (size_t)(tb + r) * kD + colK + (odd ? 2 * q + 6 : 2 * q);
#pragma unroll
            for (int i = 0; i < 16; i += 2) {
#pragma unroll
                for (int h = 0; h < 2; ++h) {
                    const int va = 4 * i + 2 * h, vb = va + 4;
                    PIN_F(acc[va]); PIN_F(acc[va + 1]); PIN_F(acc[vb]); PIN_F(acc[vb + 1]);
                    const float a0 = acc[va] + acc[64 + va], a1 = acc[va + 1] + acc[65 + va];
                    const float b0 = acc[vb] + acc[64 + vb], b1 = acc[vb + 1] + acc[65 + vb];
                    const float t0 = __shfl_xor_sync(0xffffffffu, odd ? a0 : b0, 1), t1 = __shfl_xor_sync(0xffffffffu, odd ? a1 : b1, 1);
                    stg128f(o0 + h * 64 * kD + 8 * i, odd ? t0 : a0, odd ? t1 : a1, odd ? b0 : t0, odd ? b1 : t1);
                }
            }
        }
        STAMP(tid == 0, 7);
        STAMP(tid == 128, 5);
    }
}

typedef CUresult (*EncodeFn)(CUtensorMap*, CUtensorMapDataType, cuuint32_t, void*, const cuuint64_t*, const cuuint64_t*,
                             const cuuint32_t*, const cuuint32_t*, CUtensorMapInterleave, CUtensorMapSwizzle,
                             CUtensorMapL2promotion, CUtensorMapFloatOOBfill);

bool encode(EncodeFn fn, CUtensorMap* m, const void* base, int rank, const cuuint64_t* dims, const cuuint64_t* strides,
            const cuuint32_t* box) {
    cuuint32_t es[5] = {1, 1, 1, 1, 1};
    return fn(m, CU_TENSOR_MAP_DATA_TYPE_BFLOAT16, rank, const_cast<void*>(base), dims, strides, box, es,
              CU_TENSOR_MAP_INTERLEAVE_NONE, CU_TENSOR_MAP_SWIZZLE_128B, CU_TENSOR_MAP_L2_PROMOTION_L2_256B,
              CU_TENSOR_MAP_FLOAT_OOB_FILL_NONE) == CUDA_SUCCESS;
}

}

extern "C" void kernel_launch(void* const* d_in, const int* in_sizes, int n_in, void* d_out, int out_size) {
    (void)in_sizes; (void)n_in; (void)out_size;
    typedef const __nv_bfloat16* bp;
    bp x = (bp)d_in[0], lam_re = (bp)d_in[1], lam_im = (bp)d_in[2], B_re = (bp)d_in[3], B_im = (bp)d_in[4];
    bp C_re = (bp)d_in[5], C_im = (bp)d_in[6], log_dt = (bp)d_in[7], dskip = (bp)d_in[8];
    bp w1 = (bp)d_in[10], b1 = (bp)d_in[11], w2 = (bp)d_in[12], b2 = (bp)d_in[13], gate_w = (bp)d_in[14];

    static EncodeFn fn = nullptr;
    static Scratch* ps = nullptr;
    if (!fn) {
        void* f = nullptr;
        cudaDriverEntryPointQueryResult qr;
        cudaGetDriverEntryPoint("cuTensorMapEncodeTiled", &f, cudaEnableDefault, &qr);
        fn = (EncodeFn)f;
        cudaGetSymbolAddress((void**)&ps, g_s);
        cudaFuncSetAttribute(fused_kernel, cudaFuncAttributeMaxDynamicSharedMemorySize, kSmemBytes);
    }
    cudaStream_t stream = cudaStreamPerThread;

    Params p;
    p.x = x; p.lam_re = lam_re; p.lam_im = lam_im; p.log_dt = log_dt; p.dskip = dskip; p.b1 = b1; p.b2 = b2;
    p.gate_w = gate_w; p.b_re = B_re; p.b_im = B_im; p.out = (float*)d_out; p.s = ps;
    char* const pHs = (char*)ps + offsetof(Scratch, Hs);
    char* const pHf = (char*)ps + offsetof(Scratch, Hf);
    char* const pBc = (char*)ps + offsetof(Scratch, Bcopy);

    const char* lo = (const char*)B_re; const char* hi = (const char*)B_im;
    p.swap = 0;
    if (hi < lo) { const char* t = lo; lo = hi; hi = t; p.swap = 1; }
    unsigned long long diff = (unsigned long long)(hi - lo);
    if (diff >= (1ull << 40) || (diff & 15) || diff == 0) {
        cudaMemcpyAsync(pBc, B_re, 2u << 20, cudaMemcpyDeviceToDevice, stream);
        cudaMemcpyAsync((char*)pBc + (2u << 20), B_im, 2u << 20, cudaMemcpyDeviceToDevice, stream);
        lo = (const char*)pBc; diff = 2u << 20; p.swap = 0;
    }

    CUtensorMap mB, mXs, mXf, mW1a, mW1b, mHs, mHf, mCre, mCim, mW2, mW2n;
    bool ok = true;
    { cuuint64_t d[4] = {1024, 8, 2, 128}, s[3] = {2048, diff, 16384}; cuuint32_t b[4] = {64, 8, 2, 8};
      ok &= encode(fn, &mB, lo, 4, d, s, b); }
    { cuuint64_t d[5] = {1024, 2, 4, 32, 8}, s[4] = {2048, 64 * 2048, 2 * 2048, 256 * 2048}; cuuint32_t b[5] = {64, 2, 4, 16, 1};
      ok &= encode(fn, &mXs, x, 5, d, s, b); }
    { cuuint64_t d[5] = {1024, 8, 4, 8, 8}, s[4] = {2048, 64 * 2048, 8 * 2048, 256 * 2048}; cuuint32_t b[5] = {64, 8, 4, 4, 1};
      ok &= encode(fn, &mXf, x, 5, d, s, b); }
    { cuuint64_t d[3] = {64, 1024, 56}, s[2] = {7168, 128}; cuuint32_t ba[3] = {64, 32, 4}, bb[3] = {64, 32, 3};
      ok &= encode(fn, &mW1a, w1, 3, d, s, ba); ok &= encode(fn, &mW1b, w1, 3, d, s, bb); }
    { cuuint64_t d[3] = {64, 2048, 32}, s[2] = {4096, 128}; cuuint32_t b[3] = {64, 64, 2};
      ok &= encode(fn, &mHs, pHs, 3, d, s, b); }
    { cuuint64_t d[2] = {3584, 2048}, s[1] = {7168}; cuuint32_t b[2] = {64, 128};
      ok &= encode(fn, &mHf, pHf, 2, d, s, b); }
    { cuuint64_t d[2] = {1024, 1024}, s[1] = {2048}; cuuint32_t b[2] = {64, 128};
      ok &= encode(fn, &mCre, C_re, 2, d, s, b); ok &= encode(fn, &mCim, C_im, 2, d, s, b); }
    { cuuint64_t d[5] = {64, 2, 448, 4, 16}, s[4] = {2048, 8 * 2048, 2 * 2048, 128}; cuuint32_t b[5] = {64, 2, 4, 4, 2};
      ok &= encode(fn, &mW2, w2, 5, d, s, b); }
    { cuuint64_t d[3] = {64, 3584, 16}, s[2] = {2048, 128}; cuuint32_t b[3] = {64, 32, 2};
      ok &= encode(fn, &mW2n, w2, 3, d, s, b); }
    if (!ok) return;

    fused_kernel<<<128, 384, kSmemBytes, stream>>>(mB, mXs, mXf, mW1b, mW1a, mHs, mHf, mCre, mCim, mW2, mW2n, p);
}
```

```cpp
#include <cuda_runtime.h>
#include <cuda_bf16.h>
#include <cuda_fp16.h>
#include <cuda.h>
#include <stdint.h>
#include <stddef.h>

#define XLDKB 40
#define PF0LINES 1
#define ETKB 60
#define PFKB 80
#define RXPOS 0
#define MC0 0
#define PFTOP 0
#define INITW 0
#define PRODCOND warp >= 8
#define ORDER 0

namespace {

constexpr int kD = 1024, kF = 3584;
constexpr int kStages = 4;
constexpr int kStageBytes = 49152;
constexpr int kABytes = 16384;
constexpr int kXOff = kStages * kStageBytes;
constexpr int kTabOff = kXOff + 2048;
constexpr int kGateOff = kXOff + 32768;
constexpr int kBiasOff = kGateOff + 4 * 72 * 2;
constexpr int kBarOff = kBiasOff + 88 * 16;
constexpr int kSmemBytes = 232448;
static_assert(kBarOff + 160 <= kSmemBytes, "smem");
constexpr int kXBytes = 33792;
constexpr uint32_t kSmemOrg = 1024;
constexpr unsigned kSpinLimit = 1u << 18;
constexpr int kTotal = 92;

__host__ __device__ constexpr int pass2_kb(int s) {
    return s < 2 ? 6 : s < 8 ? 7 : s < 12 ? 8 : s < 18 ? 9 : s < 22 ? 10 : s < 28 ? 11 : s < 32 ? 12 : s < 38 ? 13 : s < 42 ? 14 : s < 48 ? 15 : s < 56 ? 16 : 17;
}

struct Scratch {
    unsigned claim[64];
    unsigned epoch, pad0[31];
    unsigned done, pad1[31];
    unsigned cnt[40 * 32];
    uint2 gate[2048];
    uint4 agg[8 * 1024];
    __align__(1024) uint8_t X[128 * kXBytes];
    __align__(1024) __nv_bfloat16 Hs[2048 * 2048];
    __align__(1024) __nv_bfloat16 Hf[2048 * 3584];
    __align__(1024) __nv_bfloat16 Bcopy[2 * 1024 * 1024];
};
__device__ Scratch g_s;

#define TRAP() break
#define PIN_F(x) asm volatile("" : "+f"(x))
#define PIN_R(x) asm volatile("" : "+r"(x))
#define UNDEF_F(x) asm volatile("" : "=f"(x))
#define UNDEF_R(x) asm volatile("" : "=r"(x))
#define RESPIN()
__device__ __forceinline__ uint32_t smem_u32(const void* p) { return (uint32_t)__cvta_generic_to_shared(p); }
__device__ __forceinline__ void mbar_init(uint32_t bar, uint32_t count) {
    asm volatile("mbarrier.init.shared::cta.b64 [%0], %1;" ::"r"(bar), "r"(count) : "memory");
}
__device__ __forceinline__ void mbar_expect_tx(uint32_t bar, uint32_t bytes) {
    asm volatile("mbarrier.arrive.expect_tx.shared::cta.b64 _, [%0], %1;" ::"r"(bar), "r"(bytes) : "memory");
}
__device__ __forceinline__ void mbar_wait(uint32_t bar, uint32_t parity) {
    asm volatile(
        "{\n.reg .pred p;\n.reg .u32 n;\n"
        "mbarrier.try_wait.parity.shared::cta.b64 p, [%0], %1;\n"
        "@p bra DONE;\n"
        "mov.u32 n, 0;\n"
        "LOOP:\n"
        "mbarrier.try_wait.parity.shared::cta.b64 p, [%0], %1;\n"
        "@p bra DONE;\n"
        "add.u32 n, n, 1;\n"
        "setp.lt.u32 p, n, %2;\n"
        "@p bra LOOP;\n"
        "DONE:\n}\n"
        ::"r"(bar), "r"(parity), "n"(kSpinLimit) : "memory");
}
__device__ __forceinline__ void sched_fence(uint32_t nonzero) {
    asm volatile("{\n.reg .pred p;\n.reg .u32 n;\nsetp.ne.u32 p, %0, 0;\n@p bra DONE;\nLOOP:\nmov.u32 n, %%clock;\n"
                 "setp.eq.u32 p, n, 0;\n@p bra LOOP;\nDONE:\n}\n" ::"r"(nonzero) : "memory");
}
__device__ __forceinline__ void mbar_arrive_local(uint32_t bar) {
    asm volatile("mbarrier.arrive.shared::cta.b64 _, [%0];" ::"r"(bar) : "memory");
}
__device__ __forceinline__ void mbar_arrive_cluster(uint32_t cluster_addr) {
    asm volatile("mbarrier.arrive.shared::cluster.b64 _, [%0];" ::"r"(cluster_addr) : "memory");
}
__device__ __forceinline__ uint32_t mapa(uint32_t addr, uint32_t rank) {
    uint32_t r;
    asm("mapa.shared::cluster.u32 %0, %1, %2;" : "=r"(r) : "r"(addr), "r"(rank));
    return r;
}
__device__ __forceinline__ void cluster_arrive() { asm volatile("barrier.cluster.arrive.relaxed.aligned;" ::: "memory"); }
__device__ __forceinline__ void cluster_wait() { asm volatile("barrier.cluster.wait.acquire.aligned;" ::: "memory"); }
__device__ __forceinline__ void bar_sync(int id, int n) { asm volatile("bar.sync %0, %1;" ::"r"(id), "r"(n) : "memory"); }
__device__ __forceinline__ void bar_arrive(int id, int n) { asm volatile("bar.arrive %0, %1;" ::"r"(id), "r"(n) : "memory"); }
__device__ __forceinline__ bool elect_one() {
    uint32_t p;
    asm volatile("{\n.reg .pred P;\nelect.sync _|P, 0xffffffff;\nselp.u32 %0, 1, 0, P;\n}\n" : "=r"(p));
    return p != 0;
}

__device__ __forceinline__ void tma2(uint32_t dst, const CUtensorMap* m, uint32_t bar, int c0, int c1) {
    asm volatile("cp.async.bulk.tensor.2d.shared::cluster.global.mbarrier::complete_tx::bytes [%0], [%1, {%3, %4}], [%2];"
                 ::"r"(dst), "l"(m), "r"(bar), "r"(c0), "r"(c1) : "memory");
}
__device__ __forceinline__ void tma3(uint32_t dst, const CUtensorMap* m, uint32_t bar, int c0, int c1, int c2) {
    asm volatile("cp.async.bulk.tensor.3d.shared::cluster.global.mbarrier::complete_tx::bytes [%0], [%1, {%3, %4, %5}], [%2];"
                 ::"r"(dst), "l"(m), "r"(bar), "r"(c0), "r"(c1), "r"(c2) : "memory");
}
__device__ __forceinline__ void tma4(uint32_t dst, const CUtensorMap* m, uint32_t bar, int c0, int c1, int c2, int c3) {
    asm volatile("cp.async.bulk.tensor.4d.shared::cluster.global.mbarrier::complete_tx::bytes [%0], [%1, {%3, %4, %5, %6}], [%2];"
                 ::"r"(dst), "l"(m), "r"(bar), "r"(c0), "r"(c1), "r"(c2), "r"(c3) : "memory");
}
__device__ __forceinline__ void tma5(uint32_t dst, const CUtensorMap* m, uint32_t bar, int c0, int c1, int c2, int c3, int c4) {
    asm volatile("cp.async.bulk.tensor.5d.shared::cluster.global.mbarrier::complete_tx::bytes [%0], [%1, {%3, %4, %5, %6, %7}], [%2];"
                 ::"r"(dst), "l"(m), "r"(bar), "r"(c0), "r"(c1), "r"(c2), "r"(c3), "r"(c4) : "memory");
}
__device__ __forceinline__ void tma2_mc(uint32_t dst, const CUtensorMap* m, uint32_t bar, int c0, int c1) {
    asm volatile("cp.async.bulk.tensor.2d.shared::cluster.global.mbarrier::complete_tx::bytes.multicast::cluster [%0], [%1, {%3, %4}], [%2], %5;"
                 ::"r"(dst), "l"(m), "r"(bar), "r"(c0), "r"(c1), "h"((uint16_t)3) : "memory");
}
__device__ __forceinline__ void tma3_mc(uint32_t dst, const CUtensorMap* m, uint32_t bar, int c0, int c1, int c2) {
    asm volatile("cp.async.bulk.tensor.3d.shared::cluster.global.mbarrier::complete_tx::bytes.multicast::cluster [%0], [%1, {%3, %4, %5}], [%2], %6;"
                 ::"r"(dst), "l"(m), "r"(bar), "r"(c0), "r"(c1), "r"(c2), "h"((uint16_t)3) : "memory");
}
__device__ __forceinline__ void tma5_mc(uint32_t dst, const CUtensorMap* m, uint32_t bar, int c0, int c1, int c2, int c3, int c4) {
    asm volatile("cp.async.bulk.tensor.5d.shared::cluster.global.mbarrier::complete_tx::bytes.multicast::cluster [%0], [%1, {%3, %4, %5, %6, %7}], [%2], %8;"
                 ::"r"(dst), "l"(m), "r"(bar), "r"(c0), "r"(c1), "r"(c2), "r"(c3), "r"(c4), "h"((uint16_t)3) : "memory");
}
__device__ __forceinline__ void tma2_pf(const CUtensorMap* m, int c0, int c1) {
    asm volatile("cp.async.bulk.prefetch.tensor.2d.L2.global [%0, {%1, %2}];" ::"l"(m), "r"(c0), "r"(c1) : "memory");
}
__device__ __forceinline__ void bulk_store(void* dst, uint32_t src, uint32_t bytes) {
    asm volatile("cp.async.bulk.global.shared::cta.bulk_group [%0], [%1], %2;" ::"l"(dst), "r"(src), "r"(bytes) : "memory");
}
__device__ __forceinline__ void bulk_load(uint32_t dst, const void* src, uint32_t bytes, uint32_t bar) {
    asm volatile("cp.async.bulk.shared::cluster.global.mbarrier::complete_tx::bytes [%0], [%1], %2, [%3];"
                 ::"r"(dst), "l"(src), "r"(bytes), "r"(bar) : "memory");
}
__device__ __forceinline__ unsigned atom_exch(unsigned* p, unsigned v) {
    unsigned r;
    asm volatile("atom.relaxed.gpu.global.exch.b32 %0, [%1], %2;" : "=r"(r) : "l"(p), "r"(v) : "memory");
    return r;
}
__device__ __forceinline__ void st_async32(uint32_t a, uint32_t v, uint32_t bar) {
    asm volatile("st.async.shared::cluster.mbarrier::complete_tx::bytes.u32 [%0], %1, [%2];" ::"r"(a), "r"(v), "r"(bar) : "memory");
}
__device__ __forceinline__ void sts128f(uint32_t a, float x, float y, float z, float w) {
    asm volatile("st.shared.v4.f32 [%0], {%1, %2, %3, %4};" ::"r"(a), "f"(x), "f"(y), "f"(z), "f"(w) : "memory");
}
__device__ __forceinline__ void prefetch_map(const CUtensorMap* m) {
    asm volatile("prefetch.tensormap [%0];" ::"l"(m) : "memory");
}

__device__ __forceinline__ void prefetch_l2(const void* p, uint32_t bytes) {
    asm volatile("cp.async.bulk.prefetch.L2.global [%0], %1;" ::"l"(p), "r"(bytes) : "memory");
}

__device__ __forceinline__ void wgmma_fence() { asm volatile("wgmma.fence.sync.aligned;" ::: "memory"); }
__device__ __forceinline__ void wgmma_commit() { asm volatile("wgmma.commit_group.sync.aligned;" ::: "memory"); }
template <int N>
__device__ __forceinline__ void wgmma_wait() { asm volatile("wgmma.wait_group.sync.aligned %0;" ::"n"(N) : "memory"); }

__device__ __forceinline__ uint32_t pack_bf16(float lo, float hi) {
    uint32_t r;
    asm("cvt.rn.bf16x2.f32 %0, %1, %2;" : "=r"(r) : "f"(hi), "f"(lo));
    return r;
}
__device__ __forceinline__ uint32_t pack_f16(float lo, float hi) {
    uint32_t r;
    asm("cvt.rn.f16x2.f32 %0, %1, %2;" : "=r"(r) : "f"(hi), "f"(lo));
    return r;
}
__device__ __forceinline__ uint32_t pack_bf16_v(float lo, float hi) {
    uint32_t r;
    asm volatile("cvt.rn.bf16x2.f32 %0, %1, %2;" : "=r"(r) : "f"(hi), "f"(lo));
    return r;
}
template <int LUT>
__device__ __forceinline__ uint32_t lop3(uint32_t a, uint32_t b, uint32_t c) {
    uint32_t r;
    asm("lop3.b32 %0, %1, %2, %3, %4;" : "=r"(r) : "r"(a), "r"(b), "r"(c), "n"(LUT));
    return r;
}
__device__ __forceinline__ float bf_lo(uint32_t v) { return __uint_as_float(v << 16); }
__device__ __forceinline__ float bf_hi(uint32_t v) { return __uint_as_float(v & 0xffff0000u); }
__device__ __forceinline__ float bf16_round(float v) { return __bfloat162float(__float2bfloat16_rn(v)); }
__device__ __forceinline__ uint32_t bf2_mul(uint32_t a, uint32_t b) {
    uint32_t r;
    asm("mul.rn.bf16x2 %0, %1, %2;" : "=r"(r) : "r"(a), "r"(b));
    return r;
}
__device__ __forceinline__ uint32_t bf2_add_relu(uint32_t a, uint32_t b) {
    uint32_t r;
    asm("fma.rn.relu.bf16x2 %0, %1, %2, %3;" : "=r"(r) : "r"(a), "r"(0x3f803f80u), "r"(b));
    return r;
}
__device__ __forceinline__ uint4 ldg128(const void* p) {
    uint4 v;
    asm volatile("ld.global.nc.v4.u32 {%0, %1, %2, %3}, [%4];" : "=r"(v.x), "=r"(v.y), "=r"(v.z), "=r"(v.w) : "l"(p));
    return v;
}
__device__ __forceinline__ uint32_t ldg32(const void* p) {
    uint32_t v;
    asm volatile("ld.global.nc.u32 %0, [%1];" : "=r"(v) : "l"(p));
    return v;
}
__device__ __forceinline__ uint32_t ldg32na(const void* p) {
    uint32_t v;
    asm volatile("ld.global.nc.L1::no_allocate.u32 %0, [%1];" : "=r"(v) : "l"(p));
    return v;
}
__device__ __forceinline__ uint32_t ldg16(const __nv_bfloat16* p) {
    uint32_t v;
    asm volatile("ld.global.nc.u16 %0, [%1];" : "=r"(v) : "l"(p));
    return v;
}
__device__ __forceinline__ uint4 ld_relaxed128(const void* p) {
    uint4 v;
    asm volatile("ld.relaxed.gpu.global.v4.u32 {%0, %1, %2, %3}, [%4];" : "=r"(v.x), "=r"(v.y), "=r"(v.z), "=r"(v.w) : "l"(p) : "memory");
    return v;
}
__device__ __forceinline__ uint2 ld_relaxed64(const void* p) {
    unsigned long long v;
    asm volatile("ld.relaxed.gpu.global.u64 %0, [%1];" : "=l"(v) : "l"(p) : "memory");
    return make_uint2((uint32_t)v, (uint32_t)(v >> 32));
}
__device__ __forceinline__ void st_relaxed64(void* p, uint32_t lo, uint32_t hi) {
    unsigned long long v = ((unsigned long long)hi << 32) | lo;
    asm volatile("st.relaxed.gpu.global.u64 [%0], %1;" ::"l"(p), "l"(v) : "memory");
}
__device__ __forceinline__ void st_relaxed2x64(void* p, uint32_t a, uint32_t b, uint32_t c, uint32_t d) {
    unsigned long long v0 = ((unsigned long long)b << 32) | a, v1 = ((unsigned long long)d << 32) | c;
    asm volatile("st.relaxed.gpu.global.v2.u64 [%0], {%1, %2};" ::"l"(p), "l"(v0), "l"(v1) : "memory");
}
__device__ __forceinline__ uint4 ld_relaxed2x64(const void* p) {
    unsigned long long v0, v1;
    asm volatile("ld.relaxed.gpu.global.v2.u64 {%0, %1}, [%2];" : "=l"(v0), "=l"(v1) : "l"(p) : "memory");
    return make_uint4((uint32_t)v0, (uint32_t)(v0 >> 32), (uint32_t)v1, (uint32_t)(v1 >> 32));
}
__device__ __forceinline__ void stg128(void* p, uint32_t a, uint32_t b, uint32_t c, uint32_t d) {
    asm volatile("st.global.v4.u32 [%0], {%1, %2, %3, %4};" ::"l"(p), "r"(a), "r"(b), "r"(c), "r"(d) : "memory");
}
__device__ __forceinline__ void stg64f(void* p, float a, float b) {
    asm volatile("st.global.v2.f32 [%0], {%1, %2};" ::"l"(p), "f"(a), "f"(b) : "memory");
}
__device__ __forceinline__ uint4 lds128(uint32_t a) {
    uint4 v;
    asm volatile("ld.shared.v4.u32 {%0, %1, %2, %3}, [%4];" : "=r"(v.x), "=r"(v.y), "=r"(v.z), "=r"(v.w) : "r"(a) : "memory");
    return v;
}
__device__ __forceinline__ uint2 lds64(uint32_t a) {
    uint2 v;
    asm volatile("ld.shared.v2.u32 {%0, %1}, [%2];" : "=r"(v.x), "=r"(v.y) : "r"(a) : "memory");
    return v;
}
__device__ __forceinline__ uint4 ldsm4(uint32_t a) {
    uint4 v;
    asm volatile("ldmatrix.sync.aligned.m8n8.x4.shared.b16 {%0, %1, %2, %3}, [%4];" : "=r"(v.x), "=r"(v.y), "=r"(v.z), "=r"(v.w) : "r"(a) : "memory");
    return v;
}
__device__ __forceinline__ uint32_t lds16(uint32_t a) {
    uint32_t v;
    asm volatile("ld.shared.u16 %0, [%1];" : "=r"(v) : "r"(a) : "memory");
    return v;
}
__device__ __forceinline__ void sts16(uint32_t a, uint32_t x) {
    asm volatile("st.shared.u16 [%0], %1;" ::"r"(a), "h"((uint16_t)x) : "memory");
}
__device__ __forceinline__ void st_relaxed32(void* p, uint32_t v) {
    asm volatile("st.relaxed.gpu.global.u32 [%0], %1;" ::"l"(p), "r"(v) : "memory");
}
__device__ __forceinline__ float lds32f(uint32_t a) {
    float v;
    asm volatile("ld.shared.f32 %0, [%1];" : "=f"(v) : "r"(a) : "memory");
    return v;
}
__device__ __forceinline__ void sts128(uint32_t a, uint32_t x, uint32_t y, uint32_t z, uint32_t w) {
    asm volatile("st.shared.v4.u32 [%0], {%1, %2, %3, %4};" ::"r"(a), "r"(x), "r"(y), "r"(z), "r"(w) : "memory");
}
__device__ __forceinline__ void sts64f(uint32_t a, float x, float y) {
    asm volatile("st.shared.v2.f32 [%0], {%1, %2};" ::"r"(a), "f"(x), "f"(y) : "memory");
}
__device__ __forceinline__ float4 lds128f(uint32_t a) {
    float4 v;
    asm volatile("ld.shared.v4.f32 {%0, %1, %2, %3}, [%4];" : "=f"(v.x), "=f"(v.y), "=f"(v.z), "=f"(v.w) : "r"(a) : "memory");
    return v;
}
__device__ __forceinline__ uint32_t lds32(uint32_t a) {
    uint32_t v;
    asm volatile("ld.shared.u32 %0, [%1];" : "=r"(v) : "r"(a) : "memory");
    return v;
}
__device__ __forceinline__ void sts32(uint32_t a, uint32_t x) {
    asm volatile("st.shared.u32 [%0], %1;" ::"r"(a), "r"(x) : "memory");
}
__device__ __forceinline__ void stg128f(void* p, float a, float b, float c, float d) {
    asm volatile("st.global.v4.f32 [%0], {%1, %2, %3, %4};" ::"l"(p), "f"(a), "f"(b), "f"(c), "f"(d) : "memory");
}
__device__ __forceinline__ unsigned ld_relaxed32(const unsigned* p) {
    unsigned v;
    asm volatile("ld.relaxed.gpu.global.u32 %0, [%1];" : "=r"(v) : "l"(p) : "memory");
    return v;
}
__device__ __forceinline__ void wait_counter(const unsigned* p, unsigned target) {
    unsigned n = 0, v;
    while (true) {
        asm volatile("ld.acquire.gpu.global.u32 %0, [%1];" : "=r"(v) : "l"(p) : "memory");
        if ((int)(v - target) >= 0) break;
        if (++n > kSpinLimit) TRAP();
        __nanosleep(32);
    }
}
#define KT(IT, W) do { } while (0)
#define STAMP(cond, slot) do { } while (0)
#define STAMPA(cond, slot) STAMP(cond, slot)
#define STAMPB(cond, slot) do { } while (0)

template <int TA, int TB>
__device__ __forceinline__ void wgmma_n256(float (&d)[128], uint64_t da, uint64_t db, int keep) {
    asm volatile(
        "{\n.reg .pred p;\nsetp.ne.b32 p, %132, 0;\n"
        "wgmma.mma_async.sync.aligned.m64n256k16.f32.bf16.bf16 "
        "{%0, %1, %2, %3, %4, %5, %6, %7, %8, %9, %10, %11, %12, %13, %14, %15, "
        "%16, %17, %18, %19, %20, %21, %22, %23, %24, %25, %26, %27, %28, %29, %30, %31, "
        "%32, %33, %34, %35, %36, %37, %38, %39, %40, %41, %42, %43, %44, %45, %46, %47, "
        "%48, %49, %50, %51, %52, %53, %54, %55, %56, %57, %58, %59, %60, %61, %62, %63, "
        "%64, %65, %66, %67, %68, %69, %70, %71, %72, %73, %74, %75, %76, %77, %78, %79, "
        "%80, %81, %82, %83, %84, %85, %86, %87, %88, %89, %90, %91, %92, %93, %94, %95, "
        "%96, %97, %98, %99, %100, %101, %102, %103, %104, %105, %106, %107, %108, %109, %110, %111, "
        "%112, %113, %114, %115, %116, %117, %118, %119, %120, %121, %122, %123, %124, %125, %126, %127}, "
        "%128, %129, p, 1, 1, %130, %131;\n}\n"
        : "+f"(d[0]), "+f"(d[1]), "+f"(d[2]), "+f"(d[3]), "+f"(d[4]), "+f"(d[5]), "+f"(d[6]), "+f"(d[7]),
          "+f"(d[8]), "+f"(d[9]), "+f"(d[10]), "+f"(d[11]), "+f"(d[12]), "+f"(d[13]), "+f"(d[14]), "+f"(d[15]),
          "+f"(d[16]), "+f"(d[17]), "+f"(d[18]), "+f"(d[19]), "+f"(d[20]), "+f"(d[21]), "+f"(d[22]), "+f"(d[23]),
          "+f"(d[24]), "+f"(d[25]), "+f"(d[26]), "+f"(d[27]), "+f"(d[28]), "+f"(d[29]), "+f"(d[30]), "+f"(d[31]),
          "+f"(d[32]), "+f"(d[33]), "+f"(d[34]), "+f"(d[35]), "+f"(d[36]), "+f"(d[37]), "+f"(d[38]), "+f"(d[39]),
          "+f"(d[40]), "+f"(d[41]), "+f"(d[42]), "+f"(d[43]), "+f"(d[44]), "+f"(d[45]), "+f"(d[46]), "+f"(d[47]),
          "+f"(d[48]), "+f"(d[49]), "+f"(d[50]), "+f"(d[51]), "+f"(d[52]), "+f"(d[53]), "+f"(d[54]), "+f"(d[55]),
          "+f"(d[56]), "+f"(d[57]), "+f"(d[58]), "+f"(d[59]), "+f"(d[60]), "+f"(d[61]), "+f"(d[62]), "+f"(d[63]),
          "+f"(d[64]), "+f"(d[65]), "+f"(d[66]), "+f"(d[67]), "+f"(d[68]), "+f"(d[69]), "+f"(d[70]), "+f"(d[71]),
          "+f"(d[72]), "+f"(d[73]), "+f"(d[74]), "+f"(d[75]), "+f"(d[76]), "+f"(d[77]), "+f"(d[78]), "+f"(d[79]),
          "+f"(d[80]), "+f"(d[81]), "+f"(d[82]), "+f"(d[83]), "+f"(d[84]), "+f"(d[85]), "+f"(d[86]), "+f"(d[87]),
          "+f"(d[88]), "+f"(d[89]), "+f"(d[90]), "+f"(d[91]), "+f"(d[92]), "+f"(d[93]), "+f"(d[94]), "+f"(d[95]),
          "+f"(d[96]), "+f"(d[97]), "+f"(d[98]), "+f"(d[99]), "+f"(d[100]), "+f"(d[101]), "+f"(d[102]), "+f"(d[103]),
          "+f"(d[104]), "+f"(d[105]), "+f"(d[106]), "+f"(d[107]), "+f"(d[108]), "+f"(d[109]), "+f"(d[110]), "+f"(d[111]),
          "+f"(d[112]), "+f"(d[113]), "+f"(d[114]), "+f"(d[115]), "+f"(d[116]), "+f"(d[117]), "+f"(d[118]), "+f"(d[119]),
          "+f"(d[120]), "+f"(d[121]), "+f"(d[122]), "+f"(d[123]), "+f"(d[124]), "+f"(d[125]), "+f"(d[126]), "+f"(d[127])
        : "l"(da), "l"(db), "n"(TA), "n"(TB), "r"(keep));
}
template <int TA, int TB>
__device__ __forceinline__ void wgmma_n192(float (&d)[128], uint64_t da, uint64_t db, int keep) {
    asm volatile(
        "{\n.reg .pred p;\nsetp.ne.b32 p, %100, 0;\n"
        "wgmma.mma_async.sync.aligned.m64n192k16.f32.bf16.bf16 "
        "{%0, %1, %2, %3, %4, %5, %6, %7, %8, %9, %10, %11, %12, %13, %14, %15, "
        "%16, %17, %18, %19, %20, %21, %22, %23, %24, %25, %26, %27, %28, %29, %30, %31, "
        "%32, %33, %34, %35, %36, %37, %38, %39, %40, %41, %42, %43, %44, %45, %46, %47, "
        "%48, %49, %50, %51, %52, %53, %54, %55, %56, %57, %58, %59, %60, %61, %62, %63, "
        "%64, %65, %66, %67, %68, %69, %70, %71, %72, %73, %74, %75, %76, %77, %78, %79, "
        "%80, %81, %82, %83, %84, %85, %86, %87, %88, %89, %90, %91, %92, %93, %94, %95}, "
        "%96, %97, p, 1, 1, %98, %99;\n}\n"
        : "+f"(d[0]), "+f"(d[1]), "+f"(d[2]), "+f"(d[3]), "+f"(d[4]), "+f"(d[5]), "+f"(d[6]), "+f"(d[7]),
          "+f"(d[8]), "+f"(d[9]), "+f"(d[10]), "+f"(d[11]), "+f"(d[12]), "+f"(d[13]), "+f"(d[14]), "+f"(d[15]),
          "+f"(d[16]), "+f"(d[17]), "+f"(d[18]), "+f"(d[19]), "+f"(d[20]), "+f"(d[21]), "+f"(d[22]), "+f"(d[23]),
          "+f"(d[24]), "+f"(d[25]), "+f"(d[26]), "+f"(d[27]), "+f"(d[28]), "+f"(d[29]), "+f"(d[30]), "+f"(d[31]),
          "+f"(d[32]), "+f"(d[33]), "+f"(d[34]), "+f"(d[35]), "+f"(d[36]), "+f"(d[37]), "+f"(d[38]), "+f"(d[39]),
          "+f"(d[40]), "+f"(d[41]), "+f"(d[42]), "+f"(d[43]), "+f"(d[44]), "+f"(d[45]), "+f"(d[46]), "+f"(d[47]),
          "+f"(d[48]), "+f"(d[49]), "+f"(d[50]), "+f"(d[51]), "+f"(d[52]), "+f"(d[53]), "+f"(d[54]), "+f"(d[55]),
          "+f"(d[56]), "+f"(d[57]), "+f"(d[58]), "+f"(d[59]), "+f"(d[60]), "+f"(d[61]), "+f"(d[62]), "+f"(d[63]),
          "+f"(d[64]), "+f"(d[65]), "+f"(d[66]), "+f"(d[67]), "+f"(d[68]), "+f"(d[69]), "+f"(d[70]), "+f"(d[71]),
          "+f"(d[72]), "+f"(d[73]), "+f"(d[74]), "+f"(d[75]), "+f"(d[76]), "+f"(d[77]), "+f"(d[78]), "+f"(d[79]),
          "+f"(d[80]), "+f"(d[81]), "+f"(d[82]), "+f"(d[83]), "+f"(d[84]), "+f"(d[85]), "+f"(d[86]), "+f"(d[87]),
          "+f"(d[88]), "+f"(d[89]), "+f"(d[90]), "+f"(d[91]), "+f"(d[92]), "+f"(d[93]), "+f"(d[94]), "+f"(d[95])
        : "l"(da), "l"(db), "n"(TA), "n"(TB), "r"(keep));
}
template <int TA, int TB, int O>
__device__ __forceinline__ void wgmma_n64(float (&d)[128], uint64_t da, uint64_t db, int keep) {
    asm volatile(
        "{\n.reg .pred p;\nsetp.ne.b32 p, %36, 0;\n"
        "wgmma.mma_async.sync.aligned.m64n64k16.f32.bf16.bf16 "
        "{%0, %1, %2, %3, %4, %5, %6, %7, %8, %9, %10, %11, %12, %13, %14, %15, "
        "%16, %17, %18, %19, %20, %21, %22, %23, %24, %25, %26, %27, %28, %29, %30, %31}, "
        "%32, %33, p, 1, 1, %34, %35;\n}\n"
        : "+f"(d[O + 0]), "+f"(d[O + 1]), "+f"(d[O + 2]), "+f"(d[O + 3]), "+f"(d[O + 4]), "+f"(d[O + 5]), "+f"(d[O + 6]), "+f"(d[O + 7]),
          "+f"(d[O + 8]), "+f"(d[O + 9]), "+f"(d[O + 10]), "+f"(d[O + 11]), "+f"(d[O + 12]), "+f"(d[O + 13]), "+f"(d[O + 14]), "+f"(d[O + 15]),
          "+f"(d[O + 16]), "+f"(d[O + 17]), "+f"(d[O + 18]), "+f"(d[O + 19]), "+f"(d[O + 20]), "+f"(d[O + 21]), "+f"(d[O + 22]), "+f"(d[O + 23]),
          "+f"(d[O + 24]), "+f"(d[O + 25]), "+f"(d[O + 26]), "+f"(d[O + 27]), "+f"(d[O + 28]), "+f"(d[O + 29]), "+f"(d[O + 30]), "+f"(d[O + 31])
        : "l"(da), "l"(db), "n"(TA), "n"(TB), "r"(keep));
}
template <int O>
__device__ __forceinline__ void wgmma_n64_rs(float (&d)[128], uint32_t a0, uint32_t a1, uint32_t a2, uint32_t a3, uint64_t db) {
    asm volatile(
        "{\n.reg .pred p;\nsetp.ne.b32 p, 1, 0;\n"
        "wgmma.mma_async.sync.aligned.m64n64k16.f32.bf16.bf16 "
        "{%0, %1, %2, %3, %4, %5, %6, %7, %8, %9, %10, %11, %12, %13, %14, %15, "
        "%16, %17, %18, %19, %20, %21, %22, %23, %24, %25, %26, %27, %28, %29, %30, %31}, "
        "{%32, %33, %34, %35}, %36, p, 1, 1, 1;\n}\n"
        : "+f"(d[O + 0]), "+f"(d[O + 1]), "+f"(d[O + 2]), "+f"(d[O + 3]), "+f"(d[O + 4]), "+f"(d[O + 5]), "+f"(d[O + 6]), "+f"(d[O + 7]),
          "+f"(d[O + 8]), "+f"(d[O + 9]), "+f"(d[O + 10]), "+f"(d[O + 11]), "+f"(d[O + 12]), "+f"(d[O + 13]), "+f"(d[O + 14]), "+f"(d[O + 15]),
          "+f"(d[O + 16]), "+f"(d[O + 17]), "+f"(d[O + 18]), "+f"(d[O + 19]), "+f"(d[O + 20]), "+f"(d[O + 21]), "+f"(d[O + 22]), "+f"(d[O + 23]),
          "+f"(d[O + 24]), "+f"(d[O + 25]), "+f"(d[O + 26]), "+f"(d[O + 27]), "+f"(d[O + 28]), "+f"(d[O + 29]), "+f"(d[O + 30]), "+f"(d[O + 31])
        : "r"(a0), "r"(a1), "r"(a2), "r"(a3), "l"(db));
}

constexpr uint64_t kDescHi = (uint64_t)(64u | 0x40000000u) << 32;
template <int MODE>
__device__ __forceinline__ void mma_kblock(float (&acc)[128], uint32_t a_lo, uint32_t b_lo, int keep) {
    constexpr uint32_t HALF = (MODE == 1) ? 12288u : 16384u;
    constexpr bool BN = (MODE == 1 || MODE == 2);
#pragma unroll
    for (int kk = 0; kk < 4; ++kk) {
        const uint32_t ao = (MODE == 3) ? kk * 2048u : kk * 32u;
        const uint32_t bo = BN ? ((kk >> 1) * HALF + (kk & 1) * 2048u) : kk * 32u;
        const uint64_t da = kDescHi | (uint64_t)(a_lo + (ao >> 4) + (1u << 16));
        const uint64_t db = kDescHi | (uint64_t)(b_lo + (bo >> 4) + (BN ? (256u << 16) : (1u << 16)));
        if (MODE == 1) wgmma_n192<0, 1>(acc, da, db, kk == 0 ? keep : 1);
        else wgmma_n256<(MODE == 3), BN>(acc, da, db, kk == 0 ? keep : 1);
    }
}

struct Params {
    Scratch* s;
    const __nv_bfloat16* x;
    const __nv_bfloat16* b_re;
    const __nv_bfloat16* b_im;
    const __nv_bfloat16* gate_w;
    const __nv_bfloat16* lam_re;
    const __nv_bfloat16* lam_im;
    const __nv_bfloat16* log_dt;
    const __nv_bfloat16* dskip;
    const __nv_bfloat16* b1;
    const __nv_bfloat16* b2;
    float* out;
    int swap;
};

#define CMUL(rr, ri, ar, ai, br, bi) do { float _r = (ar) * (br) - (ai) * (bi); float _i = (ar) * (bi) + (ai) * (br); rr = _r; ri = _i; } while (0)
#define CFMA(rr, ri, ar, ai, br, bi) do { float _r = fmaf(-(ai), (bi), fmaf((ar), (br), rr)); float _i = fmaf((ai), (br), fmaf((ar), (bi), ri)); rr = _r; ri = _i; } while (0)

#define KB_OPEN(IT, LAST)                                                                        \
    KT(IT, 0);                                                                                   \
    if (ORDER && (LAST) && wg == 1) bar_sync(7, 256);                                            \
    mbar_wait(bar_full + 8 * ((IT) & 3), ((IT) >> 2) & 1);                                \
    KT(IT, 1);
#define KB_CLOSE(IT, LAST, REL)                                                                  \
    if (ORDER && (LAST) && wg == 0) bar_arrive(7, 256);                                          \
    wgmma_wait<1>();                                                                             \
    if (lane < 2 && (REL)) mbar_arrive_cluster(rel_addr + 8 * (((IT) - 1) & 3));
#define KBLOCK(MODE, IT, FIRST, LAST)                                                            \
    {                                                                                            \
        const uint32_t so = ((IT) & 3) * (kStageBytes >> 4);                                     \
        KB_OPEN(IT, LAST);                                                                       \
        wgmma_fence();                                                                           \
        mma_kblock<MODE>(acc, a_lo + so, b_lo + so, !(FIRST));                                   \
        wgmma_commit();                                                                          \
        KB_CLOSE(IT, LAST, !(FIRST));                                                            \
    }
#define TILE_END() do { wgmma_wait<0>(); if (lane < 2) mbar_arrive_cluster(rel_addr + 24); } while (0)

__global__ void __cluster_dims__(2, 1, 1) __launch_bounds__(384, 1)
fused_kernel(const __grid_constant__ CUtensorMap mB, const __grid_constant__ CUtensorMap mXs, const __grid_constant__ CUtensorMap mXf,
             const __grid_constant__ CUtensorMap mW1b, const __grid_constant__ CUtensorMap mW1a, const __grid_constant__ CUtensorMap mHs,
             const __grid_constant__ CUtensorMap mHf, const __grid_constant__ CUtensorMap mCre, const __grid_constant__ CUtensorMap mCim,
             const __grid_constant__ CUtensorMap mW2, const __grid_constant__ CUtensorMap mW2n, const __grid_constant__ CUtensorMap mW2p,
             const __grid_constant__ CUtensorMap mHf3, const Params p) {
    extern __shared__ __align__(1024) uint8_t smem_raw[];
    if (PFTOP) { prefetch_map(&mB); prefetch_map(&mXs); }
    const uint32_t sbase = smem_u32(smem_raw);
    if ((sbase & 0x3ffffu) != kSmemOrg) return;
    const uint32_t bar_full = sbase + kBarOff, bar_empty = bar_full + 32, bar_dep = bar_full + 64;
    const uint32_t bar_x = bar_full + 88, bar_c = bar_full + 96, role_s = bar_full + 104, bar_role = bar_full + 120, tag_s = bar_full + 112 + (threadIdx.x & 1) * 4;

    const int tid = threadIdx.x, lane = tid & 31;
    const int warp = __shfl_sync(0xffffffffu, tid >> 5, 0);
    const uint32_t rank = blockIdx.x & 1;

    int pref;
    {
        unsigned smid;
        asm("mov.u32 %0, %%smid;" : "=r"(smid));
        const int t = smid >> 1, u = t - 32, d = (u * 37) >> 8;
        pref = (t < 32) ? (t & 7) * 8 + (t >> 3) : (t < 60) ? (1 + u - 7 * d) * 8 + 4 + d : ((t - 58) & 7);
    }
    STAMP(tid == 0, 0);
    int role = pref;
#define ROLE_VARS()                                                                                               \
    const int c = role >> 3;                                                             \
    const int j8 = role & 7;                                                        \
    const int cb = j8 * 2 + (int)rank;                                             \
    const int rb = 2 * c + (int)rank;                                               \
    const int kh = j8 >> 2;                 \
    const int colK = (j8 & 3) * 256 + kh * 128, colS = colK ^ 128;    \
    (void)cb; (void)rb; (void)colS;

#define INIT_ALL()                                                                                    \
    if (warp == INITW && elect_one()) {                                                               \
        if (!PFTOP) { prefetch_map(&mB); prefetch_map(&mXs); }                                        \
        _Pragma("unroll") for (int s = 0; s < kStages; ++s) {                                         \
            mbar_init(bar_full + 8 * s, 1);                                                           \
            mbar_init(bar_empty + 8 * s, 16);                                                         \
            mbar_init(bar_dep + 8 * s, 1);                                \
        }                                                                                             \
        mbar_init(bar_c, 96);                                                                         \
        mbar_init(bar_role, 1);                                                                       \
        asm volatile("fence.mbarrier_init.release.cluster;\nfence.proxy.async.shared::cta;" ::: "memory"); \
        mbar_expect_tx(bar_full, 49152);            \
        tma4(sbase, &mB, bar_full, 0, 0, 0, ((pref & 7) * 2 + (int)rank) * 8);                        \
        if (!MC0) {                                                                                   \
        tma5(sbase + kABytes, &mXs, bar_full, 0, 0, 0, 0, pref >> 3);                                 \
        tma5(sbase + kABytes + 16384, &mXs, bar_full, 0, 0, 0, 16, pref >> 3);                        \
        }                                                                                             \
        mbar_expect_tx(bar_x, 2048);                                                                  \
        bulk_load(sbase + kXOff, p.gate_w, 2048, bar_x);                                              \
        mbar_expect_tx(bar_role, 8);                                                                  \
    }
    if (PRODCOND) {
        asm volatile("setmaxnreg.dec.sync.aligned.u32 24;");
        unsigned taken = 0;
        if (tid == 352 && rank == 0) {
            taken = atom_exch(&p.s->claim[pref], 1u);
        }
        __syncwarp();
        cluster_arrive();
        cluster_wait();
        if (warp > 8) {
            if (tid == 352) {
#pragma unroll 1
                for (int i = 0; taken != 0 && i < 64; ++i) { role = i + 256; taken = atom_exch(&p.s->claim[i], 1u); }
                st_async32(mapa(role_s + 4 * rank, 0), role, mapa(bar_role, 0));
                st_async32(mapa(role_s + 4 * rank, 1), role, mapa(bar_role, 1));
            }
            __syncwarp();
            mbar_wait(bar_role, 0);
            role = __shfl_sync(0xffffffffu, (int)lds32(role_s), 0) & 63;
            ROLE_VARS();
            if (warp == 11) {
                if (lane < 11) prefetch_map(&mXf + lane);
#pragma unroll 1
                for (int en = lane; en < 88; en += 32) {
                    const int J = en >> 2;
                    const __nv_bfloat16* src = ((J < 14) ? p.b1 : (J < 18) ? p.dskip : p.b2) + 32 * J + 2 * (en & 3) +
                                               ((J < 6) ? 2048 + 192 * j8 : (J < 14) ? 256 * j8 - 192 : colK - ((J < 18) ? 448 : 576));
                    sts128(sbase + kBiasOff + en * 16, ldg32(src), ldg32(src + 8), ldg32(src + 16), ldg32(src + 24));
                }
                mbar_arrive_local(bar_c);
            } else {
                {
                    sts32(tag_s, ld_relaxed32(&p.s->epoch) + 1);
                    const int ch = cb * 64 + (tid - 288);
                    const uint32_t t_s = sbase + kTabOff + (tid - 288) * 64;
                    const float Lr = bf_lo(ldg16(p.lam_re + ch)), Li = bf_lo(ldg16(p.lam_im + ch));
                    const float dt = bf16_round(expf(bf_lo(ldg16(p.log_dt + ch))));
                    const float ea = expf(dt * Lr);
                    float lr, li;
                    sincospif((dt * Li) * 0.31830988618379067f, &li, &lr);
                    lr *= ea; li *= ea;
                    const float nr = lr - 1.0f, ni = li;
                    const bool big = fabsf(Lr) >= fabsf(Li);
                    const float u = big ? Lr : Li, v = big ? Li : Lr;
                    const float t = v / u, d = 2.0f / fmaf(v, t, u);
                    const float cr = (big ? fmaf(ni, t, nr) : fmaf(nr, t, ni)) * d, ci = (big ? fmaf(-nr, t, ni) : fmaf(ni, t, -nr)) * d;
                    if (p.swap) li = -li;
                    const float m00 = p.swap ? -ci : cr, m01 = p.swap ? cr : -ci, m10 = p.swap ? -cr : -ci, m11 = p.swap ? -ci : -cr;
#pragma unroll
                    for (int q = 0; q < 4; ++q) {
                        sts128f(t_s + q * 16, lr, li, m00, m01);
                        sts128f(t_s + 12288 + q * 16, 0.f, 0.f, 0.f, 0.f);
                    }
#pragma unroll 1
                    for (int i = 0; i < 6; ++i) CMUL(lr, li, lr, li, lr, li);
                    float ar, ai, br, bi;
                    CMUL(ar, ai, lr, li, lr, li);
                    CMUL(br, bi, ar, ai, lr, li);
                    sts128f(t_s + 4096, m10, m11, 0.f, 0.f);
#pragma unroll
                    for (int q = 1; q < 4; ++q) sts128f(t_s + 4096 + q * 16, m10, m11, lr, li);
                    sts128f(t_s + 8192, 0.f, 0.f, 1.f, 0.f);
                    sts128f(t_s + 8192 + 16, 0.f, 0.f, lr, li);
                    sts128f(t_s + 8192 + 32, ar, ai, ar, ai);
                    sts128f(t_s + 8192 + 48, ar, ai, br, bi);
                    CMUL(ar, ai, ar, ai, ar, ai);
                    br = 1.f; bi = 0.f;
#pragma unroll 1
                    for (int k = c - 1; k >= 0; --k) {
                        sts64f(t_s + 12288 + (k & 3) * 16 + (k >> 2) * 8, br, bi);
                        CMUL(br, bi, br, bi, ar, ai);
                    }
                    mbar_arrive_local(bar_c);
                }
                if (warp == 9) {
#pragma unroll 1
                    for (int ev = 0; ev < 3; ++ev) {
                        if (ev == 2) {
                            uint8_t* box = p.s->X + (size_t)(role * 2 + rank) * kXBytes + lane * 16;
#pragma unroll 1
                            for (int i = 0; i < kXBytes; i += 512) stg128(box + i, 0, 0, 0, 0);
                        }
                        bar_sync(3 + ev, 288);
                        if (lane == 0) {
                            unsigned* cnt = &p.s->cnt[(ev == 0 ? c : 16 * ev - 8 + rb) * 32];
                            asm volatile("fence.acq_rel.gpu;\nfence.proxy.async.global;" ::: "memory");
                            asm volatile("red.relaxed.gpu.global.add.u32 [%0], 1;" ::"l"(cnt) : "memory");
                        }
                        __syncwarp();
                    }
                } else if (lane == 0) {
                    const unsigned tag = lds32(tag_s);
#pragma unroll 1
                    for (int ev = 0; ev < 3; ++ev) {
                        wait_counter(&p.s->cnt[(ev == 0 ? c : 16 * ev - 8 + rb) * 32], tag * (ev == 0 ? 16u : 8u));
                        mbar_arrive_local(bar_dep + 8 * ev);
                        if (ev == 0 && atomicInc(&p.s->done, 127u) == 127u) {
                            st_relaxed32(&p.s->epoch, tag);
#pragma unroll 1
                            for (int i = 0; i < 64; i += 4) stg128(&p.s->claim[i], 0, 0, 0, 0);
                        }
                    }
                }
            }
        } else if (elect_one()) {
            int it = 1, again = 15;
            if (MC0) tma5_mc(sbase + kABytes + rank * 16384, &mXs, bar_full, 0, 0, 0, rank * 16, role >> 3);
#define ACQUIRE(BYTES)                                                   \
    const uint32_t st = sbase + (it & 3) * kStageBytes, fb = bar_full + 8 * (it & 3); \
    mbar_wait(bar_empty + 8 * (it & 3), ((it >> 2) & 1) ^ 1);     \
    mbar_expect_tx(fb, BYTES);
#pragma unroll 1
            for (; it < 16; ++it) {
                ACQUIRE(49152);
                tma4(st, &mB, fb, it * 64, 0, 0, ((role & 7) * 2 + (int)rank) * 8);
                tma5_mc(st + kABytes + rank * 16384, &mXs, fb, it * 64, 0, 0, rank * 16, role >> 3);
                if (it == again) {
                    mbar_wait(bar_role, 0);
                    const uint2 fin = lds64(role_s);
                    role = fin.x & 63;
                    if (fin.x != fin.y) { it = -1; again = 16; }
                }
            }
            ROLE_VARS();
#pragma unroll 1
            for (; it < 48; ++it) {
                const bool t1 = it < 32;
                const int k0 = (it & 15) * 64;
                ACQUIRE(t1 ? 40960 : 49152);
                tma5(st, &mXf, fb, k0, 0, 0, rank * 4, c);
                tma3_mc(st + kABytes + rank * (t1 ? 12288 : 16384), t1 ? &mW1b : &mW1a, fb, 0, k0 + rank * 32, t1 ? 32 + 3 * j8 : 4 * j8);
                if ((it & ~2) == XLDKB) {
                    const int h = (it >> 1) & 1;
                    if (h == 0) mbar_expect_tx(bar_x, 32768);
                    tma5(sbase + kXOff + h * 16384, &mXf, bar_x, colK + h * 64, 0, 0, rank * 4, c);
                }
            }
            STAMPA(true, 8);
            mbar_wait(bar_dep, 0);
            asm volatile("fence.proxy.async.global;" ::: "memory");
            STAMPA(true, 9);
#pragma unroll 1
            for (; it < 64; ++it) {
                const int k0 = (it & 15) * 64;
                ACQUIRE(49152);
                tma3(st, &mHs, fb, 0, kh * 1024 + k0, rb * 2);
                tma2_mc(st + kABytes + rank * 16384, kh ? &mCim : &mCre, fb, k0, rank ? colS : colK);
            }
            int f0 = 2048 + 768 * kh;
#pragma unroll 1
            for (; it < 88; ++it, f0 += 64) {
                if (it == 64 || it == 76) {
                    mbar_wait(bar_dep + (it == 64 ? 8 : 16), 0);
                    asm volatile("fence.proxy.async.global;" ::: "memory");
                    if (it == 76) f0 = 1024 * kh;
                }
                if (f0 == 256 * j8) f0 += 256;
                ACQUIRE(49152);
                tma2(st, &mHf, fb, f0, rb * 128);
                tma5_mc(st + kABytes + rank * 16384, &mW2, fb, 0, 0, (f0 >> 3) + 4 * rank, 0, colK >> 6);
                tma5_mc(st + kABytes + rank * 16384 + 8192, &mW2, fb, 0, 0, (f0 >> 3) + 4 * rank, 0, colS >> 6);
                if ((it >> 2) == PFKB / 4) tma2_pf(&mW2n, colK + (it & 2) * 32, 256 * (j8 ^ ((it & 1) * 4)) + 128 * rank);
            }
#pragma unroll 1
            for (; it < kTotal; ++it) {
                const int h = (it & 2) * 32;
                ACQUIRE(49152);
                tma3(st, &mHf3, fb, 0, rb * 128 + h, 4 * (j8 ^ 4) + 2 * (it & 1));
                if (it & 1) tma5_mc(st + kABytes + rank * 16384, &mW2p, fb, colK + h, 0, 0, 0, 8 * (j8 ^ 4) + 4 * rank);
                else tma2_mc(st + kABytes + rank * 16384, &mW2n, fb, colK + h, 256 * j8 + 128 * rank);
            }
        }
    } else {
        INIT_ALL();
        if (warp >= 8 - PF0LINES) {
            const int row = blockIdx.x * 32 + lane;
            const __nv_bfloat16* src = (row < 2048) ? p.x : (row < 3072) ? p.b_re - 2048 * kD : p.b_im - 3072 * kD;
            asm volatile("prefetch.global.L2 [%0];" ::"l"(src + row * kD + (7 - warp) * 64) : "memory");
        }
        __syncwarp();
        cluster_arrive();
        asm volatile("setmaxnreg.inc.sync.aligned.u32 240;");
        const int wg = warp >> 2, w = warp & 3, r = lane >> 2, q = lane & 3, tw = tid & 127;
        uint32_t a_lo = (kSmemOrg + wg * 8192) >> 4;
        constexpr uint32_t b_lo = (kSmemOrg + kABytes) >> 4;
        const uint32_t rel_addr = mapa(bar_empty, (uint32_t)(lane & 1));
        const uint32_t gate_s = sbase + kGateOff;
        float acc[128];
        uint32_t pk[64];
        unsigned tag;
        UNDEF_R(tag);

#pragma unroll
        for (int i = 0; i < 128; ++i) UNDEF_F(acc[i]);
        float gs = 0.f;
        {
            const uint32_t gx_s = sbase + kABytes + (16 * rank + 2 * warp + (lane >> 4)) * 128 +
                                  ((((lane & 15) >> 1) ^ (2 * w + (lane >> 4))) << 4) + (lane & 1) * 8;
            const uint32_t gw_s = sbase + kXOff + (lane & 15) * 8;
            uint32_t again = 15;
            cluster_wait();
#pragma unroll 1
            for (uint32_t it = 0; it < 16; ++it) {
                const uint32_t so = (it & 3) * (kStageBytes >> 4);
                KB_OPEN(it, it == 15);
                wgmma_fence();
                mma_kblock<0>(acc, a_lo + so, b_lo + so, it != 0);
                wgmma_commit();
                KB_CLOSE(it, it == 15, it + again != 15);
                STAMPA(tid == 0 && it == 0, 1);
                mbar_wait(bar_x, 0);
                const uint2 xa = lds64(gx_s + (role & 7) * 4096 + (it & 3) * kStageBytes), wa = lds64(gw_s + it * 128);
                const uint32_t pa = bf2_mul(xa.x, wa.x), pb = bf2_mul(xa.y, wa.y);
                gs += (bf_lo(pa) + bf_hi(pa)) + (bf_lo(pb) + bf_hi(pb));
                if (it == again) {
                    mbar_wait(bar_c, 0);
                    const uint2 fin = lds64(role_s);
                    role = fin.x & 63;
                    if (__shfl_sync(0xffffffffu, fin.x != fin.y, 0)) { it = -1; again = 16; gs = 0.f; }
                }
            }
        }
        role = __shfl_sync(0xffffffffu, role, 0);
        ROLE_VARS();
        {
            tag = lds32(tag_s);
#pragma unroll
            for (int o = 8; o > 0; o >>= 1) gs += __shfl_xor_sync(0xffffffffu, gs, o);
            const float g = bf16_round(__frcp_rn(1.0f + expf(-bf16_round(gs))));
            if ((lane & 15) == 0) st_relaxed64(&p.s->gate[c * 256 + (lane >> 4) + 64 * w + 4 * cb + 2 * wg], __float_as_uint(g), tag);
        }
        const uint32_t tab_s = sbase + kTabOff + tid * 16;
        const float4 k0 = lds128f(tab_s);
        TILE_END();
        STAMPA(tid == 0, 2);
#pragma unroll
        for (int s = 0; s < 64; ++s) pk[s] = pack_bf16_v(acc[4 * (s >> 1) + (s & 1)], acc[4 * (s >> 1) + 2 + (s & 1)]);
#pragma unroll
        for (int i = 0; i < 96; ++i) UNDEF_F(acc[i]);

        const float lr = k0.x, li = k0.y, m00 = k0.z, m01 = k0.w;
        float m10, m11, hr = 0.f, hi = 0.f;
        uint32_t gg[4], orr[4], oii[4];
        const int ch = cb * 64 + warp * 8 + r;
        __nv_bfloat16* hs = p.s->Hs + (size_t)ch * 2048 + c * 256 + q * 8;
#define PASS2(KB)                                                                                      \
    _Pragma("unroll") for (int s = 0; s < 64; s += 2) {                                                \
        if (pass2_kb(s) != (KB)) continue;                                                             \
        if ((s & 7) == 0) {                                                                            \
            const uint4 ga = lds128(gate_s + (q * 72 + s) * 2);                                        \
            gg[0] = ga.x; gg[1] = ga.y; gg[2] = ga.z; gg[3] = ga.w;                                    \
        }                                                                                              \
        float o0[2], o1[2];                                                                            \
        _Pragma("unroll") for (int k = 0; k < 2; ++k) {                                                \
            PIN_R(pk[s + k]);                                                                          \
            float nr = bf_lo(pk[s + k]), ni = bf_hi(pk[s + k]);                                        \
            CFMA(nr, ni, lr, li, hr, hi);                                                              \
            hr = nr; hi = ni;                                                                          \
            o0[k] = fmaf(m00, hr, m01 * hi);                                                           \
            o1[k] = fmaf(m10, hr, m11 * hi);                                                           \
        }                                                                                              \
        orr[(s >> 1) & 3] = bf2_mul(pack_bf16(o0[0], o0[1]), gg[(s >> 1) & 3]);                        \
        oii[(s >> 1) & 3] = bf2_mul(pack_bf16(o1[0], o1[1]), gg[(s >> 1) & 3]);                        \
        if ((s & 7) == 6) {                                                                            \
            stg128(hs + 32 * (s >> 3), orr[0], orr[1], orr[2], orr[3]);                                \
            stg128(hs + 1024 * 2048 + 32 * (s >> 3), oii[0], oii[1], oii[2], oii[3]);                  \
        }                                                                                              \
    }                                                                                                  \
    PIN_F(hr); PIN_F(hi);
        {
            uint4 av0, av1, gv;
            float lqr, lqi;
#pragma unroll
            for (int kb = 0; kb < 16; ++kb) {
                PIN_R(a_lo);
                KBLOCK(1, 16 + kb, kb == 0, kb == 15);
                if (kb < 4) {
#pragma unroll
                    for (int s = kb * 16; s < kb * 16 + 16; ++s) {
                        float nr = bf_lo(pk[s]), ni = bf_hi(pk[s]);
                        CFMA(nr, ni, lr, li, hr, hi);
                        hr = nr; hi = ni;
                    }
                    PIN_F(hr); PIN_F(hi);
                }
                if (kb == 2) gv = ld_relaxed2x64(&p.s->gate[c * 256 + 2 * tw]);
                if (kb == 3) {
                    const float4 k1 = lds128f(tab_s + 4096), k2 = lds128f(tab_s + 8192);
                    m10 = k1.x; m11 = k1.y; lqr = k2.z; lqi = k2.w;
                    float tr = __shfl_up_sync(0xffffffffu, hr, 1, 4), ti = __shfl_up_sync(0xffffffffu, hi, 1, 4);
                    if (q >= 1) CFMA(hr, hi, k1.z, k1.w, tr, ti);
                    tr = __shfl_up_sync(0xffffffffu, hr, 2, 4); ti = __shfl_up_sync(0xffffffffu, hi, 2, 4);
                    if (q >= 2) CFMA(hr, hi, k2.x, k2.y, tr, ti);
                    if (q == 3) st_relaxed2x64(&p.s->agg[c * 1024 + ch], __float_as_uint(hr), tag, __float_as_uint(hi), tag);
                    tr = __shfl_up_sync(0xffffffffu, hr, 1, 4); ti = __shfl_up_sync(0xffffffffu, hi, 1, 4);
                    hr = (q >= 1) ? tr : 0.f; hi = (q >= 1) ? ti : 0.f;
                }
                if (kb == 4) {
                    unsigned spins = 0;
                    while (__any_sync(0xffffffffu, gv.y != tag || gv.w != tag)) {
                        if (++spins > kSpinLimit) break;
                        gv = ld_relaxed2x64(&p.s->gate[c * 256 + 2 * tw]);
                    }
                    sts32(gate_s + ((tw >> 5) * 72 + 2 * lane) * 2, __byte_perm(gv.x, gv.z, 0x7632));
                }
                if (kb == 5) {
                    av0 = make_uint4(0, tag, 0, tag); av1 = av0;
                    if (q < c) av0 = ld_relaxed2x64(&p.s->agg[q * 1024 + ch]);
                    if (q + 4 < c) av1 = ld_relaxed2x64(&p.s->agg[(q + 4) * 1024 + ch]);
                    bar_sync(1 + wg, 128);
                }
                if (kb == 6) {
                    const float4 k3 = lds128f(tab_s + 12288);
                    unsigned spins = 0;
                    while (__any_sync(0xffffffffu, av0.y != tag || av0.w != tag || av1.y != tag || av1.w != tag)) {
                        if (++spins > kSpinLimit) break;
                        if (q < c) av0 = ld_relaxed2x64(&p.s->agg[q * 1024 + ch]);
                        if (q + 4 < c) av1 = ld_relaxed2x64(&p.s->agg[(q + 4) * 1024 + ch]);
                    }
                    float vr, vi;
                    CMUL(vr, vi, k3.x, k3.y, __uint_as_float(av0.x), __uint_as_float(av0.z));
                    CFMA(vr, vi, k3.z, k3.w, __uint_as_float(av1.x), __uint_as_float(av1.z));
                    vr += __shfl_xor_sync(0xffffffffu, vr, 1); vi += __shfl_xor_sync(0xffffffffu, vi, 1);
                    vr += __shfl_xor_sync(0xffffffffu, vr, 2); vi += __shfl_xor_sync(0xffffffffu, vi, 2);
                    CFMA(hr, hi, lqr, lqi, vr, vi);
                }
                if (kb >= 6) { PASS2(kb); }
            }
            TILE_END();
        }
        STAMPA(tid == 0, 3);
#pragma unroll
        for (int i = 0; i < 48; ++i) pk[i] = pack_bf16_v(acc[2 * i], acc[2 * i + 1]);
#pragma unroll
        for (int i = 0; i < 128; ++i) UNDEF_F(acc[i]);

        PIN_R(a_lo);
        KBLOCK(2, 32, true, false);
        PASS2(16);
        PIN_R(a_lo);
        KBLOCK(2, 33, false, false);
        PASS2(17);
        bar_arrive(3, 288);
        const uint32_t gate_row = gate_s + ((2 * (w & 1)) * 72 + 8 * (4 * rank + 2 * wg + (w >> 1)) + r) * 2;
        uint32_t om0, om1;
        {
            const float a = 1.0f - bf_lo(lds16(gate_row)), b = 1.0f - bf_lo(lds16(gate_row + 72 * 2));
            om0 = pack_bf16(a, a); om1 = pack_bf16(b, b);
        }
        __nv_bfloat16* hf = p.s->Hf + (size_t)(rb * 128 + wg * 64 + w * 16 + r) * kF + q * 8 + 2048 + 192 * j8;
        uint32_t bias_s = sbase + kBiasOff + q * 16;
#define FFN_SLICE(J)                                                                                   \
    {                                                                                                  \
        const uint4 bv = lds128(bias_s + (J) * 64);                                                    \
        const uint32_t bb[4] = {bv.x, bv.y, bv.z, bv.w};                                               \
        _Pragma("unroll") for (int jj = 0; jj < 4; ++jj) {                                             \
            const uint32_t r0 = bf2_add_relu(pk[8 * (J) + 2 * jj], bb[jj]), r1 = bf2_add_relu(pk[8 * (J) + 2 * jj + 1], bb[jj]); \
            pk[8 * (J) + 2 * jj] = bf2_mul(bf2_mul(r0, r0), om0);                                      \
            pk[8 * (J) + 2 * jj + 1] = bf2_mul(bf2_mul(r1, r1), om1);                                  \
        }                                                                                              \
        stg128(hf + 32 * (J), pk[8 * (J)], pk[8 * (J) + 2], pk[8 * (J) + 4], pk[8 * (J) + 6]);         \
        stg128(hf + 8 * kF + 32 * (J), pk[8 * (J) + 1], pk[8 * (J) + 3], pk[8 * (J) + 5], pk[8 * (J) + 7]); \
    }
        const uint32_t x_s = sbase + kXOff + (wg * 64 + w * 16 + (lane & 15)) * 128 + (((lane >> 4) ^ (lane & 7)) << 4);
        {
            uint32_t j = 0, nsl = 6;
#pragma unroll 1
            for (uint32_t it = 34; it < 88; ++it, ++j) {
                const uint32_t so = (it & 3) * (kStageBytes >> 4);
                if (wg == 1 && (it == 86 || (ORDER && it == 47))) bar_sync(7, 256);
                KB_OPEN(it, false);
                if ((it & ~15u) == 48) {
                    wgmma_fence();
                    mma_kblock<3>(acc, a_lo + so, b_lo + so, it != 48);
                    wgmma_commit();
                } else {
                    wgmma_fence();
                    mma_kblock<2>(acc, a_lo + so, b_lo + so, 1);
                    wgmma_commit();
                }
                if (wg == 0 && (it == 87 || (ORDER && it == 47))) bar_arrive(7, 256);
                KB_CLOSE(it, false, it != 48);
                if (j < nsl) {
                    if (j & 4) {
                        if (j & 2) { if (j & 1) FFN_SLICE(7) else FFN_SLICE(6) } else { if (j & 1) FFN_SLICE(5) else FFN_SLICE(4) }
                    } else {
                        if (j & 2) { if (j & 1) FFN_SLICE(3) else FFN_SLICE(2) } else { if (j & 1) FFN_SLICE(1) else FFN_SLICE(0) }
                    }
                    if (j + 1 == nsl) bar_arrive(1 + (nsl >> 1), 288);
                } else if (it == 47) {
                    hf += 64 * j8 - 2048;
                    bias_s += 6 * 64;
                    j = -1; nsl = 8;
                    TILE_END();
                    STAMPA(tid == 0, 4);
#pragma unroll
                    for (int i = 0; i < 64; ++i) pk[i] = pack_bf16_v(acc[2 * i], acc[2 * i + 1]);
                } else if ((it >> 2) == ETKB / 4) {
                    mbar_wait(bar_x, 1);
                    const uint32_t xa_s = (x_s ^ ((it & 1) << 6)) + (it & 2) * 8192;
                    const float g0 = bf_lo(lds16(gate_row)), g1 = bf_lo(lds16(gate_row + 72 * 2));
                    const float o0f = bf_lo(om0), o1f = bf_lo(om1);
                    const uint4 dq = lds128(bias_s + (8 + (it & 3)) * 64), bq = lds128(bias_s + (12 + (it & 3)) * 64);
                    const uint4 xa = ldsm4(xa_s), xb = ldsm4(xa_s ^ 32);
                    const uint32_t dv[4] = {dq.x, dq.y, dq.z, dq.w}, bv2[4] = {bq.x, bq.y, bq.z, bq.w};
                    uint32_t xv[8] = {xa.x, xa.y, xa.z, xa.w, xb.x, xb.y, xb.z, xb.w};
#pragma unroll
                    for (int jj = 0; jj < 4; ++jj) {
                        const uint32_t x0 = bf2_mul(xv[2 * jj], dv[jj]), x1 = bf2_mul(xv[2 * jj + 1], dv[jj]);
                        const float bl = bf_lo(bv2[jj]), bh = bf_hi(bv2[jj]);
                        xv[2 * jj] = pack_bf16(fmaf(g0, bf_lo(x0), o0f * bl), fmaf(g0, bf_hi(x0), o0f * bh));
                        xv[2 * jj + 1] = pack_bf16(fmaf(g1, bf_lo(x1), o1f * bl), fmaf(g1, bf_hi(x1), o1f * bh));
                    }
                    sts128(xa_s, xv[0], xv[1], xv[2], xv[3]);
                    sts128(xa_s ^ 32, xv[4], xv[5], xv[6], xv[7]);
                }
            }
        }
#define OWN_MMA(H)                                                                                     \
    wgmma_fence();                                                                                     \
    _Pragma("unroll") for (int i = 0; i < 16; ++i)                                                     \
        wgmma_n64_rs<32 * (H)>(acc, pk[4 * i], pk[4 * i + 1], pk[4 * i + 2], pk[4 * i + 3],            \
                               kDescHi | (uint64_t)(b_lo + ((2 * (H) * kStageBytes + i * 2048) >> 4) + (256u << 16))); \
    wgmma_commit();
#define OTHER_MMA(H, P)                                                                                \
    PIN_R(a_lo);                                                                                       \
    wgmma_fence();                                                                                     \
    _Pragma("unroll") for (int i = 0; i < 8; ++i)                                                      \
        wgmma_n64<0, 1, 32 * (H)>(acc, kDescHi | (uint64_t)(a_lo + (((P) * kStageBytes + (i >> 2) * 8192 + (i & 3) * 32) >> 4) + (1u << 16)), \
                               kDescHi | (uint64_t)(b_lo + (((2 * (H) + 1) * kStageBytes + (8 * (P) + i) * 2048) >> 4) + (256u << 16)), 1); \
    wgmma_commit();
#define LOAD_E(H) _Pragma("unroll") for (int u = 0; u < 4; ++u) ev[u] = lds128((x_s ^ (u << 5)) + (H) * 16384);
#define RXLOAD(H)                                                                                      \
    {                                                                                                  \
        if ((H) == 0) rs = ld_relaxed32((const unsigned*)(xi + 32768 - tid * 12));                     \
        _Pragma("unroll") for (int u = 0; u < 4; ++u) rx[u] = ld_relaxed2x64(xi + (4 * (H) + u) * 4096); \
    }
#define RXCHECK(H)                                                                                     \
    {                                                                                                  \
        unsigned spins = 0;                                                                            \
        _Pragma("unroll 1") while (true) {                                                             \
            uint32_t ok = rs != 0;                                                                     \
            _Pragma("unroll") for (int u = 0; u < 4; ++u) ok &= rx[u].x & rx[u].z;                     \
            if (__all_sync(0xffffffffu, ok) || ++spins > kSpinLimit) break;                            \
            RXLOAD(H);                                                                                 \
            RESPIN();                                                                                  \
        }                                                                                              \
    }
#define SUM(H)                                                                                         \
    _Pragma("unroll") for (int u = 0; u < 4; ++u) {                                                    \
        const uint32_t rr[4] = {rx[u].x, rx[u].y, rx[u].z, rx[u].w}, ee[4] = {ev[u].x, ev[u].y, ev[u].z, ev[u].w}; \
        _Pragma("unroll") for (int k = 0; k < 4; ++k) {                                                \
            const float2 f = __half22float2(*reinterpret_cast<const __half2*>(&rr[k]));                \
            ex[8 * u + 2 * k] = (H) ? f.x : fmaf(f.x, xsc, bf_lo(ee[k]));                              \
            ex[8 * u + 2 * k + 1] = (H) ? f.y : fmaf(f.y, xsc, bf_hi(ee[k]));                          \
            PIN_F(ex[8 * u + 2 * k]); PIN_F(ex[8 * u + 2 * k + 1]);                                    \
        }                                                                                              \
    }
#define PUT(H)                                                                                         \
    _Pragma("unroll") for (int uh = 0; uh < 8; ++uh) {                                                 \
        const int ea = 4 * (uh & 6) + 2 * (uh & 1), va = 32 * (H) + ea, vb = va + 4;                   \
        const float mul = (H) ? xsc : 1.0f;                                                            \
        PIN_F(acc[va]); PIN_F(acc[va + 1]); PIN_F(acc[vb]); PIN_F(acc[vb + 1]);                        \
        const float a0 = fmaf(ex[ea], mul, acc[va]), a1 = fmaf(ex[ea + 1], mul, acc[va + 1]);          \
        const float b0 = fmaf(ex[ea + 4], mul, acc[vb]), b1 = fmaf(ex[ea + 5], mul, acc[vb + 1]);      \
        const float t0 = __shfl_xor_sync(0xffffffffu, odd ? a0 : b0, 1), t1 = __shfl_xor_sync(0xffffffffu, odd ? a1 : b1, 1); \
        stg128f(o0 + (uh & 1) * 64 * kD + 64 * (H) + 8 * (uh & 6), odd ? t0 : a0, odd ? t1 : a1, odd ? b0 : t0, odd ? b1 : t1); \
    }
        TILE_END();
        sched_fence(a_lo);
        {
            const uint8_t* xi = p.s->X + (size_t)(role * 2 + rank) * kXBytes + tid * 16;
            uint8_t* xo = const_cast<uint8_t*>(xi) + (kh ? -8 * kXBytes : 8 * kXBytes);
            uint4 rx[4], ev[4];
            uint32_t rs;
            float ex[32];
            {
                STAMP(tid == 0, 15); STAMPB(tid == 128, 1);
                float m[4] = {0.f, 0.f, 0.f, 0.f};
#pragma unroll
                for (int i = 64; i < 128; ++i) m[i & 3] = fmaxf(m[i & 3], fabsf(acc[i]));
                const uint32_t eb = max(__float_as_uint(fmaxf(fmaxf(m[0], m[1]), fmaxf(m[2], m[3]))) >> 23, 15u);
                const float xsc = __uint_as_float((268u - eb) << 23);
                st_relaxed32(xo + 32768 - tid * 12, (eb - 14u) << 23);
#pragma unroll
                for (int u = 0; u < 8; ++u) {
                    const int v = 64 + 8 * u;
                    st_relaxed2x64(xo + u * 4096, pack_f16(acc[v] * xsc, acc[v + 1] * xsc) | 1, pack_f16(acc[v + 2] * xsc, acc[v + 3] * xsc),
                                   pack_f16(acc[v + 4] * xsc, acc[v + 5] * xsc) | 1, pack_f16(acc[v + 6] * xsc, acc[v + 7] * xsc));
                }
                STAMP(tid == 0, 12); STAMPB(tid == 128, 2);
            }
            LOAD_E(1);
            a_lo += wg * ((2 * kStageBytes - 8192) >> 4);
            mbar_wait(bar_full, 0);
            if (wg == 1) bar_sync(9, 256);
            STAMPB(tid == 128, 3);
            OWN_MMA(0);
            sched_fence(a_lo);
            STAMPB(tid == 0, 9);
            RXLOAD(0);
#pragma unroll
            for (int u = 0; u < 4; ++u) {
                const uint32_t ee[4] = {ev[u].x, ev[u].y, ev[u].z, ev[u].w};
#pragma unroll
                for (int k = 0; k < 4; ++k) {
                    const int v = 32 + 8 * u + 2 * k;
                    acc[v] += bf_lo(ee[k]); acc[v + 1] += bf_hi(ee[k]);
                    PIN_F(acc[v]); PIN_F(acc[v + 1]);
                }
            }
            LOAD_E(0);
            mbar_wait(bar_full + 8, 0);
            mbar_wait(bar_full + 16 * wg, 0);
            OTHER_MMA(0, 0);
            mbar_wait(bar_full + 8 + 16 * wg, 0);
            OTHER_MMA(0, 1);
            bar_arrive(9 - wg, 256);
            sched_fence(a_lo);
            STAMPB(tid == 0, 10);
            const bool odd = q & 1;
            const int tb = c * 256 + 128 * (w & 1) + 8 * (4 * rank + 2 * wg + (w >> 1));
            float* o0 = p.out + (size_t)(tb + r) * kD + colK + (odd ? 2 * q + 6 : 2 * q);
            RXCHECK(0);
            STAMP(tid == 0, 13);
            const float xsc = __uint_as_float(rs);
            SUM(0);
            sched_fence(a_lo);
            wgmma_wait<0>();
            STAMPB(tid == 0, 11); STAMPB(tid == 128, 8);
            PUT(0);
            STAMP(tid == 0, 14);
            mbar_wait(bar_full + 16, 0);
            mbar_wait(bar_full + 24, 0);
            bar_sync(8 + 2 * wg, 256);
            OWN_MMA(1);
            sched_fence(a_lo);
            RXLOAD(1);
            sched_fence(a_lo);
            OTHER_MMA(1, 0);
            OTHER_MMA(1, 1);
            if (wg == 0) bar_arrive(10, 256);
            sched_fence(a_lo);
            RXCHECK(1);
            SUM(1);
            sched_fence(a_lo);
            wgmma_wait<0>();
            STAMP(tid == 0, 6); STAMPB(tid == 128, 4);
            PUT(1);
        }
        STAMP(tid == 0, 7);
        STAMP(tid == 128, 5);
    }
}

typedef CUresult (*EncodeFn)(CUtensorMap*, CUtensorMapDataType, cuuint32_t, void*, const cuuint64_t*, const cuuint64_t*,
                             const cuuint32_t*, const cuuint32_t*, CUtensorMapInterleave, CUtensorMapSwizzle,
                             CUtensorMapL2promotion, CUtensorMapFloatOOBfill);

bool encode(EncodeFn fn, CUtensorMap* m, const void* base, int rank, const cuuint64_t* dims, const cuuint64_t* strides,
            const cuuint32_t* box) {
    cuuint32_t es[5] = {1, 1, 1, 1, 1};
    return fn(m, CU_TENSOR_MAP_DATA_TYPE_BFLOAT16, rank, const_cast<void*>(base), dims, strides, box, es,
              CU_TENSOR_MAP_INTERLEAVE_NONE, CU_TENSOR_MAP_SWIZZLE_128B, CU_TENSOR_MAP_L2_PROMOTION_L2_256B,
              CU_TENSOR_MAP_FLOAT_OOB_FILL_NONE) == CUDA_SUCCESS;
}

}

extern "C" void kernel_launch(void* const* d_in, const int* in_sizes, int n_in, void* d_out, int out_size) {
    (void)in_sizes; (void)n_in; (void)out_size;
    typedef const __nv_bfloat16* bp;
    bp x = (bp)d_in[0], lam_re = (bp)d_in[1], lam_im = (bp)d_in[2], B_re = (bp)d_in[3], B_im = (bp)d_in[4];
    bp C_re = (bp)d_in[5], C_im = (bp)d_in[6], log_dt = (bp)d_in[7], dskip = (bp)d_in[8];
    bp w1 = (bp)d_in[10], b1 = (bp)d_in[11], w2 = (bp)d_in[12], b2 = (bp)d_in[13], gate_w = (bp)d_in[14];

    static EncodeFn fn = nullptr;
    static Scratch* ps = nullptr;
    if (!fn) {
        void* f = nullptr;
        cudaDriverEntryPointQueryResult qr;
        cudaGetDriverEntryPoint("cuTensorMapEncodeTiled", &f, cudaEnableDefault, &qr);
        fn = (EncodeFn)f;
        cudaGetSymbolAddress((void**)&ps, g_s);
        cudaFuncSetAttribute(fused_kernel, cudaFuncAttributeMaxDynamicSharedMemorySize, kSmemBytes);
    }
    cudaStream_t stream = cudaStreamPerThread;

    Params p;
    p.x = x; p.lam_re = lam_re; p.lam_im = lam_im; p.log_dt = log_dt; p.dskip = dskip; p.b1 = b1; p.b2 = b2;
    p.gate_w = gate_w; p.b_re = B_re; p.b_im = B_im; p.out = (float*)d_out; p.s = ps;
    char* const pHs = (char*)ps + offsetof(Scratch, Hs);
    char* const pHf = (char*)ps + offsetof(Scratch, Hf);
    char* const pBc = (char*)ps + offsetof(Scratch, Bcopy);

    const char* lo = (const char*)B_re; const char* hi = (const char*)B_im;
    p.swap = 0;
    if (hi < lo) { const char* t = lo; lo = hi; hi = t; p.swap = 1; }
    unsigned long long diff = (unsigned long long)(hi - lo);
    if (diff >= (1ull << 40) || (diff & 15) || diff == 0) {
        cudaMemcpyAsync(pBc, B_re, 2u << 20, cudaMemcpyDeviceToDevice, stream);
        cudaMemcpyAsync((char*)pBc + (2u << 20), B_im, 2u << 20, cudaMemcpyDeviceToDevice, stream);
        lo = (const char*)pBc; diff = 2u << 20; p.swap = 0;
    }

    CUtensorMap mB, mXs, mXf, mW1a, mW1b, mHs, mHf, mCre, mCim, mW2, mW2n, mW2p, mHf3;
    bool ok = true;
    { cuuint64_t d[4] = {1024, 8, 2, 128}, s[3] = {2048, diff, 16384}; cuuint32_t b[4] = {64, 8, 2, 8};
      ok &= encode(fn, &mB, lo, 4, d, s, b); }
    { cuuint64_t d[5] = {1024, 2, 4, 32, 8}, s[4] = {2048, 64 * 2048, 2 * 2048, 256 * 2048}; cuuint32_t b[5] = {64, 2, 4, 16, 1};
      ok &= encode(fn, &mXs, x, 5, d, s, b); }
    { cuuint64_t d[5] = {1024, 8, 4, 8, 8}, s[4] = {2048, 64 * 2048, 8 * 2048, 256 * 2048}; cuuint32_t b[5] = {64, 8, 4, 4, 1};
      ok &= encode(fn, &mXf, x, 5, d, s, b); }
    { cuuint64_t d[3] = {64, 1024, 56}, s[2] = {7168, 128}; cuuint32_t ba[3] = {64, 32, 4}, bb[3] = {64, 32, 3};
      ok &= encode(fn, &mW1a, w1, 3, d, s, ba); ok &= encode(fn, &mW1b, w1, 3, d, s, bb); }
    { cuuint64_t d[3] = {64, 2048, 32}, s[2] = {4096, 128}; cuuint32_t b[3] = {64, 64, 2};
      ok &= encode(fn, &mHs, pHs, 3, d, s, b); }
    { cuuint64_t d[2] = {3584, 2048}, s[1] = {7168}; cuuint32_t b[2] = {64, 128};
      ok &= encode(fn, &mHf, pHf, 2, d, s, b); }
    { cuuint64_t d[2] = {1024, 1024}, s[1] = {2048}; cuuint32_t b[2] = {64, 128};
      ok &= encode(fn, &mCre, C_re, 2, d, s, b); ok &= encode(fn, &mCim, C_im, 2, d, s, b); }
    { cuuint64_t d[5] = {64, 2, 448, 4, 16}, s[4] = {2048, 8 * 2048, 2 * 2048, 128}; cuuint32_t b[5] = {64, 2, 4, 4, 2};
      ok &= encode(fn, &mW2, w2, 5, d, s, b); }
    { cuuint64_t d[2] = {1024, 3584}, s[1] = {2048}; cuuint32_t b[2] = {64, 128};
      ok &= encode(fn, &mW2n, w2, 2, d, s, b); }
    { cuuint64_t d[5] = {1024, 2, 4, 4, 112}, s[4] = {2048, 8 * 2048, 2 * 2048, 32 * 2048}; cuuint32_t b[5] = {64, 2, 4, 4, 4};
      ok &= encode(fn, &mW2p, w2, 5, d, s, b); }
    { cuuint64_t d[3] = {64, 2048, 56}, s[2] = {7168, 128}; cuuint32_t b[3] = {64, 64, 2};
      ok &= encode(fn, &mHf3, pHf, 3, d, s, b); }
    if (!ok) return;

    fused_kernel<<<128, 384, kSmemBytes, stream>>>(mB, mXs, mXf, mW1b, mW1a, mHs, mHf, mCre, mCim, mW2, mW2n, mW2p, mHf3, p);
}
```

```cpp
#include <cuda_runtime.h>
#include <cuda_bf16.h>
#include <cuda_fp16.h>
#include <cuda.h>
#include <stdint.h>
#include <stddef.h>

#define XLDKB 40
#define PF0LINES 1
#define ETKB 60
#define PFKB 80
#define SKEW 3
#define MC0 0
#define PFTOP 0
#define INITW 0
#define PRODCOND warp >= 8
#define ORDER 0

namespace {

constexpr int kD = 1024, kF = 3584;
constexpr int kStages = 4;
constexpr int kStageBytes = 49152;
constexpr int kABytes = 16384;
constexpr int kXOff = kStages * kStageBytes;
constexpr int kTabOff = kXOff + 2048;
constexpr int kGateOff = kXOff + 32768;
constexpr int kBiasOff = kGateOff + 4 * 72 * 2;
constexpr int kBarOff = kBiasOff + 88 * 16;
constexpr int kSmemBytes = 232448;
static_assert(kBarOff + 160 <= kSmemBytes, "smem");
constexpr int kXBytes = 33792;
constexpr uint32_t kSmemOrg = 1024;
constexpr unsigned kSpinLimit = 1u << 18;
constexpr int kTotal = 92;

__host__ __device__ constexpr int pass2_kb(int s) {
    return s < 2 ? 6 : s < 8 ? 7 : s < 12 ? 8 : s < 18 ? 9 : s < 22 ? 10 : s < 28 ? 11 : s < 32 ? 12 : s < 38 ? 13 : s < 42 ? 14 : s < 48 ? 15 : s < 56 ? 16 : 17;
}

struct Scratch {
    unsigned claim[64];
    unsigned epoch, pad0[31];
    unsigned done, pad1[31];
    unsigned cnt[40 * 32];
    uint2 gate[2048];
    uint4 agg[8 * 1024];
    __align__(1024) uint8_t X[128 * kXBytes];
    __align__(1024) __nv_bfloat16 Hs[2048 * 2048];
    __align__(1024) __nv_bfloat16 Hf[2048 * 3584];
    __align__(1024) __nv_bfloat16 Bcopy[2 * 1024 * 1024];
};
__device__ Scratch g_s;

#define TRAP() break
#define PIN_F(x) asm volatile("" : "+f"(x))
#define PIN_R(x) asm volatile("" : "+r"(x))
#define UNDEF_F(x) asm volatile("" : "=f"(x))
#define UNDEF_R(x) asm volatile("" : "=r"(x))
#define RESPIN()
__device__ __forceinline__ uint32_t smem_u32(const void* p) { return (uint32_t)__cvta_generic_to_shared(p); }
__device__ __forceinline__ void mbar_init(uint32_t bar, uint32_t count) {
    asm volatile("mbarrier.init.shared::cta.b64 [%0], %1;" ::"r"(bar), "r"(count) : "memory");
}
__device__ __forceinline__ void mbar_expect_tx(uint32_t bar, uint32_t bytes) {
    asm volatile("mbarrier.arrive.expect_tx.shared::cta.b64 _, [%0], %1;" ::"r"(bar), "r"(bytes) : "memory");
}
__device__ __forceinline__ void mbar_wait(uint32_t bar, uint32_t parity) {
    asm volatile(
        "{\n.reg .pred p;\n.reg .u32 n;\n"
        "mbarrier.try_wait.parity.shared::cta.b64 p, [%0], %1;\n"
        "@p bra DONE;\n"
        "mov.u32 n, 0;\n"
        "LOOP:\n"
        "mbarrier.try_wait.parity.shared::cta.b64 p, [%0], %1;\n"
        "@p bra DONE;\n"
        "add.u32 n, n, 1;\n"
        "setp.lt.u32 p, n, %2;\n"
        "@p bra LOOP;\n"
        "DONE:\n}\n"
        ::"r"(bar), "r"(parity), "n"(kSpinLimit) : "memory");
}
__device__ __forceinline__ void sched_fence(uint32_t nonzero) {
    asm volatile("{\n.reg .pred p;\n.reg .u32 n;\nsetp.ne.u32 p, %0, 0;\n@p bra DONE;\nLOOP:\nmov.u32 n, %%clock;\n"
                 "setp.eq.u32 p, n, 0;\n@p bra LOOP;\nDONE:\n}\n" ::"r"(nonzero) : "memory");
}
__device__ __forceinline__ void mbar_arrive_local(uint32_t bar) {
    asm volatile("mbarrier.arrive.shared::cta.b64 _, [%0];" ::"r"(bar) : "memory");
}
__device__ __forceinline__ void mbar_arrive_cluster(uint32_t cluster_addr) {
    asm volatile("mbarrier.arrive.shared::cluster.b64 _, [%0];" ::"r"(cluster_addr) : "memory");
}
__device__ __forceinline__ uint32_t mapa(uint32_t addr, uint32_t rank) {
    uint32_t r;
    asm("mapa.shared::cluster.u32 %0, %1, %2;" : "=r"(r) : "r"(addr), "r"(rank));
    return r;
}
__device__ __forceinline__ void cluster_arrive() { asm volatile("barrier.cluster.arrive.relaxed.aligned;" ::: "memory"); }
__device__ __forceinline__ void cluster_wait() { asm volatile("barrier.cluster.wait.acquire.aligned;" ::: "memory"); }
__device__ __forceinline__ void bar_sync(int id, int n) { asm volatile("bar.sync %0, %1;" ::"r"(id), "r"(n) : "memory"); }
__device__ __forceinline__ void bar_arrive(int id, int n) { asm volatile("bar.arrive %0, %1;" ::"r"(id), "r"(n) : "memory"); }
__device__ __forceinline__ bool elect_one() {
    uint32_t p;
    asm volatile("{\n.reg .pred P;\nelect.sync _|P, 0xffffffff;\nselp.u32 %0, 1, 0, P;\n}\n" : "=r"(p));
    return p != 0;
}

__device__ __forceinline__ void tma2(uint32_t dst, const CUtensorMap* m, uint32_t bar, int c0, int c1) {
    asm volatile("cp.async.bulk.tensor.2d.shared::cluster.global.mbarrier::complete_tx::bytes [%0], [%1, {%3, %4}], [%2];"
                 ::"r"(dst), "l"(m), "r"(bar), "r"(c0), "r"(c1) : "memory");
}
__device__ __forceinline__ void tma3(uint32_t dst, const CUtensorMap* m, uint32_t bar, int c0, int c1, int c2) {
    asm volatile("cp.async.bulk.tensor.3d.shared::cluster.global.mbarrier::complete_tx::bytes [%0], [%1, {%3, %4, %5}], [%2];"
                 ::"r"(dst), "l"(m), "r"(bar), "r"(c0), "r"(c1), "r"(c2) : "memory");
}
__device__ __forceinline__ void tma4(uint32_t dst, const CUtensorMap* m, uint32_t bar, int c0, int c1, int c2, int c3) {
    asm volatile("cp.async.bulk.tensor.4d.shared::cluster.global.mbarrier::complete_tx::bytes [%0], [%1, {%3, %4, %5, %6}], [%2];"
                 ::"r"(dst), "l"(m), "r"(bar), "r"(c0), "r"(c1), "r"(c2), "r"(c3) : "memory");
}
__device__ __forceinline__ void tma5(uint32_t dst, const CUtensorMap* m, uint32_t bar, int c0, int c1, int c2, int c3, int c4) {
    asm volatile("cp.async.bulk.tensor.5d.shared::cluster.global.mbarrier::complete_tx::bytes [%0], [%1, {%3, %4, %5, %6, %7}], [%2];"
                 ::"r"(dst), "l"(m), "r"(bar), "r"(c0), "r"(c1), "r"(c2), "r"(c3), "r"(c4) : "memory");
}
__device__ __forceinline__ void tma2_mc(uint32_t dst, const CUtensorMap* m, uint32_t bar, int c0, int c1) {
    asm volatile("cp.async.bulk.tensor.2d.shared::cluster.global.mbarrier::complete_tx::bytes.multicast::cluster [%0], [%1, {%3, %4}], [%2], %5;"
                 ::"r"(dst), "l"(m), "r"(bar), "r"(c0), "r"(c1), "h"((uint16_t)3) : "memory");
}
__device__ __forceinline__ void tma3_mc(uint32_t dst, const CUtensorMap* m, uint32_t bar, int c0, int c1, int c2) {
    asm volatile("cp.async.bulk.tensor.3d.shared::cluster.global.mbarrier::complete_tx::bytes.multicast::cluster [%0], [%1, {%3, %4, %5}], [%2], %6;"
                 ::"r"(dst), "l"(m), "r"(bar), "r"(c0), "r"(c1), "r"(c2), "h"((uint16_t)3) : "memory");
}
__device__ __forceinline__ void tma5_mc(uint32_t dst, const CUtensorMap* m, uint32_t bar, int c0, int c1, int c2, int c3, int c4) {
    asm volatile("cp.async.bulk.tensor.5d.shared::cluster.global.mbarrier::complete_tx::bytes.multicast::cluster [%0], [%1, {%3, %4, %5, %6, %7}], [%2], %8;"
                 ::"r"(dst), "l"(m), "r"(bar), "r"(c0), "r"(c1), "r"(c2), "r"(c3), "r"(c4), "h"((uint16_t)3) : "memory");
}
__device__ __forceinline__ void tma2_pf(const CUtensorMap* m, int c0, int c1) {
    asm volatile("cp.async.bulk.prefetch.tensor.2d.L2.global [%0, {%1, %2}];" ::"l"(m), "r"(c0), "r"(c1) : "memory");
}
__device__ __forceinline__ void bulk_store(void* dst, uint32_t src, uint32_t bytes) {
    asm volatile("cp.async.bulk.global.shared::cta.bulk_group [%0], [%1], %2;" ::"l"(dst), "r"(src), "r"(bytes) : "memory");
}
__device__ __forceinline__ void bulk_load(uint32_t dst, const void* src, uint32_t bytes, uint32_t bar) {
    asm volatile("cp.async.bulk.shared::cluster.global.mbarrier::complete_tx::bytes [%0], [%1], %2, [%3];"
                 ::"r"(dst), "l"(src), "r"(bytes), "r"(bar) : "memory");
}
__device__ __forceinline__ unsigned atom_exch(unsigned* p, unsigned v) {
    unsigned r;
    asm volatile("atom.relaxed.gpu.global.exch.b32 %0, [%1], %2;" : "=r"(r) : "l"(p), "r"(v) : "memory");
    return r;
}
__device__ __forceinline__ void st_async32(uint32_t a, uint32_t v, uint32_t bar) {
    asm volatile("st.async.shared::cluster.mbarrier::complete_tx::bytes.u32 [%0], %1, [%2];" ::"r"(a), "r"(v), "r"(bar) : "memory");
}
__device__ __forceinline__ void sts128f(uint32_t a, float x, float y, float z, float w) {
    asm volatile("st.shared.v4.f32 [%0], {%1, %2, %3, %4};" ::"r"(a), "f"(x), "f"(y), "f"(z), "f"(w) : "memory");
}
__device__ __forceinline__ void prefetch_map(const CUtensorMap* m) {
    asm volatile("prefetch.tensormap [%0];" ::"l"(m) : "memory");
}

__device__ __forceinline__ void prefetch_l2(const void* p, uint32_t bytes) {
    asm volatile("cp.async.bulk.prefetch.L2.global [%0], %1;" ::"l"(p), "r"(bytes) : "memory");
}

__device__ __forceinline__ void wgmma_fence() { asm volatile("wgmma.fence.sync.aligned;" ::: "memory"); }
__device__ __forceinline__ void wgmma_commit() { asm volatile("wgmma.commit_group.sync.aligned;" ::: "memory"); }
template <int N>
__device__ __forceinline__ void wgmma_wait() { asm volatile("wgmma.wait_group.sync.aligned %0;" ::"n"(N) : "memory"); }

__device__ __forceinline__ uint32_t pack_bf16(float lo, float hi) {
    uint32_t r;
    asm("cvt.rn.bf16x2.f32 %0, %1, %2;" : "=r"(r) : "f"(hi), "f"(lo));
    return r;
}
__device__ __forceinline__ uint32_t pack_f16(float lo, float hi) {
    uint32_t r;
    asm("cvt.rn.f16x2.f32 %0, %1, %2;" : "=r"(r) : "f"(hi), "f"(lo));
    return r;
}
__device__ __forceinline__ uint32_t pack_bf16_v(float lo, float hi) {
    uint32_t r;
    asm volatile("cvt.rn.bf16x2.f32 %0, %1, %2;" : "=r"(r) : "f"(hi), "f"(lo));
    return r;
}
template <int LUT>
__device__ __forceinline__ uint32_t lop3(uint32_t a, uint32_t b, uint32_t c) {
    uint32_t r;
    asm("lop3.b32 %0, %1, %2, %3, %4;" : "=r"(r) : "r"(a), "r"(b), "r"(c), "n"(LUT));
    return r;
}
__device__ __forceinline__ float bf_lo(uint32_t v) { return __uint_as_float(v << 16); }
__device__ __forceinline__ float bf_hi(uint32_t v) { return __uint_as_float(v & 0xffff0000u); }
__device__ __forceinline__ float bf16_round(float v) { return __bfloat162float(__float2bfloat16_rn(v)); }
__device__ __forceinline__ uint32_t bf2_mul(uint32_t a, uint32_t b) {
    uint32_t r;
    asm("mul.rn.bf16x2 %0, %1, %2;" : "=r"(r) : "r"(a), "r"(b));
    return r;
}
__device__ __forceinline__ uint32_t bf2_add_relu(uint32_t a, uint32_t b) {
    uint32_t r;
    asm("fma.rn.relu.bf16x2 %0, %1, %2, %3;" : "=r"(r) : "r"(a), "r"(0x3f803f80u), "r"(b));
    return r;
}
__device__ __forceinline__ uint4 ldg128(const void* p) {
    uint4 v;
    asm volatile("ld.global.nc.v4.u32 {%0, %1, %2, %3}, [%4];" : "=r"(v.x), "=r"(v.y), "=r"(v.z), "=r"(v.w) : "l"(p));
    return v;
}
__device__ __forceinline__ uint32_t ldg32(const void* p) {
    uint32_t v;
    asm volatile("ld.global.nc.u32 %0, [%1];" : "=r"(v) : "l"(p));
    return v;
}
__device__ __forceinline__ uint32_t ldg32na(const void* p) {
    uint32_t v;
    asm volatile("ld.global.nc.L1::no_allocate.u32 %0, [%1];" : "=r"(v) : "l"(p));
    return v;
}
__device__ __forceinline__ uint32_t ldg16(const __nv_bfloat16* p) {
    uint32_t v;
    asm volatile("ld.global.nc.u16 %0, [%1];" : "=r"(v) : "l"(p));
    return v;
}
__device__ __forceinline__ uint4 ld_relaxed128(const void* p) {
    uint4 v;
    asm volatile("ld.relaxed.gpu.global.v4.u32 {%0, %1, %2, %3}, [%4];" : "=r"(v.x), "=r"(v.y), "=r"(v.z), "=r"(v.w) : "l"(p) : "memory");
    return v;
}
__device__ __forceinline__ uint2 ld_relaxed64(const void* p) {
    unsigned long long v;
    asm volatile("ld.relaxed.gpu.global.u64 %0, [%1];" : "=l"(v) : "l"(p) : "memory");
    return make_uint2((uint32_t)v, (uint32_t)(v >> 32));
}
__device__ __forceinline__ void st_relaxed64(void* p, uint32_t lo, uint32_t hi) {
    unsigned long long v = ((unsigned long long)hi << 32) | lo;
    asm volatile("st.relaxed.gpu.global.u64 [%0], %1;" ::"l"(p), "l"(v) : "memory");
}
__device__ __forceinline__ void st_relaxed2x64(void* p, uint32_t a, uint32_t b, uint32_t c, uint32_t d) {
    unsigned long long v0 = ((unsigned long long)b << 32) | a, v1 = ((unsigned long long)d << 32) | c;
    asm volatile("st.relaxed.gpu.global.v2.u64 [%0], {%1, %2};" ::"l"(p), "l"(v0), "l"(v1) : "memory");
}
__device__ __forceinline__ uint4 ld_relaxed2x64(const void* p) {
    unsigned long long v0, v1;
    asm volatile("ld.relaxed.gpu.global.v2.u64 {%0, %1}, [%2];" : "=l"(v0), "=l"(v1) : "l"(p) : "memory");
    return make_uint4((uint32_t)v0, (uint32_t)(v0 >> 32), (uint32_t)v1, (uint32_t)(v1 >> 32));
}
__device__ __forceinline__ void stg128(void* p, uint32_t a, uint32_t b, uint32_t c, uint32_t d) {
    asm volatile("st.global.v4.u32 [%0], {%1, %2, %3, %4};" ::"l"(p), "r"(a), "r"(b), "r"(c), "r"(d) : "memory");
}
__device__ __forceinline__ void stg64f(void* p, float a, float b) {
    asm volatile("st.global.v2.f32 [%0], {%1, %2};" ::"l"(p), "f"(a), "f"(b) : "memory");
}
__device__ __forceinline__ uint4 lds128(uint32_t a) {
    uint4 v;
    asm volatile("ld.shared.v4.u32 {%0, %1, %2, %3}, [%4];" : "=r"(v.x), "=r"(v.y), "=r"(v.z), "=r"(v.w) : "r"(a) : "memory");
    return v;
}
__device__ __forceinline__ uint2 lds64(uint32_t a) {
    uint2 v;
    asm volatile("ld.shared.v2.u32 {%0, %1}, [%2];" : "=r"(v.x), "=r"(v.y) : "r"(a) : "memory");
    return v;
}
__device__ __forceinline__ uint4 ldsm4(uint32_t a) {
    uint4 v;
    asm volatile("ldmatrix.sync.aligned.m8n8.x4.shared.b16 {%0, %1, %2, %3}, [%4];" : "=r"(v.x), "=r"(v.y), "=r"(v.z), "=r"(v.w) : "r"(a) : "memory");
    return v;
}
__device__ __forceinline__ uint32_t lds16(uint32_t a) {
    uint32_t v;
    asm volatile("ld.shared.u16 %0, [%1];" : "=r"(v) : "r"(a) : "memory");
    return v;
}
__device__ __forceinline__ void sts16(uint32_t a, uint32_t x) {
    asm volatile("st.shared.u16 [%0], %1;" ::"r"(a), "h"((uint16_t)x) : "memory");
}
__device__ __forceinline__ void st_relaxed32(void* p, uint32_t v) {
    asm volatile("st.relaxed.gpu.global.u32 [%0], %1;" ::"l"(p), "r"(v) : "memory");
}
__device__ __forceinline__ float lds32f(uint32_t a) {
    float v;
    asm volatile("ld.shared.f32 %0, [%1];" : "=f"(v) : "r"(a) : "memory");
    return v;
}
__device__ __forceinline__ void sts128(uint32_t a, uint32_t x, uint32_t y, uint32_t z, uint32_t w) {
    asm volatile("st.shared.v4.u32 [%0], {%1, %2, %3, %4};" ::"r"(a), "r"(x), "r"(y), "r"(z), "r"(w) : "memory");
}
__device__ __forceinline__ void sts64f(uint32_t a, float x, float y) {
    asm volatile("st.shared.v2.f32 [%0], {%1, %2};" ::"r"(a), "f"(x), "f"(y) : "memory");
}
__device__ __forceinline__ float4 lds128f(uint32_t a) {
    float4 v;
    asm volatile("ld.shared.v4.f32 {%0, %1, %2, %3}, [%4];" : "=f"(v.x), "=f"(v.y), "=f"(v.z), "=f"(v.w) : "r"(a) : "memory");
    return v;
}
__device__ __forceinline__ uint32_t lds32(uint32_t a) {
    uint32_t v;
    asm volatile("ld.shared.u32 %0, [%1];" : "=r"(v) : "r"(a) : "memory");
    return v;
}
__device__ __forceinline__ void sts32(uint32_t a, uint32_t x) {
    asm volatile("st.shared.u32 [%0], %1;" ::"r"(a), "r"(x) : "memory");
}
__device__ __forceinline__ void stg128f(void* p, float a, float b, float c, float d) {
    asm volatile("st.global.v4.f32 [%0], {%1, %2, %3, %4};" ::"l"(p), "f"(a), "f"(b), "f"(c), "f"(d) : "memory");
}
__device__ __forceinline__ unsigned ld_relaxed32(const unsigned* p) {
    unsigned v;
    asm volatile("ld.relaxed.gpu.global.u32 %0, [%1];" : "=r"(v) : "l"(p) : "memory");
    return v;
}
__device__ __forceinline__ void wait_counter(const unsigned* p, unsigned target) {
    unsigned n = 0, v;
    while (true) {
        asm volatile("ld.acquire.gpu.global.u32 %0, [%1];" : "=r"(v) : "l"(p) : "memory");
        if ((int)(v - target) >= 0) break;
        if (++n > kSpinLimit) TRAP();
        __nanosleep(32);
    }
}
#define KT(IT, W) do { } while (0)
#define STAMP(cond, slot) do { } while (0)
#define STAMPA(cond, slot) STAMP(cond, slot)
#define STAMPB(cond, slot) do { } while (0)

template <int TA, int TB>
__device__ __forceinline__ void wgmma_n256(float (&d)[128], uint64_t da, uint64_t db, int keep) {
    asm volatile(
        "{\n.reg .pred p;\nsetp.ne.b32 p, %132, 0;\n"
        "wgmma.mma_async.sync.aligned.m64n256k16.f32.bf16.bf16 "
        "{%0, %1, %2, %3, %4, %5, %6, %7, %8, %9, %10, %11, %12, %13, %14, %15, "
        "%16, %17, %18, %19, %20, %21, %22, %23, %24, %25, %26, %27, %28, %29, %30, %31, "
        "%32, %33, %34, %35, %36, %37, %38, %39, %40, %41, %42, %43, %44, %45, %46, %47, "
        "%48, %49, %50, %51, %52, %53, %54, %55, %56, %57, %58, %59, %60, %61, %62, %63, "
        "%64, %65, %66, %67, %68, %69, %70, %71, %72, %73, %74, %75, %76, %77, %78, %79, "
        "%80, %81, %82, %83, %84, %85, %86, %87, %88, %89, %90, %91, %92, %93, %94, %95, "
        "%96, %97, %98, %99, %100, %101, %102, %103, %104, %105, %106, %107, %108, %109, %110, %111, "
        "%112, %113, %114, %115, %116, %117, %118, %119, %120, %121, %122, %123, %124, %125, %126, %127}, "
        "%128, %129, p, 1, 1, %130, %131;\n}\n"
        : "+f"(d[0]), "+f"(d[1]), "+f"(d[2]), "+f"(d[3]), "+f"(d[4]), "+f"(d[5]), "+f"(d[6]), "+f"(d[7]),
          "+f"(d[8]), "+f"(d[9]), "+f"(d[10]), "+f"(d[11]), "+f"(d[12]), "+f"(d[13]), "+f"(d[14]), "+f"(d[15]),
          "+f"(d[16]), "+f"(d[17]), "+f"(d[18]), "+f"(d[19]), "+f"(d[20]), "+f"(d[21]), "+f"(d[22]), "+f"(d[23]),
          "+f"(d[24]), "+f"(d[25]), "+f"(d[26]), "+f"(d[27]), "+f"(d[28]), "+f"(d[29]), "+f"(d[30]), "+f"(d[31]),
          "+f"(d[32]), "+f"(d[33]), "+f"(d[34]), "+f"(d[35]), "+f"(d[36]), "+f"(d[37]), "+f"(d[38]), "+f"(d[39]),
          "+f"(d[40]), "+f"(d[41]), "+f"(d[42]), "+f"(d[43]), "+f"(d[44]), "+f"(d[45]), "+f"(d[46]), "+f"(d[47]),
          "+f"(d[48]), "+f"(d[49]), "+f"(d[50]), "+f"(d[51]), "+f"(d[52]), "+f"(d[53]), "+f"(d[54]), "+f"(d[55]),
          "+f"(d[56]), "+f"(d[57]), "+f"(d[58]), "+f"(d[59]), "+f"(d[60]), "+f"(d[61]), "+f"(d[62]), "+f"(d[63]),
          "+f"(d[64]), "+f"(d[65]), "+f"(d[66]), "+f"(d[67]), "+f"(d[68]), "+f"(d[69]), "+f"(d[70]), "+f"(d[71]),
          "+f"(d[72]), "+f"(d[73]), "+f"(d[74]), "+f"(d[75]), "+f"(d[76]), "+f"(d[77]), "+f"(d[78]), "+f"(d[79]),
          "+f"(d[80]), "+f"(d[81]), "+f"(d[82]), "+f"(d[83]), "+f"(d[84]), "+f"(d[85]), "+f"(d[86]), "+f"(d[87]),
          "+f"(d[88]), "+f"(d[89]), "+f"(d[90]), "+f"(d[91]), "+f"(d[92]), "+f"(d[93]), "+f"(d[94]), "+f"(d[95]),
          "+f"(d[96]), "+f"(d[97]), "+f"(d[98]), "+f"(d[99]), "+f"(d[100]), "+f"(d[101]), "+f"(d[102]), "+f"(d[103]),
          "+f"(d[104]), "+f"(d[105]), "+f"(d[106]), "+f"(d[107]), "+f"(d[108]), "+f"(d[109]), "+f"(d[110]), "+f"(d[111]),
          "+f"(d[112]), "+f"(d[113]), "+f"(d[114]), "+f"(d[115]), "+f"(d[116]), "+f"(d[117]), "+f"(d[118]), "+f"(d[119]),
          "+f"(d[120]), "+f"(d[121]), "+f"(d[122]), "+f"(d[123]), "+f"(d[124]), "+f"(d[125]), "+f"(d[126]), "+f"(d[127])
        : "l"(da), "l"(db), "n"(TA), "n"(TB), "r"(keep));
}
template <int TA, int TB>
__device__ __forceinline__ void wgmma_n192(float (&d)[128], uint64_t da, uint64_t db, int keep) {
    asm volatile(
        "{\n.reg .pred p;\nsetp.ne.b32 p, %100, 0;\n"
        "wgmma.mma_async.sync.aligned.m64n192k16.f32.bf16.bf16 "
        "{%0, %1, %2, %3, %4, %5, %6, %7, %8, %9, %10, %11, %12, %13, %14, %15, "
        "%16, %17, %18, %19, %20, %21, %22, %23, %24, %25, %26, %27, %28, %29, %30, %31, "
        "%32, %33, %34, %35, %36, %37, %38, %39, %40, %41, %42, %43, %44, %45, %46, %47, "
        "%48, %49, %50, %51, %52, %53, %54, %55, %56, %57, %58, %59, %60, %61, %62, %63, "
        "%64, %65, %66, %67, %68, %69, %70, %71, %72, %73, %74, %75, %76, %77, %78, %79, "
        "%80, %81, %82, %83, %84, %85, %86, %87, %88, %89, %90, %91, %92, %93, %94, %95}, "
        "%96, %97, p, 1, 1, %98, %99;\n}\n"
        : "+f"(d[0]), "+f"(d[1]), "+f"(d[2]), "+f"(d[3]), "+f"(d[4]), "+f"(d[5]), "+f"(d[6]), "+f"(d[7]),
          "+f"(d[8]), "+f"(d[9]), "+f"(d[10]), "+f"(d[11]), "+f"(d[12]), "+f"(d[13]), "+f"(d[14]), "+f"(d[15]),
          "+f"(d[16]), "+f"(d[17]), "+f"(d[18]), "+f"(d[19]), "+f"(d[20]), "+f"(d[21]), "+f"(d[22]), "+f"(d[23]),
          "+f"(d[24]), "+f"(d[25]), "+f"(d[26]), "+f"(d[27]), "+f"(d[28]), "+f"(d[29]), "+f"(d[30]), "+f"(d[31]),
          "+f"(d[32]), "+f"(d[33]), "+f"(d[34]), "+f"(d[35]), "+f"(d[36]), "+f"(d[37]), "+f"(d[38]), "+f"(d[39]),
          "+f"(d[40]), "+f"(d[41]), "+f"(d[42]), "+f"(d[43]), "+f"(d[44]), "+f"(d[45]), "+f"(d[46]), "+f"(d[47]),
          "+f"(d[48]), "+f"(d[49]), "+f"(d[50]), "+f"(d[51]), "+f"(d[52]), "+f"(d[53]), "+f"(d[54]), "+f"(d[55]),
          "+f"(d[56]), "+f"(d[57]), "+f"(d[58]), "+f"(d[59]), "+f"(d[60]), "+f"(d[61]), "+f"(d[62]), "+f"(d[63]),
          "+f"(d[64]), "+f"(d[65]), "+f"(d[66]), "+f"(d[67]), "+f"(d[68]), "+f"(d[69]), "+f"(d[70]), "+f"(d[71]),
          "+f"(d[72]), "+f"(d[73]), "+f"(d[74]), "+f"(d[75]), "+f"(d[76]), "+f"(d[77]), "+f"(d[78]), "+f"(d[79]),
          "+f"(d[80]), "+f"(d[81]), "+f"(d[82]), "+f"(d[83]), "+f"(d[84]), "+f"(d[85]), "+f"(d[86]), "+f"(d[87]),
          "+f"(d[88]), "+f"(d[89]), "+f"(d[90]), "+f"(d[91]), "+f"(d[92]), "+f"(d[93]), "+f"(d[94]), "+f"(d[95])
        : "l"(da), "l"(db), "n"(TA), "n"(TB), "r"(keep));
}
template <int TA, int TB, int O>
__device__ __forceinline__ void wgmma_n64(float (&d)[128], uint64_t da, uint64_t db, int keep) {
    asm volatile(
        "{\n.reg .pred p;\nsetp.ne.b32 p, %36, 0;\n"
        "wgmma.mma_async.sync.aligned.m64n64k16.f32.bf16.bf16 "
        "{%0, %1, %2, %3, %4, %5, %6, %7, %8, %9, %10, %11, %12, %13, %14, %15, "
        "%16, %17, %18, %19, %20, %21, %22, %23, %24, %25, %26, %27, %28, %29, %30, %31}, "
        "%32, %33, p, 1, 1, %34, %35;\n}\n"
        : "+f"(d[O + 0]), "+f"(d[O + 1]), "+f"(d[O + 2]), "+f"(d[O + 3]), "+f"(d[O + 4]), "+f"(d[O + 5]), "+f"(d[O + 6]), "+f"(d[O + 7]),
          "+f"(d[O + 8]), "+f"(d[O + 9]), "+f"(d[O + 10]), "+f"(d[O + 11]), "+f"(d[O + 12]), "+f"(d[O + 13]), "+f"(d[O + 14]), "+f"(d[O + 15]),
          "+f"(d[O + 16]), "+f"(d[O + 17]), "+f"(d[O + 18]), "+f"(d[O + 19]), "+f"(d[O + 20]), "+f"(d[O + 21]), "+f"(d[O + 22]), "+f"(d[O + 23]),
          "+f"(d[O + 24]), "+f"(d[O + 25]), "+f"(d[O + 26]), "+f"(d[O + 27]), "+f"(d[O + 28]), "+f"(d[O + 29]), "+f"(d[O + 30]), "+f"(d[O + 31])
        : "l"(da), "l"(db), "n"(TA), "n"(TB), "r"(keep));
}
template <int O>
__device__ __forceinline__ void wgmma_n64_rs(float (&d)[128], uint32_t a0, uint32_t a1, uint32_t a2, uint32_t a3, uint64_t db) {
    asm volatile(
        "{\n.reg .pred p;\nsetp.ne.b32 p, 1, 0;\n"
        "wgmma.mma_async.sync.aligned.m64n64k16.f32.bf16.bf16 "
        "{%0, %1, %2, %3, %4, %5, %6, %7, %8, %9, %10, %11, %12, %13, %14, %15, "
        "%16, %17, %18, %19, %20, %21, %22, %23, %24, %25, %26, %27, %28, %29, %30, %31}, "
        "{%32, %33, %34, %35}, %36, p, 1, 1, 1;\n}\n"
        : "+f"(d[O + 0]), "+f"(d[O + 1]), "+f"(d[O + 2]), "+f"(d[O + 3]), "+f"(d[O + 4]), "+f"(d[O + 5]), "+f"(d[O + 6]), "+f"(d[O + 7]),
          "+f"(d[O + 8]), "+f"(d[O + 9]), "+f"(d[O + 10]), "+f"(d[O + 11]), "+f"(d[O + 12]), "+f"(d[O + 13]), "+f"(d[O + 14]), "+f"(d[O + 15]),
          "+f"(d[O + 16]), "+f"(d[O + 17]), "+f"(d[O + 18]), "+f"(d[O + 19]), "+f"(d[O + 20]), "+f"(d[O + 21]), "+f"(d[O + 22]), "+f"(d[O + 23]),
          "+f"(d[O + 24]), "+f"(d[O + 25]), "+f"(d[O + 26]), "+f"(d[O + 27]), "+f"(d[O + 28]), "+f"(d[O + 29]), "+f"(d[O + 30]), "+f"(d[O + 31])
        : "r"(a0), "r"(a1), "r"(a2), "r"(a3), "l"(db));
}

constexpr uint64_t kDescHi = (uint64_t)(64u | 0x40000000u) << 32;
template <int MODE>
__device__ __forceinline__ void mma_kblock(float (&acc)[128], uint32_t a_lo, uint32_t b_lo, int keep) {
    constexpr uint32_t HALF = (MODE == 1) ? 12288u : 16384u;
    constexpr bool BN = (MODE == 1 || MODE == 2);
#pragma unroll
    for (int kk = 0; kk < 4; ++kk) {
        const uint32_t ao = (MODE == 3) ? kk * 2048u : kk * 32u;
        const uint32_t bo = BN ? ((kk >> 1) * HALF + (kk & 1) * 2048u) : kk * 32u;
        const uint64_t da = kDescHi | (uint64_t)(a_lo + (ao >> 4) + (1u << 16));
        const uint64_t db = kDescHi | (uint64_t)(b_lo + (bo >> 4) + (BN ? (256u << 16) : (1u << 16)));
        if (MODE == 1) wgmma_n192<0, 1>(acc, da, db, kk == 0 ? keep : 1);
        else wgmma_n256<(MODE == 3), BN>(acc, da, db, kk == 0 ? keep : 1);
    }
}

struct Params {
    Scratch* s;
    const __nv_bfloat16* x;
    const __nv_bfloat16* b_re;
    const __nv_bfloat16* b_im;
    const __nv_bfloat16* gate_w;
    const __nv_bfloat16* lam_re;
    const __nv_bfloat16* lam_im;
    const __nv_bfloat16* log_dt;
    const __nv_bfloat16* dskip;
    const __nv_bfloat16* b1;
    const __nv_bfloat16* b2;
    float* out;
    int swap;
};

#define CMUL(rr, ri, ar, ai, br, bi) do { float _r = (ar) * (br) - (ai) * (bi); float _i = (ar) * (bi) + (ai) * (br); rr = _r; ri = _i; } while (0)
#define CFMA(rr, ri, ar, ai, br, bi) do { float _r = fmaf(-(ai), (bi), fmaf((ar), (br), rr)); float _i = fmaf((ai), (br), fmaf((ar), (bi), ri)); rr = _r; ri = _i; } while (0)

#define KB_OPEN(IT, LAST)                                                                        \
    KT(IT, 0);                                                                                   \
    if (ORDER && (LAST) && wg == 1) bar_sync(7, 256);                                            \
    mbar_wait(bar_full + 8 * ((IT) & 3), ((IT) >> 2) & 1);                                \
    KT(IT, 1);
#define KB_CLOSE(IT, LAST, REL)                                                                  \
    if (ORDER && (LAST) && wg == 0) bar_arrive(7, 256);                                          \
    wgmma_wait<1>();                                                                             \
    if (lane < 2 && (REL)) mbar_arrive_cluster(rel_addr + 8 * (((IT) - 1) & 3));
#define KBLOCK(MODE, IT, FIRST, LAST)                                                            \
    {                                                                                            \
        const uint32_t so = ((IT) & 3) * (kStageBytes >> 4);                                     \
        KB_OPEN(IT, LAST);                                                                       \
        wgmma_fence();                                                                           \
        mma_kblock<MODE>(acc, a_lo + so, b_lo + so, !(FIRST));                                   \
        wgmma_commit();                                                                          \
        KB_CLOSE(IT, LAST, !(FIRST));                                                            \
    }
#define TILE_END() do { wgmma_wait<0>(); if (lane < 2) mbar_arrive_cluster(rel_addr + 24); } while (0)

__global__ void __cluster_dims__(2, 1, 1) __launch_bounds__(384, 1)
fused_kernel(const __grid_constant__ CUtensorMap mB, const __grid_constant__ CUtensorMap mXs, const __grid_constant__ CUtensorMap mXf,
             const __grid_constant__ CUtensorMap mW1b, const __grid_constant__ CUtensorMap mW1a, const __grid_constant__ CUtensorMap mHs,
             const __grid_constant__ CUtensorMap mHf, const __grid_constant__ CUtensorMap mCre, const __grid_constant__ CUtensorMap mCim,
             const __grid_constant__ CUtensorMap mW2, const __grid_constant__ CUtensorMap mW2n, const __grid_constant__ CUtensorMap mW2p,
             const __grid_constant__ CUtensorMap mHf3, const Params p) {
    extern __shared__ __align__(1024) uint8_t smem_raw[];
    if (PFTOP) { prefetch_map(&mB); prefetch_map(&mXs); }
    const uint32_t sbase = smem_u32(smem_raw);
    if ((sbase & 0x3ffffu) != kSmemOrg) return;
    const uint32_t bar_full = sbase + kBarOff, bar_empty = bar_full + 32, bar_dep = bar_full + 64;
    const uint32_t bar_x = bar_full + 88, bar_c = bar_full + 96, role_s = bar_full + 104, bar_role = bar_full + 120, tag_s = bar_full + 112 + (threadIdx.x & 1) * 4;

    const int tid = threadIdx.x, lane = tid & 31;
    const int warp = __shfl_sync(0xffffffffu, tid >> 5, 0);
    const uint32_t rank = blockIdx.x & 1;

    int pref;
    {
        unsigned smid;
        asm("mov.u32 %0, %%smid;" : "=r"(smid));
        const int t = smid >> 1, u = t - 32, d = (u * 37) >> 8;
        pref = (t < 32) ? (t & 7) * 8 + (t >> 3) : (t < 60) ? (1 + u - 7 * d) * 8 + 4 + d : ((t - 58) & 7);
    }
    STAMP(tid == 0, 0);
    int role = pref;
#define ROLE_VARS()                                                                                               \
    const int c = role >> 3;                                                             \
    const int j8 = role & 7;                                                        \
    const int cb = j8 * 2 + (int)rank;                                             \
    const int rb = 2 * c + (int)rank;                                               \
    const int kh = j8 >> 2;                 \
    const int colK = (j8 & 3) * 256 + kh * 128, colS = colK ^ 128;    \
    (void)cb; (void)rb; (void)colS;

#define INIT_ALL()                                                                                    \
    if (warp == INITW && elect_one()) {                                                               \
        if (!PFTOP) { prefetch_map(&mB); prefetch_map(&mXs); }                                        \
        _Pragma("unroll") for (int s = 0; s < kStages; ++s) {                                         \
            mbar_init(bar_full + 8 * s, 1);                                                           \
            mbar_init(bar_empty + 8 * s, 16);                                                         \
            mbar_init(bar_dep + 8 * s, 1);                                \
        }                                                                                             \
        mbar_init(bar_c, 96);                                                                         \
        mbar_init(bar_role, 1);                                                                       \
        asm volatile("fence.mbarrier_init.release.cluster;\nfence.proxy.async.shared::cta;" ::: "memory"); \
        mbar_expect_tx(bar_full, 49152);            \
        tma4(sbase, &mB, bar_full, 0, 0, 0, ((pref & 7) * 2 + (int)rank) * 8);                        \
        if (!MC0) {                                                                                   \
        tma5(sbase + kABytes, &mXs, bar_full, 0, 0, 0, 0, pref >> 3);                                 \
        tma5(sbase + kABytes + 16384, &mXs, bar_full, 0, 0, 0, 16, pref >> 3);                        \
        }                                                                                             \
        mbar_expect_tx(bar_x, 2048);                                                                  \
        bulk_load(sbase + kXOff, p.gate_w, 2048, bar_x);                                              \
        mbar_expect_tx(bar_role, 8);                                                                  \
    }
    if (PRODCOND) {
        asm volatile("setmaxnreg.dec.sync.aligned.u32 24;");
        unsigned taken = 0;
        if (tid == 352 && rank == 0) {
            taken = atom_exch(&p.s->claim[pref], 1u);
        }
        __syncwarp();
        cluster_arrive();
        cluster_wait();
        if (warp > 8) {
            if (tid == 352) {
#pragma unroll 1
                for (int i = 0; taken != 0 && i < 64; ++i) { role = i + 256; taken = atom_exch(&p.s->claim[i], 1u); }
                st_async32(mapa(role_s + 4 * rank, 0), role, mapa(bar_role, 0));
                st_async32(mapa(role_s + 4 * rank, 1), role, mapa(bar_role, 1));
            }
            __syncwarp();
            mbar_wait(bar_role, 0);
            role = __shfl_sync(0xffffffffu, (int)lds32(role_s), 0) & 63;
            ROLE_VARS();
            if (warp == 11) {
                if (lane < 11) prefetch_map(&mXf + lane);
#pragma unroll 1
                for (int en = lane; en < 88; en += 32) {
                    const int J = en >> 2;
                    const __nv_bfloat16* src = ((J < 14) ? p.b1 : (J < 18) ? p.dskip : p.b2) + 32 * J + 2 * (en & 3) +
                                               ((J < 6) ? 2048 + 192 * j8 : (J < 14) ? 256 * j8 - 192 : colK - ((J < 18) ? 448 : 576));
                    sts128(sbase + kBiasOff + en * 16, ldg32(src), ldg32(src + 8), ldg32(src + 16), ldg32(src + 24));
                }
                mbar_arrive_local(bar_c);
            } else {
                {
                    sts32(tag_s, ld_relaxed32(&p.s->epoch) + 1);
                    const int ch = cb * 64 + (tid - 288);
                    const uint32_t t_s = sbase + kTabOff + (tid - 288) * 64;
                    const float Lr = bf_lo(ldg16(p.lam_re + ch)), Li = bf_lo(ldg16(p.lam_im + ch));
                    const float dt = bf16_round(expf(bf_lo(ldg16(p.log_dt + ch))));
                    const float ea = expf(dt * Lr);
                    float lr, li;
                    sincospif((dt * Li) * 0.31830988618379067f, &li, &lr);
                    lr *= ea; li *= ea;
                    const float nr = lr - 1.0f, ni = li;
                    const bool big = fabsf(Lr) >= fabsf(Li);
                    const float u = big ? Lr : Li, v = big ? Li : Lr;
                    const float t = v / u, d = 2.0f / fmaf(v, t, u);
                    const float cr = (big ? fmaf(ni, t, nr) : fmaf(nr, t, ni)) * d, ci = (big ? fmaf(-nr, t, ni) : fmaf(ni, t, -nr)) * d;
                    if (p.swap) li = -li;
                    const float m00 = p.swap ? -ci : cr, m01 = p.swap ? cr : -ci, m10 = p.swap ? -cr : -ci, m11 = p.swap ? -ci : -cr;
#pragma unroll
                    for (int q = 0; q < 4; ++q) {
                        sts128f(t_s + q * 16, lr, li, m00, m01);
                        sts128f(t_s + 12288 + q * 16, 0.f, 0.f, 0.f, 0.f);
                    }
#pragma unroll 1
                    for (int i = 0; i < 6; ++i) CMUL(lr, li, lr, li, lr, li);
                    float ar, ai, br, bi;
                    CMUL(ar, ai, lr, li, lr, li);
                    CMUL(br, bi, ar, ai, lr, li);
                    sts128f(t_s + 4096, m10, m11, 0.f, 0.f);
#pragma unroll
                    for (int q = 1; q < 4; ++q) sts128f(t_s + 4096 + q * 16, m10, m11, lr, li);
                    sts128f(t_s + 8192, 0.f, 0.f, 1.f, 0.f);
                    sts128f(t_s + 8192 + 16, 0.f, 0.f, lr, li);
                    sts128f(t_s + 8192 + 32, ar, ai, ar, ai);
                    sts128f(t_s + 8192 + 48, ar, ai, br, bi);
                    CMUL(ar, ai, ar, ai, ar, ai);
                    br = 1.f; bi = 0.f;
#pragma unroll 1
                    for (int k = c - 1; k >= 0; --k) {
                        sts64f(t_s + 12288 + (k & 3) * 16 + (k >> 2) * 8, br, bi);
                        CMUL(br, bi, br, bi, ar, ai);
                    }
                    mbar_arrive_local(bar_c);
                }
                if (warp == 9) {
#pragma unroll 1
                    for (int ev = 0; ev < 3; ++ev) {
                        if (ev == 2) {
                            uint8_t* box = p.s->X + (size_t)(role * 2 + rank) * kXBytes + lane * 16;
#pragma unroll 1
                            for (int i = 0; i < kXBytes; i += 512) stg128(box + i, 0, 0, 0, 0);
                        }
                        bar_sync(3 + ev, 288);
                        if (lane == 0) {
                            unsigned* cnt = &p.s->cnt[(ev == 0 ? c : 16 * ev - 8 + rb) * 32];
                            asm volatile("fence.acq_rel.gpu;\nfence.proxy.async.global;" ::: "memory");
                            asm volatile("red.relaxed.gpu.global.add.u32 [%0], 1;" ::"l"(cnt) : "memory");
                        }
                        __syncwarp();
                    }
                } else if (lane == 0) {
                    const unsigned tag = lds32(tag_s);
#pragma unroll 1
                    for (int ev = 0; ev < 3; ++ev) {
                        wait_counter(&p.s->cnt[(ev == 0 ? c : 16 * ev - 8 + rb) * 32], tag * (ev == 0 ? 16u : 8u));
                        mbar_arrive_local(bar_dep + 8 * ev);
                        if (ev == 0 && atomicInc(&p.s->done, 127u) == 127u) {
                            st_relaxed32(&p.s->epoch, tag);
#pragma unroll 1
                            for (int i = 0; i < 64; i += 4) stg128(&p.s->claim[i], 0, 0, 0, 0);
                        }
                    }
                }
            }
        } else if (elect_one()) {
            int it = 1, again = 15;
            if (MC0) tma5_mc(sbase + kABytes + rank * 16384, &mXs, bar_full, 0, 0, 0, rank * 16, role >> 3);
#define ACQUIRE(BYTES)                                                   \
    const uint32_t st = sbase + (it & 3) * kStageBytes, fb = bar_full + 8 * (it & 3); \
    mbar_wait(bar_empty + 8 * (it & 3), ((it >> 2) & 1) ^ 1);     \
    mbar_expect_tx(fb, BYTES);
#pragma unroll 1
            for (; it < 16; ++it) {
                ACQUIRE(49152);
                tma4(st, &mB, fb, it * 64, 0, 0, ((role & 7) * 2 + (int)rank) * 8);
                tma5_mc(st + kABytes + rank * 16384, &mXs, fb, it * 64, 0, 0, rank * 16, role >> 3);
                if (it == again) {
                    mbar_wait(bar_role, 0);
                    const uint2 fin = lds64(role_s);
                    role = fin.x & 63;
                    if (fin.x != fin.y) { it = -1; again = 16; }
                }
            }
            ROLE_VARS();
#pragma unroll 1
            for (; it < 48; ++it) {
                const bool t1 = it < 32;
                const int k0 = (it & 15) * 64;
                ACQUIRE(t1 ? 40960 : 49152);
                tma5(st, &mXf, fb, k0, 0, 0, rank * 4, c);
                tma3_mc(st + kABytes + rank * (t1 ? 12288 : 16384), t1 ? &mW1b : &mW1a, fb, 0, k0 + rank * 32, t1 ? 32 + 3 * j8 : 4 * j8);
                if ((it & ~2) == XLDKB) {
                    const int h = (it >> 1) & 1;
                    if (h == 0) mbar_expect_tx(bar_x, 32768);
                    tma5(sbase + kXOff + h * 16384, &mXf, bar_x, colK + h * 64, 0, 0, rank * 4, c);
                }
            }
            STAMPA(true, 8);
            mbar_wait(bar_dep, 0);
            asm volatile("fence.proxy.async.global;" ::: "memory");
            STAMPA(true, 9);
#pragma unroll 1
            for (; it < 64; ++it) {
                const int k0 = (it & 15) * 64;
                ACQUIRE(49152);
                tma3(st, &mHs, fb, 0, kh * 1024 + k0, rb * 2);
                tma2_mc(st + kABytes + rank * 16384, kh ? &mCim : &mCre, fb, k0, rank ? colS : colK);
            }
            int f0 = 2048 + 768 * kh;
#pragma unroll 1
            for (; it < 88; ++it, f0 += 64) {
                if (it == 64 || it == 76) {
                    mbar_wait(bar_dep + (it == 64 ? 8 : 16), 0);
                    asm volatile("fence.proxy.async.global;" ::: "memory");
                    if (it == 76) f0 = 1024 * kh;
                }
                if (f0 == 256 * j8) f0 += 256;
                ACQUIRE(49152);
                tma2(st, &mHf, fb, f0, rb * 128);
                tma5_mc(st + kABytes + rank * 16384, &mW2, fb, 0, 0, (f0 >> 3) + 4 * rank, 0, colK >> 6);
                tma5_mc(st + kABytes + rank * 16384 + 8192, &mW2, fb, 0, 0, (f0 >> 3) + 4 * rank, 0, colS >> 6);
                if ((it >> 2) == PFKB / 4) tma2_pf(&mW2n, colK + (it & 2) * 32, 256 * (j8 ^ ((it & 1) * 4)) + 128 * rank);
            }
#pragma unroll 1
            for (; it < kTotal; ++it) {
                const int h = (it & 2) * 32;
                ACQUIRE(49152);
                tma3(st, &mHf3, fb, 0, rb * 128 + h, 4 * (j8 ^ 4) + 2 * (it & 1));
                if (it & 1) tma5_mc(st + kABytes + rank * 16384, &mW2p, fb, colK + h, 0, 0, 0, 8 * (j8 ^ 4) + 4 * rank);
                else tma2_mc(st + kABytes + rank * 16384, &mW2n, fb, colK + h, 256 * j8 + 128 * rank);
            }
        }
    } else {
        INIT_ALL();
        if (warp >= 8 - PF0LINES) {
            const int row = blockIdx.x * 32 + lane;
            const __nv_bfloat16* src = (row < 2048) ? p.x : (row < 3072) ? p.b_re - 2048 * kD : p.b_im - 3072 * kD;
            asm volatile("prefetch.global.L2 [%0];" ::"l"(src + row * kD + (7 - warp) * 64) : "memory");
        }
        __syncwarp();
        cluster_arrive();
        asm volatile("setmaxnreg.inc.sync.aligned.u32 240;");
        const int wg = warp >> 2, w = warp & 3, r = lane >> 2, q = lane & 3, tw = tid & 127;
        uint32_t a_lo = (kSmemOrg + wg * 8192) >> 4;
        constexpr uint32_t b_lo = (kSmemOrg + kABytes) >> 4;
        const uint32_t rel_addr = mapa(bar_empty, (uint32_t)(lane & 1));
        const uint32_t gate_s = sbase + kGateOff;
        float acc[128];
        uint32_t pk[64];
        unsigned tag;
        UNDEF_R(tag);

#pragma unroll
        for (int i = 0; i < 128; ++i) UNDEF_F(acc[i]);
        float gs = 0.f;
        {
            const uint32_t gx_s = sbase + kABytes + (16 * rank + 2 * warp + (lane >> 4)) * 128 +
                                  ((((lane & 15) >> 1) ^ (2 * w + (lane >> 4))) << 4) + (lane & 1) * 8;
            const uint32_t gw_s = sbase + kXOff + (lane & 15) * 8;
            uint32_t again = 15;
            cluster_wait();
#pragma unroll 1
            for (uint32_t it = 0; it < 16; ++it) {
                const uint32_t so = (it & 3) * (kStageBytes >> 4);
                KB_OPEN(it, it == 15);
                wgmma_fence();
                mma_kblock<0>(acc, a_lo + so, b_lo + so, it != 0);
                wgmma_commit();
                KB_CLOSE(it, it == 15, it + again != 15);
                STAMPA(tid == 0 && it == 0, 1);
                mbar_wait(bar_x, 0);
                const uint2 xa = lds64(gx_s + (role & 7) * 4096 + (it & 3) * kStageBytes), wa = lds64(gw_s + it * 128);
                const uint32_t pa = bf2_mul(xa.x, wa.x), pb = bf2_mul(xa.y, wa.y);
                gs += (bf_lo(pa) + bf_hi(pa)) + (bf_lo(pb) + bf_hi(pb));
                if (it == again) {
                    mbar_wait(bar_c, 0);
                    const uint2 fin = lds64(role_s);
                    role = fin.x & 63;
                    if (__shfl_sync(0xffffffffu, fin.x != fin.y, 0)) { it = -1; again = 16; gs = 0.f; }
                }
            }
        }
        role = __shfl_sync(0xffffffffu, role, 0);
        ROLE_VARS();
        {
            tag = lds32(tag_s);
#pragma unroll
            for (int o = 8; o > 0; o >>= 1) gs += __shfl_xor_sync(0xffffffffu, gs, o);
            const float g = bf16_round(__frcp_rn(1.0f + expf(-bf16_round(gs))));
            if ((lane & 15) == 0) st_relaxed64(&p.s->gate[c * 256 + (lane >> 4) + 64 * w + 4 * cb + 2 * wg], __float_as_uint(g), tag);
        }
        const uint32_t tab_s = sbase + kTabOff + tid * 16;
        const float4 k0 = lds128f(tab_s);
        TILE_END();
        STAMPA(tid == 0, 2);
#pragma unroll
        for (int s = 0; s < 64; ++s) pk[s] = pack_bf16_v(acc[4 * (s >> 1) + (s & 1)], acc[4 * (s >> 1) + 2 + (s & 1)]);
#pragma unroll
        for (int i = 0; i < 96; ++i) UNDEF_F(acc[i]);

        const float lr = k0.x, li = k0.y, m00 = k0.z, m01 = k0.w;
        float m10, m11, hr = 0.f, hi = 0.f;
        uint32_t gg[4], orr[4], oii[4];
        const int ch = cb * 64 + warp * 8 + r;
        __nv_bfloat16* hs = p.s->Hs + (size_t)ch * 2048 + c * 256 + q * 8;
#define PASS2(KB)                                                                                      \
    _Pragma("unroll") for (int s = 0; s < 64; s += 2) {                                                \
        if (pass2_kb(s) != (KB)) continue;                                                             \
        if ((s & 7) == 0) {                                                                            \
            const uint4 ga = lds128(gate_s + (q * 72 + s) * 2);                                        \
            gg[0] = ga.x; gg[1] = ga.y; gg[2] = ga.z; gg[3] = ga.w;                                    \
        }                                                                                              \
        float o0[2], o1[2];                                                                            \
        _Pragma("unroll") for (int k = 0; k < 2; ++k) {                                                \
            PIN_R(pk[s + k]);                                                                          \
            float nr = bf_lo(pk[s + k]), ni = bf_hi(pk[s + k]);                                        \
            CFMA(nr, ni, lr, li, hr, hi);                                                              \
            hr = nr; hi = ni;                                                                          \
            o0[k] = fmaf(m00, hr, m01 * hi);                                                           \
            o1[k] = fmaf(m10, hr, m11 * hi);                                                           \
        }                                                                                              \
        orr[(s >> 1) & 3] = bf2_mul(pack_bf16(o0[0], o0[1]), gg[(s >> 1) & 3]);                        \
        oii[(s >> 1) & 3] = bf2_mul(pack_bf16(o1[0], o1[1]), gg[(s >> 1) & 3]);                        \
        if ((s & 7) == 6) {                                                                            \
            stg128(hs + 32 * (s >> 3), orr[0], orr[1], orr[2], orr[3]);                                \
            stg128(hs + 1024 * 2048 + 32 * (s >> 3), oii[0], oii[1], oii[2], oii[3]);                  \
        }                                                                                              \
    }                                                                                                  \
    PIN_F(hr); PIN_F(hi);
        {
            uint4 av0, av1, gv;
            float lqr, lqi;
#pragma unroll
            for (int kb = 0; kb < 16; ++kb) {
                PIN_R(a_lo);
                KBLOCK(1, 16 + kb, kb == 0, kb == 15);
                if (kb < 4) {
#pragma unroll
                    for (int s = kb * 16; s < kb * 16 + 16; ++s) {
                        float nr = bf_lo(pk[s]), ni = bf_hi(pk[s]);
                        CFMA(nr, ni, lr, li, hr, hi);
                        hr = nr; hi = ni;
                    }
                    PIN_F(hr); PIN_F(hi);
                }
                if (kb == 2) gv = ld_relaxed2x64(&p.s->gate[c * 256 + 2 * tw]);
                if (kb == 3) {
                    const float4 k1 = lds128f(tab_s + 4096), k2 = lds128f(tab_s + 8192);
                    m10 = k1.x; m11 = k1.y; lqr = k2.z; lqi = k2.w;
                    float tr = __shfl_up_sync(0xffffffffu, hr, 1, 4), ti = __shfl_up_sync(0xffffffffu, hi, 1, 4);
                    if (q >= 1) CFMA(hr, hi, k1.z, k1.w, tr, ti);
                    tr = __shfl_up_sync(0xffffffffu, hr, 2, 4); ti = __shfl_up_sync(0xffffffffu, hi, 2, 4);
                    if (q >= 2) CFMA(hr, hi, k2.x, k2.y, tr, ti);
                    if (q == 3) st_relaxed2x64(&p.s->agg[c * 1024 + ch], __float_as_uint(hr), tag, __float_as_uint(hi), tag);
                    tr = __shfl_up_sync(0xffffffffu, hr, 1, 4); ti = __shfl_up_sync(0xffffffffu, hi, 1, 4);
                    hr = (q >= 1) ? tr : 0.f; hi = (q >= 1) ? ti : 0.f;
                }
                if (kb == 4) {
                    unsigned spins = 0;
                    while (__any_sync(0xffffffffu, gv.y != tag || gv.w != tag)) {
                        if (++spins > kSpinLimit) break;
                        gv = ld_relaxed2x64(&p.s->gate[c * 256 + 2 * tw]);
                    }
                    sts32(gate_s + ((tw >> 5) * 72 + 2 * lane) * 2, __byte_perm(gv.x, gv.z, 0x7632));
                }
                if (kb == 5) {
                    av0 = make_uint4(0, tag, 0, tag); av1 = av0;
                    if (q < c) av0 = ld_relaxed2x64(&p.s->agg[q * 1024 + ch]);
                    if (q + 4 < c) av1 = ld_relaxed2x64(&p.s->agg[(q + 4) * 1024 + ch]);
                    bar_sync(1 + wg, 128);
                }
                if (kb == 6) {
                    const float4 k3 = lds128f(tab_s + 12288);
                    unsigned spins = 0;
                    while (__any_sync(0xffffffffu, av0.y != tag || av0.w != tag || av1.y != tag || av1.w != tag)) {
                        if (++spins > kSpinLimit) break;
                        if (q < c) av0 = ld_relaxed2x64(&p.s->agg[q * 1024 + ch]);
                        if (q + 4 < c) av1 = ld_relaxed2x64(&p.s->agg[(q + 4) * 1024 + ch]);
                    }
                    float vr, vi;
                    CMUL(vr, vi, k3.x, k3.y, __uint_as_float(av0.x), __uint_as_float(av0.z));
                    CFMA(vr, vi, k3.z, k3.w, __uint_as_float(av1.x), __uint_as_float(av1.z));
                    vr += __shfl_xor_sync(0xffffffffu, vr, 1); vi += __shfl_xor_sync(0xffffffffu, vi, 1);
                    vr += __shfl_xor_sync(0xffffffffu, vr, 2); vi += __shfl_xor_sync(0xffffffffu, vi, 2);
                    CFMA(hr, hi, lqr, lqi, vr, vi);
                }
                if (kb >= 6) { PASS2(kb); }
            }
            TILE_END();
        }
        STAMPA(tid == 0, 3);
#pragma unroll
        for (int i = 0; i < 48; ++i) pk[i] = pack_bf16_v(acc[2 * i], acc[2 * i + 1]);
#pragma unroll
        for (int i = 0; i < 128; ++i) UNDEF_F(acc[i]);

        PIN_R(a_lo);
        KBLOCK(2, 32, true, false);
        PASS2(16);
        PIN_R(a_lo);
        KBLOCK(2, 33, false, false);
        PASS2(17);
        bar_arrive(3, 288);
        const uint32_t gate_row = gate_s + ((2 * (w & 1)) * 72 + 8 * (4 * rank + 2 * wg + (w >> 1)) + r) * 2;
        uint32_t om0, om1;
        {
            const float a = 1.0f - bf_lo(lds16(gate_row)), b = 1.0f - bf_lo(lds16(gate_row + 72 * 2));
            om0 = pack_bf16(a, a); om1 = pack_bf16(b, b);
        }
        __nv_bfloat16* hf = p.s->Hf + (size_t)(rb * 128 + wg * 64 + w * 16 + r) * kF + q * 8 + 2048 + 192 * j8;
        uint32_t bias_s = sbase + kBiasOff + q * 16;
#define FFN_SLICE(J)                                                                                   \
    {                                                                                                  \
        const uint4 bv = lds128(bias_s + (J) * 64);                                                    \
        const uint32_t bb[4] = {bv.x, bv.y, bv.z, bv.w};                                               \
        _Pragma("unroll") for (int jj = 0; jj < 4; ++jj) {                                             \
            const uint32_t r0 = bf2_add_relu(pk[8 * (J) + 2 * jj], bb[jj]), r1 = bf2_add_relu(pk[8 * (J) + 2 * jj + 1], bb[jj]); \
            pk[8 * (J) + 2 * jj] = bf2_mul(bf2_mul(r0, r0), om0);                                      \
            pk[8 * (J) + 2 * jj + 1] = bf2_mul(bf2_mul(r1, r1), om1);                                  \
        }                                                                                              \
        stg128(hf + 32 * (J), pk[8 * (J)], pk[8 * (J) + 2], pk[8 * (J) + 4], pk[8 * (J) + 6]);         \
        stg128(hf + 8 * kF + 32 * (J), pk[8 * (J) + 1], pk[8 * (J) + 3], pk[8 * (J) + 5], pk[8 * (J) + 7]); \
    }
        const uint32_t x_s = sbase + kXOff + (wg * 64 + w * 16 + (lane & 15)) * 128 + (((lane >> 4) ^ (lane & 7)) << 4);
        {
            uint32_t j = 0, nsl = 6;
#pragma unroll 1
            for (uint32_t it = 34; it < 88; ++it, ++j) {
                const uint32_t so = (it & 3) * (kStageBytes >> 4);
                if (wg == 1 && (it == 88 - SKEW || (ORDER && it == 47))) bar_sync(7, 256);
                KB_OPEN(it, false);
                if ((it & ~15u) == 48) {
                    wgmma_fence();
                    mma_kblock<3>(acc, a_lo + so, b_lo + so, it != 48);
                    wgmma_commit();
                } else {
                    wgmma_fence();
                    mma_kblock<2>(acc, a_lo + so, b_lo + so, 1);
                    wgmma_commit();
                }
                if (wg == 0 && (it == 87 || (ORDER && it == 47))) bar_arrive(7, 256);
                KB_CLOSE(it, false, it != 48);
                if (j < nsl) {
                    if (j & 4) {
                        if (j & 2) { if (j & 1) FFN_SLICE(7) else FFN_SLICE(6) } else { if (j & 1) FFN_SLICE(5) else FFN_SLICE(4) }
                    } else {
                        if (j & 2) { if (j & 1) FFN_SLICE(3) else FFN_SLICE(2) } else { if (j & 1) FFN_SLICE(1) else FFN_SLICE(0) }
                    }
                    if (j + 1 == nsl) bar_arrive(1 + (nsl >> 1), 288);
                } else if (it == 47) {
                    hf += 64 * j8 - 2048;
                    bias_s += 6 * 64;
                    j = -1; nsl = 8;
                    TILE_END();
                    STAMPA(tid == 0, 4);
#pragma unroll
                    for (int i = 0; i < 64; ++i) pk[i] = pack_bf16_v(acc[2 * i], acc[2 * i + 1]);
                } else if ((it >> 2) == ETKB / 4) {
                    mbar_wait(bar_x, 1);
                    const uint32_t xa_s = (x_s ^ ((it & 1) << 6)) + (it & 2) * 8192;
                    const float g0 = bf_lo(lds16(gate_row)), g1 = bf_lo(lds16(gate_row + 72 * 2));
                    const float o0f = bf_lo(om0), o1f = bf_lo(om1);
                    const uint4 dq = lds128(bias_s + (8 + (it & 3)) * 64), bq = lds128(bias_s + (12 + (it & 3)) * 64);
                    const uint4 xa = ldsm4(xa_s), xb = ldsm4(xa_s ^ 32);
                    const uint32_t dv[4] = {dq.x, dq.y, dq.z, dq.w}, bv2[4] = {bq.x, bq.y, bq.z, bq.w};
                    uint32_t xv[8] = {xa.x, xa.y, xa.z, xa.w, xb.x, xb.y, xb.z, xb.w};
#pragma unroll
                    for (int jj = 0; jj < 4; ++jj) {
                        const uint32_t x0 = bf2_mul(xv[2 * jj], dv[jj]), x1 = bf2_mul(xv[2 * jj + 1], dv[jj]);
                        const float bl = bf_lo(bv2[jj]), bh = bf_hi(bv2[jj]);
                        xv[2 * jj] = pack_bf16(fmaf(g0, bf_lo(x0), o0f * bl), fmaf(g0, bf_hi(x0), o0f * bh));
                        xv[2 * jj + 1] = pack_bf16(fmaf(g1, bf_lo(x1), o1f * bl), fmaf(g1, bf_hi(x1), o1f * bh));
                    }
                    sts128(xa_s, xv[0], xv[1], xv[2], xv[3]);
                    sts128(xa_s ^ 32, xv[4], xv[5], xv[6], xv[7]);
                }
            }
        }
#define OWN_MMA(H, P)                                                                                  \
    wgmma_fence();                                                                                     \
    _Pragma("unroll") for (int i = 8 * (P); i < 8 * (P) + 8; ++i)                                      \
        wgmma_n64_rs<32 * (H)>(acc, pk[4 * i], pk[4 * i + 1], pk[4 * i + 2], pk[4 * i + 3],            \
                               kDescHi | (uint64_t)(b_lo + ((2 * (H) * kStageBytes + i * 2048) >> 4) + (256u << 16))); \
    wgmma_commit();
#define OTHER_MMA(H, P)                                                                                \
    PIN_R(a_lo);                                                                                       \
    wgmma_fence();                                                                                     \
    _Pragma("unroll") for (int i = 0; i < 8; ++i)                                                      \
        wgmma_n64<0, 1, 32 * (H)>(acc, kDescHi | (uint64_t)(a_lo + (((P) * kStageBytes + (i >> 2) * 8192 + (i & 3) * 32) >> 4) + (1u << 16)), \
                               kDescHi | (uint64_t)(b_lo + (((2 * (H) + 1) * kStageBytes + (8 * (P) + i) * 2048) >> 4) + (256u << 16)), 1); \
    wgmma_commit();
#define RXLOAD(H)                                                                                      \
    {                                                                                                  \
        if ((H) == 0) rs = ld_relaxed32((const unsigned*)(xi + 32768 - tid * 12));                     \
        _Pragma("unroll") for (int u = 4 * (H); u < 4 * (H) + 4; ++u) rx[u] = ld_relaxed2x64(xi + u * 4096); \
    }
#define RXCHECK(H)                                                                                     \
    {                                                                                                  \
        unsigned spins = 0;                                                                            \
        _Pragma("unroll 1") while (true) {                                                             \
            uint32_t ok = rs != 0;                                                                     \
            _Pragma("unroll") for (int u = 4 * (H); u < 4 * (H) + 4; ++u) ok &= rx[u].x & rx[u].z;     \
            if (__all_sync(0xffffffffu, ok) || ++spins > kSpinLimit) break;                            \
            RXLOAD(H);                                                                                 \
            RESPIN();                                                                                  \
        }                                                                                              \
    }
#define PUT(FROM, TO)                                                                                  \
    _Pragma("unroll") for (int uh = (FROM); uh < (TO); ++uh) {                                         \
        const int va = 4 * (uh & 14) + 2 * (uh & 1), vb = va + 4;                                      \
        const uint32_t ra = (uh & 1) ? rx[uh >> 1].y : rx[uh >> 1].x, rb2 = (uh & 1) ? rx[uh >> 1].w : rx[uh >> 1].z; \
        const float2 fa = __half22float2(*reinterpret_cast<const __half2*>(&ra)), fb = __half22float2(*reinterpret_cast<const __half2*>(&rb2)); \
        PIN_F(acc[va]); PIN_F(acc[va + 1]); PIN_F(acc[vb]); PIN_F(acc[vb + 1]);                        \
        const float a0 = fmaf(fa.x, xsc, acc[va]), a1 = fmaf(fa.y, xsc, acc[va + 1]);                  \
        const float b0 = fmaf(fb.x, xsc, acc[vb]), b1 = fmaf(fb.y, xsc, acc[vb + 1]);                  \
        const float t0 = __shfl_xor_sync(0xffffffffu, odd ? a0 : b0, 1), t1 = __shfl_xor_sync(0xffffffffu, odd ? a1 : b1, 1); \
        stg128f(o0 + (uh & 1) * 64 * kD + 8 * (uh & 14), odd ? t0 : a0, odd ? t1 : a1, odd ? b0 : t0, odd ? b1 : t1); \
    }
        TILE_END();
        sched_fence(a_lo);
        {
            const uint8_t* xi = p.s->X + (size_t)(role * 2 + rank) * kXBytes + tid * 16;
            uint8_t* xo = const_cast<uint8_t*>(xi) + (kh ? -8 * kXBytes : 8 * kXBytes);
            uint4 rx[8];
            uint32_t rs;
            {
                STAMP(tid == 0, 15); STAMPB(tid == 128, 1);
                float m[4] = {0.f, 0.f, 0.f, 0.f};
#pragma unroll
                for (int i = 64; i < 128; ++i) m[i & 3] = fmaxf(m[i & 3], fabsf(acc[i]));
                const uint32_t eb = max(__float_as_uint(fmaxf(fmaxf(m[0], m[1]), fmaxf(m[2], m[3]))) >> 23, 15u);
                const float xsc = __uint_as_float((268u - eb) << 23);
                st_relaxed32(xo + 32768 - tid * 12, (eb - 14u) << 23);
#pragma unroll
                for (int u = 0; u < 8; ++u) {
                    const int v = 64 + 8 * u;
                    st_relaxed2x64(xo + u * 4096, pack_f16(acc[v] * xsc, acc[v + 1] * xsc) | 1, pack_f16(acc[v + 2] * xsc, acc[v + 3] * xsc),
                                   pack_f16(acc[v + 4] * xsc, acc[v + 5] * xsc) | 1, pack_f16(acc[v + 6] * xsc, acc[v + 7] * xsc));
                }
                STAMP(tid == 0, 12); STAMPB(tid == 128, 2);
            }
#pragma unroll
            for (int u = 0; u < 8; ++u) rx[u] = lds128((x_s ^ ((u & 3) << 5)) + (u >> 2) * 16384);
#pragma unroll
            for (int u = 0; u < 8; ++u) {
                const uint32_t ee[4] = {rx[u].x, rx[u].y, rx[u].z, rx[u].w};
#pragma unroll
                for (int k = 0; k < 4; ++k) {
                    const int v = 8 * u + 2 * k;
                    acc[v] += bf_lo(ee[k]); acc[v + 1] += bf_hi(ee[k]);
                    PIN_F(acc[v]); PIN_F(acc[v + 1]);
                }
            }
            a_lo += wg * ((2 * kStageBytes - 8192) >> 4);
            const bool odd = q & 1;
            const int tb = c * 256 + 128 * (w & 1) + 8 * (4 * rank + 2 * wg + (w >> 1));
            float* o0 = p.out + (size_t)(tb + r) * kD + colK + (odd ? 2 * q + 6 : 2 * q);
            mbar_wait(bar_full, 0);
            if (wg == 1) {
                mbar_wait(bar_full + 16, 0);
                mbar_wait(bar_full + 24, 0);
                bar_sync(9, 256);
            }
            STAMPB(tid == 128, 3); STAMPB(tid == 0, 9);
            OWN_MMA(0, 0);
            sched_fence(a_lo);
            RXLOAD(0);
            STAMPB(tid == 0, 10);
            sched_fence(a_lo);
            OWN_MMA(0, 1);
            mbar_wait(bar_full + 8, 0);
            OTHER_MMA(0, 0);
            OTHER_MMA(0, 1);
            mbar_wait(bar_full + 16, 0);
            OWN_MMA(1, 0);
            sched_fence(a_lo);
            STAMPB(tid == 0, 11);
            RXCHECK(0);
            STAMP(tid == 0, 13);
            RXLOAD(1);
            const float xsc = __uint_as_float(rs);
            wgmma_wait<1>();
            STAMPB(tid == 128, 8);
            PUT(0, 2);
            sched_fence(a_lo);
            OWN_MMA(1, 1);
            sched_fence(a_lo);
            PUT(2, 5);
            mbar_wait(bar_full + 24, 0);
            OTHER_MMA(1, 0);
            sched_fence(a_lo);
            PUT(5, 8);
            sched_fence(a_lo);
            OTHER_MMA(1, 1);
            if (wg == 0) bar_arrive(9, 256);
            sched_fence(a_lo);
            STAMP(tid == 0, 14);
            RXCHECK(1);
            wgmma_wait<0>();
            STAMP(tid == 0, 6); STAMPB(tid == 128, 4);
            PUT(8, 16);
        }
        STAMP(tid == 0, 7);
        STAMP(tid == 128, 5);
    }
}

typedef CUresult (*EncodeFn)(CUtensorMap*, CUtensorMapDataType, cuuint32_t, void*, const cuuint64_t*, const cuuint64_t*,
                             const cuuint32_t*, const cuuint32_t*, CUtensorMapInterleave, CUtensorMapSwizzle,
                             CUtensorMapL2promotion, CUtensorMapFloatOOBfill);

bool encode(EncodeFn fn, CUtensorMap* m, const void* base, int rank, const cuuint64_t* dims, const cuuint64_t* strides,
            const cuuint32_t* box) {
    cuuint32_t es[5] = {1, 1, 1, 1, 1};
    return fn(m, CU_TENSOR_MAP_DATA_TYPE_BFLOAT16, rank, const_cast<void*>(base), dims, strides, box, es,
              CU_TENSOR_MAP_INTERLEAVE_NONE, CU_TENSOR_MAP_SWIZZLE_128B, CU_TENSOR_MAP_L2_PROMOTION_L2_256B,
              CU_TENSOR_MAP_FLOAT_OOB_FILL_NONE) == CUDA_SUCCESS;
}

}

extern "C" void kernel_launch(void* const* d_in, const int* in_sizes, int n_in, void* d_out, int out_size) {
    (void)in_sizes; (void)n_in; (void)out_size;
    typedef const __nv_bfloat16* bp;
    bp x = (bp)d_in[0], lam_re = (bp)d_in[1], lam_im = (bp)d_in[2], B_re = (bp)d_in[3], B_im = (bp)d_in[4];
    bp C_re = (bp)d_in[5], C_im = (bp)d_in[6], log_dt = (bp)d_in[7], dskip = (bp)d_in[8];
    bp w1 = (bp)d_in[10], b1 = (bp)d_in[11], w2 = (bp)d_in[12], b2 = (bp)d_in[13], gate_w = (bp)d_in[14];

    static EncodeFn fn = nullptr;
    static Scratch* ps = nullptr;
    if (!fn) {
        void* f = nullptr;
        cudaDriverEntryPointQueryResult qr;
        cudaGetDriverEntryPoint("cuTensorMapEncodeTiled", &f, cudaEnableDefault, &qr);
        fn = (EncodeFn)f;
        cudaGetSymbolAddress((void**)&ps, g_s);
        cudaFuncSetAttribute(fused_kernel, cudaFuncAttributeMaxDynamicSharedMemorySize, kSmemBytes);
    }
    cudaStream_t stream = cudaStreamPerThread;

    Params p;
    p.x = x; p.lam_re = lam_re; p.lam_im = lam_im; p.log_dt = log_dt; p.dskip = dskip; p.b1 = b1; p.b2 = b2;
    p.gate_w = gate_w; p.b_re = B_re; p.b_im = B_im; p.out = (float*)d_out; p.s = ps;
    char* const pHs = (char*)ps + offsetof(Scratch, Hs);
    char* const pHf = (char*)ps + offsetof(Scratch, Hf);
    char* const pBc = (char*)ps + offsetof(Scratch, Bcopy);

    const char* lo = (const char*)B_re; const char* hi = (const char*)B_im;
    p.swap = 0;
    if (hi < lo) { const char* t = lo; lo = hi; hi = t; p.swap = 1; }
    unsigned long long diff = (unsigned long long)(hi - lo);
    if (diff >= (1ull << 40) || (diff & 15) || diff == 0) {
        cudaMemcpyAsync(pBc, B_re, 2u << 20, cudaMemcpyDeviceToDevice, stream);
        cudaMemcpyAsync((char*)pBc + (2u << 20), B_im, 2u << 20, cudaMemcpyDeviceToDevice, stream);
        lo = (const char*)pBc; diff = 2u << 20; p.swap = 0;
    }

    CUtensorMap mB, mXs, mXf, mW1a, mW1b, mHs, mHf, mCre, mCim, mW2, mW2n, mW2p, mHf3;
    bool ok = true;
    { cuuint64_t d[4] = {1024, 8, 2, 128}, s[3] = {2048, diff, 16384}; cuuint32_t b[4] = {64, 8, 2, 8};
      ok &= encode(fn, &mB, lo, 4, d, s, b); }
    { cuuint64_t d[5] = {1024, 2, 4, 32, 8}, s[4] = {2048, 64 * 2048, 2 * 2048, 256 * 2048}; cuuint32_t b[5] = {64, 2, 4, 16, 1};
      ok &= encode(fn, &mXs, x, 5, d, s, b); }
    { cuuint64_t d[5] = {1024, 8, 4, 8, 8}, s[4] = {2048, 64 * 2048, 8 * 2048, 256 * 2048}; cuuint32_t b[5] = {64, 8, 4, 4, 1};
      ok &= encode(fn, &mXf, x, 5, d, s, b); }
    { cuuint64_t d[3] = {64, 1024, 56}, s[2] = {7168, 128}; cuuint32_t ba[3] = {64, 32, 4}, bb[3] = {64, 32, 3};
      ok &= encode(fn, &mW1a, w1, 3, d, s, ba); ok &= encode(fn, &mW1b, w1, 3, d, s, bb); }
    { cuuint64_t d[3] = {64, 2048, 32}, s[2] = {4096, 128}; cuuint32_t b[3] = {64, 64, 2};
      ok &= encode(fn, &mHs, pHs, 3, d, s, b); }
    { cuuint64_t d[2] = {3584, 2048}, s[1] = {7168}; cuuint32_t b[2] = {64, 128};
      ok &= encode(fn, &mHf, pHf, 2, d, s, b); }
    { cuuint64_t d[2] = {1024, 1024}, s[1] = {2048}; cuuint32_t b[2] = {64, 128};
      ok &= encode(fn, &mCre, C_re, 2, d, s, b); ok &= encode(fn, &mCim, C_im, 2, d, s, b); }
    { cuuint64_t d[5] = {64, 2, 448, 4, 16}, s[4] = {2048, 8 * 2048, 2 * 2048, 128}; cuuint32_t b[5] = {64, 2, 4, 4, 2};
      ok &= encode(fn, &mW2, w2, 5, d, s, b); }
    { cuuint64_t d[2] = {1024, 3584}, s[1] = {2048}; cuuint32_t b[2] = {64, 128};
      ok &= encode(fn, &mW2n, w2, 2, d, s, b); }
    { cuuint64_t d[5] = {1024, 2, 4, 4, 112}, s[4] = {2048, 8 * 2048, 2 * 2048, 32 * 2048}; cuuint32_t b[5] = {64, 2, 4, 4, 4};
      ok &= encode(fn, &mW2p, w2, 5, d, s, b); }
    { cuuint64_t d[3] = {64, 2048, 56}, s[2] = {7168, 128}; cuuint32_t b[3] = {64, 64, 2};
      ok &= encode(fn, &mHf3, pHf, 3, d, s, b); }
    if (!ok) return;

    fused_kernel<<<128, 384, kSmemBytes, stream>>>(mB, mXs, mXf, mW1b, mW1a, mHs, mHf, mCre, mCim, mW2, mW2n, mW2p, mHf3, p);
}
```

```cpp
#include <cuda_runtime.h>
#include <cuda_bf16.h>
#include <cuda_fp16.h>
#include <cuda.h>
#include <stdint.h>
#include <stddef.h>

#define XLDKB 40
#define PF0LINES 1
#define ETKB 60
#define PFKB 80
#define SKEW 3
#define MC0 0
#define PFTOP 0
#define INITW 0
#define PRODCOND warp >= 8
#define ORDER 0

namespace {

constexpr int kD = 1024, kF = 3584;
constexpr int kStages = 4;
constexpr int kStageBytes = 49152;
constexpr int kABytes = 16384;
constexpr int kXOff = kStages * kStageBytes;
constexpr int kTabOff = kXOff + 2048;
constexpr int kGateOff = kXOff + 32768;
constexpr int kBiasOff = kGateOff + 4 * 72 * 2;
constexpr int kBarOff = kBiasOff + 88 * 16;
constexpr int kSmemBytes = 232448;
static_assert(kBarOff + 160 <= kSmemBytes, "smem");
constexpr int kXBytes = 33792;
constexpr uint32_t kSmemOrg = 1024;
constexpr unsigned kSpinLimit = 1u << 18;
constexpr int kTotal = 92;

__host__ __device__ constexpr int pass2_kb(int s) {
    return s < 2 ? 6 : s < 8 ? 7 : s < 12 ? 8 : s < 18 ? 9 : s < 22 ? 10 : s < 28 ? 11 : s < 32 ? 12 : s < 38 ? 13 : s < 42 ? 14 : s < 48 ? 15 : s < 56 ? 16 : 17;
}

struct Scratch {
    unsigned claim[64];
    unsigned epoch, pad0[31];
    unsigned done, pad1[31];
    unsigned cnt[40 * 32];
    uint2 gate[2048];
    uint4 agg[8 * 1024];
    __align__(1024) uint8_t X[128 * kXBytes];
    __align__(1024) __nv_bfloat16 Hs[2048 * 2048];
    __align__(1024) __nv_bfloat16 Hf[2048 * 3584];
    __align__(1024) __nv_bfloat16 Bcopy[2 * 1024 * 1024];
};
__device__ Scratch g_s;

#define TRAP() break
#define PIN_F(x) asm volatile("" : "+f"(x))
#define PIN_R(x) asm volatile("" : "+r"(x))
#define UNDEF_F(x) asm volatile("" : "=f"(x))
#define UNDEF_R(x) asm volatile("" : "=r"(x))
#define RESPIN()
__device__ __forceinline__ uint32_t smem_u32(const void* p) { return (uint32_t)__cvta_generic_to_shared(p); }
__device__ __forceinline__ void mbar_init(uint32_t bar, uint32_t count) {
    asm volatile("mbarrier.init.shared::cta.b64 [%0], %1;" ::"r"(bar), "r"(count) : "memory");
}
__device__ __forceinline__ void mbar_expect_tx(uint32_t bar, uint32_t bytes) {
    asm volatile("mbarrier.arrive.expect_tx.shared::cta.b64 _, [%0], %1;" ::"r"(bar), "r"(bytes) : "memory");
}
__device__ __forceinline__ void mbar_wait(uint32_t bar, uint32_t parity) {
    asm volatile(
        "{\n.reg .pred p;\n.reg .u32 n;\n"
        "mbarrier.try_wait.parity.shared::cta.b64 p, [%0], %1;\n"
        "@p bra DONE;\n"
        "mov.u32 n, 0;\n"
        "LOOP:\n"
        "mbarrier.try_wait.parity.shared::cta.b64 p, [%0], %1;\n"
        "@p bra DONE;\n"
        "add.u32 n, n, 1;\n"
        "setp.lt.u32 p, n, %2;\n"
        "@p bra LOOP;\n"
        "DONE:\n}\n"
        ::"r"(bar), "r"(parity), "n"(kSpinLimit) : "memory");
}
__device__ __forceinline__ void sched_fence(uint32_t nonzero) {
    asm volatile("{\n.reg .pred p;\n.reg .u32 n;\nsetp.ne.u32 p, %0, 0;\n@p bra DONE;\nLOOP:\nmov.u32 n, %%clock;\n"
                 "setp.eq.u32 p, n, 0;\n@p bra LOOP;\nDONE:\n}\n" ::"r"(nonzero) : "memory");
}
__device__ __forceinline__ void mbar_arrive_local(uint32_t bar) {
    asm volatile("mbarrier.arrive.shared::cta.b64 _, [%0];" ::"r"(bar) : "memory");
}
__device__ __forceinline__ void mbar_arrive_cluster(uint32_t cluster_addr) {
    asm volatile("mbarrier.arrive.shared::cluster.b64 _, [%0];" ::"r"(cluster_addr) : "memory");
}
__device__ __forceinline__ uint32_t mapa(uint32_t addr, uint32_t rank) {
    uint32_t r;
    asm("mapa.shared::cluster.u32 %0, %1, %2;" : "=r"(r) : "r"(addr), "r"(rank));
    return r;
}
__device__ __forceinline__ void cluster_arrive() { asm volatile("barrier.cluster.arrive.relaxed.aligned;" ::: "memory"); }
__device__ __forceinline__ void cluster_wait() { asm volatile("barrier.cluster.wait.acquire.aligned;" ::: "memory"); }
__device__ __forceinline__ void bar_sync(int id, int n) { asm volatile("bar.sync %0, %1;" ::"r"(id), "r"(n) : "memory"); }
__device__ __forceinline__ void bar_arrive(int id, int n) { asm volatile("bar.arrive %0, %1;" ::"r"(id), "r"(n) : "memory"); }
__device__ __forceinline__ bool elect_one() {
    uint32_t p;
    asm volatile("{\n.reg .pred P;\nelect.sync _|P, 0xffffffff;\nselp.u32 %0, 1, 0, P;\n}\n" : "=r"(p));
    return p != 0;
}

__device__ __forceinline__ void tma2(uint32_t dst, const CUtensorMap* m, uint32_t bar, int c0, int c1) {
    asm volatile("cp.async.bulk.tensor.2d.shared::cluster.global.mbarrier::complete_tx::bytes [%0], [%1, {%3, %4}], [%2];"
                 ::"r"(dst), "l"(m), "r"(bar), "r"(c0), "r"(c1) : "memory");
}
__device__ __forceinline__ void tma3(uint32_t dst, const CUtensorMap* m, uint32_t bar, int c0, int c1, int c2) {
    asm volatile("cp.async.bulk.tensor.3d.shared::cluster.global.mbarrier::complete_tx::bytes [%0], [%1, {%3, %4, %5}], [%2];"
                 ::"r"(dst), "l"(m), "r"(bar), "r"(c0), "r"(c1), "r"(c2) : "memory");
}
__device__ __forceinline__ void tma4(uint32_t dst, const CUtensorMap* m, uint32_t bar, int c0, int c1, int c2, int c3) {
    asm volatile("cp.async.bulk.tensor.4d.shared::cluster.global.mbarrier::complete_tx::bytes [%0], [%1, {%3, %4, %5, %6}], [%2];"
                 ::"r"(dst), "l"(m), "r"(bar), "r"(c0), "r"(c1), "r"(c2), "r"(c3) : "memory");
}
__device__ __forceinline__ void tma5(uint32_t dst, const CUtensorMap* m, uint32_t bar, int c0, int c1, int c2, int c3, int c4) {
    asm volatile("cp.async.bulk.tensor.5d.shared::cluster.global.mbarrier::complete_tx::bytes [%0], [%1, {%3, %4, %5, %6, %7}], [%2];"
                 ::"r"(dst), "l"(m), "r"(bar), "r"(c0), "r"(c1), "r"(c2), "r"(c3), "r"(c4) : "memory");
}
__device__ __forceinline__ void tma2_mc(uint32_t dst, const CUtensorMap* m, uint32_t bar, int c0, int c1) {
    asm volatile("cp.async.bulk.tensor.2d.shared::cluster.global.mbarrier::complete_tx::bytes.multicast::cluster [%0], [%1, {%3, %4}], [%2], %5;"
                 ::"r"(dst), "l"(m), "r"(bar), "r"(c0), "r"(c1), "h"((uint16_t)3) : "memory");
}
__device__ __forceinline__ void tma3_mc(uint32_t dst, const CUtensorMap* m, uint32_t bar, int c0, int c1, int c2) {
    asm volatile("cp.async.bulk.tensor.3d.shared::cluster.global.mbarrier::complete_tx::bytes.multicast::cluster [%0], [%1, {%3, %4, %5}], [%2], %6;"
                 ::"r"(dst), "l"(m), "r"(bar), "r"(c0), "r"(c1), "r"(c2), "h"((uint16_t)3) : "memory");
}
__device__ __forceinline__ void tma5_mc(uint32_t dst, const CUtensorMap* m, uint32_t bar, int c0, int c1, int c2, int c3, int c4) {
    asm volatile("cp.async.bulk.tensor.5d.shared::cluster.global.mbarrier::complete_tx::bytes.multicast::cluster [%0], [%1, {%3, %4, %5, %6, %7}], [%2], %8;"
                 ::"r"(dst), "l"(m), "r"(bar), "r"(c0), "r"(c1), "r"(c2), "r"(c3), "r"(c4), "h"((uint16_t)3) : "memory");
}
__device__ __forceinline__ void tma2_pf(const CUtensorMap* m, int c0, int c1) {
    asm volatile("cp.async.bulk.prefetch.tensor.2d.L2.global [%0, {%1, %2}];" ::"l"(m), "r"(c0), "r"(c1) : "memory");
}
__device__ __forceinline__ void bulk_store(void* dst, uint32_t src, uint32_t bytes) {
    asm volatile("cp.async.bulk.global.shared::cta.bulk_group [%0], [%1], %2;" ::"l"(dst), "r"(src), "r"(bytes) : "memory");
}
__device__ __forceinline__ void tma4_store(const CUtensorMap* m, uint32_t src, int c2, int c3) {
    asm volatile("cp.async.bulk.tensor.4d.global.shared::cta.bulk_group [%0, {%2, %2, %3, %4}], [%1];"
                 ::"l"(m), "r"(src), "r"(0), "r"(c2), "r"(c3) : "memory");
}
__device__ __forceinline__ void bulk_commit() { asm volatile("cp.async.bulk.commit_group;" ::: "memory"); }
__device__ __forceinline__ void bulk_wait_read() { asm volatile("cp.async.bulk.wait_group.read 0;" ::: "memory"); }
__device__ __forceinline__ void fence_async_smem() { asm volatile("fence.proxy.async.shared::cta;" ::: "memory"); }
__device__ __forceinline__ void bulk_load(uint32_t dst, const void* src, uint32_t bytes, uint32_t bar) {
    asm volatile("cp.async.bulk.shared::cluster.global.mbarrier::complete_tx::bytes [%0], [%1], %2, [%3];"
                 ::"r"(dst), "l"(src), "r"(bytes), "r"(bar) : "memory");
}
__device__ __forceinline__ unsigned atom_exch(unsigned* p, unsigned v) {
    unsigned r;
    asm volatile("atom.relaxed.gpu.global.exch.b32 %0, [%1], %2;" : "=r"(r) : "l"(p), "r"(v) : "memory");
    return r;
}
__device__ __forceinline__ void st_async32(uint32_t a, uint32_t v, uint32_t bar) {
    asm volatile("st.async.shared::cluster.mbarrier::complete_tx::bytes.u32 [%0], %1, [%2];" ::"r"(a), "r"(v), "r"(bar) : "memory");
}
__device__ __forceinline__ void sts128f(uint32_t a, float x, float y, float z, float w) {
    asm volatile("st.shared.v4.f32 [%0], {%1, %2, %3, %4};" ::"r"(a), "f"(x), "f"(y), "f"(z), "f"(w) : "memory");
}
__device__ __forceinline__ void prefetch_map(const CUtensorMap* m) {
    asm volatile("prefetch.tensormap [%0];" ::"l"(m) : "memory");
}

__device__ __forceinline__ void prefetch_l2(const void* p, uint32_t bytes) {
    asm volatile("cp.async.bulk.prefetch.L2.global [%0], %1;" ::"l"(p), "r"(bytes) : "memory");
}

__device__ __forceinline__ void wgmma_fence() { asm volatile("wgmma.fence.sync.aligned;" ::: "memory"); }
__device__ __forceinline__ void wgmma_commit() { asm volatile("wgmma.commit_group.sync.aligned;" ::: "memory"); }
template <int N>
__device__ __forceinline__ void wgmma_wait() { asm volatile("wgmma.wait_group.sync.aligned %0;" ::"n"(N) : "memory"); }

__device__ __forceinline__ uint32_t pack_bf16(float lo, float hi) {
    uint32_t r;
    asm("cvt.rn.bf16x2.f32 %0, %1, %2;" : "=r"(r) : "f"(hi), "f"(lo));
    return r;
}
__device__ __forceinline__ uint32_t pack_f16(float lo, float hi) {
    uint32_t r;
    asm("cvt.rn.f16x2.f32 %0, %1, %2;" : "=r"(r) : "f"(hi), "f"(lo));
    return r;
}
__device__ __forceinline__ uint32_t pack_bf16_v(float lo, float hi) {
    uint32_t r;
    asm volatile("cvt.rn.bf16x2.f32 %0, %1, %2;" : "=r"(r) : "f"(hi), "f"(lo));
    return r;
}
template <int LUT>
__device__ __forceinline__ uint32_t lop3(uint32_t a, uint32_t b, uint32_t c) {
    uint32_t r;
    asm("lop3.b32 %0, %1, %2, %3, %4;" : "=r"(r) : "r"(a), "r"(b), "r"(c), "n"(LUT));
    return r;
}
__device__ __forceinline__ float bf_lo(uint32_t v) { return __uint_as_float(v << 16); }
__device__ __forceinline__ float bf_hi(uint32_t v) { return __uint_as_float(v & 0xffff0000u); }
__device__ __forceinline__ float bf16_round(float v) { return __bfloat162float(__float2bfloat16_rn(v)); }
__device__ __forceinline__ uint32_t bf2_mul(uint32_t a, uint32_t b) {
    uint32_t r;
    asm("mul.rn.bf16x2 %0, %1, %2;" : "=r"(r) : "r"(a), "r"(b));
    return r;
}
__device__ __forceinline__ uint32_t bf2_add_relu(uint32_t a, uint32_t b) {
    uint32_t r;
    asm("fma.rn.relu.bf16x2 %0, %1, %2, %3;" : "=r"(r) : "r"(a), "r"(0x3f803f80u), "r"(b));
    return r;
}
__device__ __forceinline__ uint4 ldg128(const void* p) {
    uint4 v;
    asm volatile("ld.global.nc.v4.u32 {%0, %1, %2, %3}, [%4];" : "=r"(v.x), "=r"(v.y), "=r"(v.z), "=r"(v.w) : "l"(p));
    return v;
}
__device__ __forceinline__ uint32_t ldg32(const void* p) {
    uint32_t v;
    asm volatile("ld.global.nc.u32 %0, [%1];" : "=r"(v) : "l"(p));
    return v;
}
__device__ __forceinline__ uint32_t ldg32na(const void* p) {
    uint32_t v;
    asm volatile("ld.global.nc.L1::no_allocate.u32 %0, [%1];" : "=r"(v) : "l"(p));
    return v;
}
__device__ __forceinline__ uint32_t ldg16(const __nv_bfloat16* p) {
    uint32_t v;
    asm volatile("ld.global.nc.u16 %0, [%1];" : "=r"(v) : "l"(p));
    return v;
}
__device__ __forceinline__ uint4 ld_relaxed128(const void* p) {
    uint4 v;
    asm volatile("ld.relaxed.gpu.global.v4.u32 {%0, %1, %2, %3}, [%4];" : "=r"(v.x), "=r"(v.y), "=r"(v.z), "=r"(v.w) : "l"(p) : "memory");
    return v;
}
__device__ __forceinline__ uint2 ld_relaxed64(const void* p) {
    unsigned long long v;
    asm volatile("ld.relaxed.gpu.global.u64 %0, [%1];" : "=l"(v) : "l"(p) : "memory");
    return make_uint2((uint32_t)v, (uint32_t)(v >> 32));
}
__device__ __forceinline__ void st_relaxed64(void* p, uint32_t lo, uint32_t hi) {
    unsigned long long v = ((unsigned long long)hi << 32) | lo;
    asm volatile("st.relaxed.gpu.global.u64 [%0], %1;" ::"l"(p), "l"(v) : "memory");
}
__device__ __forceinline__ void st_relaxed2x64(void* p, uint32_t a, uint32_t b, uint32_t c, uint32_t d) {
    unsigned long long v0 = ((unsigned long long)b << 32) | a, v1 = ((unsigned long long)d << 32) | c;
    asm volatile("st.relaxed.gpu.global.v2.u64 [%0], {%1, %2};" ::"l"(p), "l"(v0), "l"(v1) : "memory");
}
__device__ __forceinline__ uint4 ld_relaxed2x64(const void* p) {
    unsigned long long v0, v1;
    asm volatile("ld.relaxed.gpu.global.v2.u64 {%0, %1}, [%2];" : "=l"(v0), "=l"(v1) : "l"(p) : "memory");
    return make_uint4((uint32_t)v0, (uint32_t)(v0 >> 32), (uint32_t)v1, (uint32_t)(v1 >> 32));
}
__device__ __forceinline__ void stg128(void* p, uint32_t a, uint32_t b, uint32_t c, uint32_t d) {
    asm volatile("st.global.v4.u32 [%0], {%1, %2, %3, %4};" ::"l"(p), "r"(a), "r"(b), "r"(c), "r"(d) : "memory");
}
__device__ __forceinline__ void stg64f(void* p, float a, float b) {
    asm volatile("st.global.v2.f32 [%0], {%1, %2};" ::"l"(p), "f"(a), "f"(b) : "memory");
}
__device__ __forceinline__ uint4 lds128(uint32_t a) {
    uint4 v;
    asm volatile("ld.shared.v4.u32 {%0, %1, %2, %3}, [%4];" : "=r"(v.x), "=r"(v.y), "=r"(v.z), "=r"(v.w) : "r"(a) : "memory");
    return v;
}
__device__ __forceinline__ uint2 lds64(uint32_t a) {
    uint2 v;
    asm volatile("ld.shared.v2.u32 {%0, %1}, [%2];" : "=r"(v.x), "=r"(v.y) : "r"(a) : "memory");
    return v;
}
__device__ __forceinline__ uint4 ldsm4(uint32_t a) {
    uint4 v;
    asm volatile("ldmatrix.sync.aligned.m8n8.x4.shared.b16 {%0, %1, %2, %3}, [%4];" : "=r"(v.x), "=r"(v.y), "=r"(v.z), "=r"(v.w) : "r"(a) : "memory");
    return v;
}
__device__ __forceinline__ uint32_t lds16(uint32_t a) {
    uint32_t v;
    asm volatile("ld.shared.u16 %0, [%1];" : "=r"(v) : "r"(a) : "memory");
    return v;
}
__device__ __forceinline__ void sts16(uint32_t a, uint32_t x) {
    asm volatile("st.shared.u16 [%0], %1;" ::"r"(a), "h"((uint16_t)x) : "memory");
}
__device__ __forceinline__ void st_relaxed32(void* p, uint32_t v) {
    asm volatile("st.relaxed.gpu.global.u32 [%0], %1;" ::"l"(p), "r"(v) : "memory");
}
__device__ __forceinline__ float lds32f(uint32_t a) {
    float v;
    asm volatile("ld.shared.f32 %0, [%1];" : "=f"(v) : "r"(a) : "memory");
    return v;
}
__device__ __forceinline__ void sts128(uint32_t a, uint32_t x, uint32_t y, uint32_t z, uint32_t w) {
    asm volatile("st.shared.v4.u32 [%0], {%1, %2, %3, %4};" ::"r"(a), "r"(x), "r"(y), "r"(z), "r"(w) : "memory");
}
__device__ __forceinline__ void sts64f(uint32_t a, float x, float y) {
    asm volatile("st.shared.v2.f32 [%0], {%1, %2};" ::"r"(a), "f"(x), "f"(y) : "memory");
}
__device__ __forceinline__ float4 lds128f(uint32_t a) {
    float4 v;
    asm volatile("ld.shared.v4.f32 {%0, %1, %2, %3}, [%4];" : "=f"(v.x), "=f"(v.y), "=f"(v.z), "=f"(v.w) : "r"(a) : "memory");
    return v;
}
__device__ __forceinline__ uint32_t lds32(uint32_t a) {
    uint32_t v;
    asm volatile("ld.shared.u32 %0, [%1];" : "=r"(v) : "r"(a) : "memory");
    return v;
}
__device__ __forceinline__ void sts32(uint32_t a, uint32_t x) {
    asm volatile("st.shared.u32 [%0], %1;" ::"r"(a), "r"(x) : "memory");
}
__device__ __forceinline__ void stg128f(void* p, float a, float b, float c, float d) {
    asm volatile("st.global.v4.f32 [%0], {%1, %2, %3, %4};" ::"l"(p), "f"(a), "f"(b), "f"(c), "f"(d) : "memory");
}
__device__ __forceinline__ unsigned ld_relaxed32(const unsigned* p) {
    unsigned v;
    asm volatile("ld.relaxed.gpu.global.u32 %0, [%1];" : "=r"(v) : "l"(p) : "memory");
    return v;
}
__device__ __forceinline__ void wait_counter(const unsigned* p, unsigned target) {
    unsigned n = 0, v;
    while (true) {
        asm volatile("ld.acquire.gpu.global.u32 %0, [%1];" : "=r"(v) : "l"(p) : "memory");
        if ((int)(v - target) >= 0) break;
        if (++n > kSpinLimit) TRAP();
        __nanosleep(32);
    }
}
#define KT(IT, W) do { } while (0)
#define STAMP(cond, slot) do { } while (0)
#define STAMPA(cond, slot) STAMP(cond, slot)
#define STAMPB(cond, slot) do { } while (0)

template <int TA, int TB>
__device__ __forceinline__ void wgmma_n256(float (&d)[128], uint64_t da, uint64_t db, int keep) {
    asm volatile(
        "{\n.reg .pred p;\nsetp.ne.b32 p, %132, 0;\n"
        "wgmma.mma_async.sync.aligned.m64n256k16.f32.bf16.bf16 "
        "{%0, %1, %2, %3, %4, %5, %6, %7, %8, %9, %10, %11, %12, %13, %14, %15, "
        "%16, %17, %18, %19, %20, %21, %22, %23, %24, %25, %26, %27, %28, %29, %30, %31, "
        "%32, %33, %34, %35, %36, %37, %38, %39, %40, %41, %42, %43, %44, %45, %46, %47, "
        "%48, %49, %50, %51, %52, %53, %54, %55, %56, %57, %58, %59, %60, %61, %62, %63, "
        "%64, %65, %66, %67, %68, %69, %70, %71, %72, %73, %74, %75, %76, %77, %78, %79, "
        "%80, %81, %82, %83, %84, %85, %86, %87, %88, %89, %90, %91, %92, %93, %94, %95, "
        "%96, %97, %98, %99, %100, %101, %102, %103, %104, %105, %106, %107, %108, %109, %110, %111, "
        "%112, %113, %114, %115, %116, %117, %118, %119, %120, %121, %122, %123, %124, %125, %126, %127}, "
        "%128, %129, p, 1, 1, %130, %131;\n}\n"
        : "+f"(d[0]), "+f"(d[1]), "+f"(d[2]), "+f"(d[3]), "+f"(d[4]), "+f"(d[5]), "+f"(d[6]), "+f"(d[7]),
          "+f"(d[8]), "+f"(d[9]), "+f"(d[10]), "+f"(d[11]), "+f"(d[12]), "+f"(d[13]), "+f"(d[14]), "+f"(d[15]),
          "+f"(d[16]), "+f"(d[17]), "+f"(d[18]), "+f"(d[19]), "+f"(d[20]), "+f"(d[21]), "+f"(d[22]), "+f"(d[23]),
          "+f"(d[24]), "+f"(d[25]), "+f"(d[26]), "+f"(d[27]), "+f"(d[28]), "+f"(d[29]), "+f"(d[30]), "+f"(d[31]),
          "+f"(d[32]), "+f"(d[33]), "+f"(d[34]), "+f"(d[35]), "+f"(d[36]), "+f"(d[37]), "+f"(d[38]), "+f"(d[39]),
          "+f"(d[40]), "+f"(d[41]), "+f"(d[42]), "+f"(d[43]), "+f"(d[44]), "+f"(d[45]), "+f"(d[46]), "+f"(d[47]),
          "+f"(d[48]), "+f"(d[49]), "+f"(d[50]), "+f"(d[51]), "+f"(d[52]), "+f"(d[53]), "+f"(d[54]), "+f"(d[55]),
          "+f"(d[56]), "+f"(d[57]), "+f"(d[58]), "+f"(d[59]), "+f"(d[60]), "+f"(d[61]), "+f"(d[62]), "+f"(d[63]),
          "+f"(d[64]), "+f"(d[65]), "+f"(d[66]), "+f"(d[67]), "+f"(d[68]), "+f"(d[69]), "+f"(d[70]), "+f"(d[71]),
          "+f"(d[72]), "+f"(d[73]), "+f"(d[74]), "+f"(d[75]), "+f"(d[76]), "+f"(d[77]), "+f"(d[78]), "+f"(d[79]),
          "+f"(d[80]), "+f"(d[81]), "+f"(d[82]), "+f"(d[83]), "+f"(d[84]), "+f"(d[85]), "+f"(d[86]), "+f"(d[87]),
          "+f"(d[88]), "+f"(d[89]), "+f"(d[90]), "+f"(d[91]), "+f"(d[92]), "+f"(d[93]), "+f"(d[94]), "+f"(d[95]),
          "+f"(d[96]), "+f"(d[97]), "+f"(d[98]), "+f"(d[99]), "+f"(d[100]), "+f"(d[101]), "+f"(d[102]), "+f"(d[103]),
          "+f"(d[104]), "+f"(d[105]), "+f"(d[106]), "+f"(d[107]), "+f"(d[108]), "+f"(d[109]), "+f"(d[110]), "+f"(d[111]),
          "+f"(d[112]), "+f"(d[113]), "+f"(d[114]), "+f"(d[115]), "+f"(d[116]), "+f"(d[117]), "+f"(d[118]), "+f"(d[119]),
          "+f"(d[120]), "+f"(d[121]), "+f"(d[122]), "+f"(d[123]), "+f"(d[124]), "+f"(d[125]), "+f"(d[126]), "+f"(d[127])
        : "l"(da), "l"(db), "n"(TA), "n"(TB), "r"(keep));
}
template <int TA, int TB>
__device__ __forceinline__ void wgmma_n192(float (&d)[128], uint64_t da, uint64_t db, int keep) {
    asm volatile(
        "{\n.reg .pred p;\nsetp.ne.b32 p, %100, 0;\n"
        "wgmma.mma_async.sync.aligned.m64n192k16.f32.bf16.bf16 "
        "{%0, %1, %2, %3, %4, %5, %6, %7, %8, %9, %10, %11, %12, %13, %14, %15, "
        "%16, %17, %18, %19, %20, %21, %22, %23, %24, %25, %26, %27, %28, %29, %30, %31, "
        "%32, %33, %34, %35, %36, %37, %38, %39, %40, %41, %42, %43, %44, %45, %46, %47, "
        "%48, %49, %50, %51, %52, %53, %54, %55, %56, %57, %58, %59, %60, %61, %62, %63, "
        "%64, %65, %66, %67, %68, %69, %70, %71, %72, %73, %74, %75, %76, %77, %78, %79, "
        "%80, %81, %82, %83, %84, %85, %86, %87, %88, %89, %90, %91, %92, %93, %94, %95}, "
        "%96, %97, p, 1, 1, %98, %99;\n}\n"
        : "+f"(d[0]), "+f"(d[1]), "+f"(d[2]), "+f"(d[3]), "+f"(d[4]), "+f"(d[5]), "+f"(d[6]), "+f"(d[7]),
          "+f"(d[8]), "+f"(d[9]), "+f"(d[10]), "+f"(d[11]), "+f"(d[12]), "+f"(d[13]), "+f"(d[14]), "+f"(d[15]),
          "+f"(d[16]), "+f"(d[17]), "+f"(d[18]), "+f"(d[19]), "+f"(d[20]), "+f"(d[21]), "+f"(d[22]), "+f"(d[23]),
          "+f"(d[24]), "+f"(d[25]), "+f"(d[26]), "+f"(d[27]), "+f"(d[28]), "+f"(d[29]), "+f"(d[30]), "+f"(d[31]),
          "+f"(d[32]), "+f"(d[33]), "+f"(d[34]), "+f"(d[35]), "+f"(d[36]), "+f"(d[37]), "+f"(d[38]), "+f"(d[39]),
          "+f"(d[40]), "+f"(d[41]), "+f"(d[42]), "+f"(d[43]), "+f"(d[44]), "+f"(d[45]), "+f"(d[46]), "+f"(d[47]),
          "+f"(d[48]), "+f"(d[49]), "+f"(d[50]), "+f"(d[51]), "+f"(d[52]), "+f"(d[53]), "+f"(d[54]), "+f"(d[55]),
          "+f"(d[56]), "+f"(d[57]), "+f"(d[58]), "+f"(d[59]), "+f"(d[60]), "+f"(d[61]), "+f"(d[62]), "+f"(d[63]),
          "+f"(d[64]), "+f"(d[65]), "+f"(d[66]), "+f"(d[67]), "+f"(d[68]), "+f"(d[69]), "+f"(d[70]), "+f"(d[71]),
          "+f"(d[72]), "+f"(d[73]), "+f"(d[74]), "+f"(d[75]), "+f"(d[76]), "+f"(d[77]), "+f"(d[78]), "+f"(d[79]),
          "+f"(d[80]), "+f"(d[81]), "+f"(d[82]), "+f"(d[83]), "+f"(d[84]), "+f"(d[85]), "+f"(d[86]), "+f"(d[87]),
          "+f"(d[88]), "+f"(d[89]), "+f"(d[90]), "+f"(d[91]), "+f"(d[92]), "+f"(d[93]), "+f"(d[94]), "+f"(d[95])
        : "l"(da), "l"(db), "n"(TA), "n"(TB), "r"(keep));
}
template <int TA, int TB, int O>
__device__ __forceinline__ void wgmma_n64(float (&d)[128], uint64_t da, uint64_t db, int keep) {
    asm volatile(
        "{\n.reg .pred p;\nsetp.ne.b32 p, %36, 0;\n"
        "wgmma.mma_async.sync.aligned.m64n64k16.f32.bf16.bf16 "
        "{%0, %1, %2, %3, %4, %5, %6, %7, %8, %9, %10, %11, %12, %13, %14, %15, "
        "%16, %17, %18, %19, %20, %21, %22, %23, %24, %25, %26, %27, %28, %29, %30, %31}, "
        "%32, %33, p, 1, 1, %34, %35;\n}\n"
        : "+f"(d[O + 0]), "+f"(d[O + 1]), "+f"(d[O + 2]), "+f"(d[O + 3]), "+f"(d[O + 4]), "+f"(d[O + 5]), "+f"(d[O + 6]), "+f"(d[O + 7]),
          "+f"(d[O + 8]), "+f"(d[O + 9]), "+f"(d[O + 10]), "+f"(d[O + 11]), "+f"(d[O + 12]), "+f"(d[O + 13]), "+f"(d[O + 14]), "+f"(d[O + 15]),
          "+f"(d[O + 16]), "+f"(d[O + 17]), "+f"(d[O + 18]), "+f"(d[O + 19]), "+f"(d[O + 20]), "+f"(d[O + 21]), "+f"(d[O + 22]), "+f"(d[O + 23]),
          "+f"(d[O + 24]), "+f"(d[O + 25]), "+f"(d[O + 26]), "+f"(d[O + 27]), "+f"(d[O + 28]), "+f"(d[O + 29]), "+f"(d[O + 30]), "+f"(d[O + 31])
        : "l"(da), "l"(db), "n"(TA), "n"(TB), "r"(keep));
}
template <int O>
__device__ __forceinline__ void wgmma_n64_rs(float (&d)[128], uint32_t a0, uint32_t a1, uint32_t a2, uint32_t a3, uint64_t db) {
    asm volatile(
        "{\n.reg .pred p;\nsetp.ne.b32 p, 1, 0;\n"
        "wgmma.mma_async.sync.aligned.m64n64k16.f32.bf16.bf16 "
        "{%0, %1, %2, %3, %4, %5, %6, %7, %8, %9, %10, %11, %12, %13, %14, %15, "
        "%16, %17, %18, %19, %20, %21, %22, %23, %24, %25, %26, %27, %28, %29, %30, %31}, "
        "{%32, %33, %34, %35}, %36, p, 1, 1, 1;\n}\n"
        : "+f"(d[O + 0]), "+f"(d[O + 1]), "+f"(d[O + 2]), "+f"(d[O + 3]), "+f"(d[O + 4]), "+f"(d[O + 5]), "+f"(d[O + 6]), "+f"(d[O + 7]),
          "+f"(d[O + 8]), "+f"(d[O + 9]), "+f"(d[O + 10]), "+f"(d[O + 11]), "+f"(d[O + 12]), "+f"(d[O + 13]), "+f"(d[O + 14]), "+f"(d[O + 15]),
          "+f"(d[O + 16]), "+f"(d[O + 17]), "+f"(d[O + 18]), "+f"(d[O + 19]), "+f"(d[O + 20]), "+f"(d[O + 21]), "+f"(d[O + 22]), "+f"(d[O + 23]),
          "+f"(d[O + 24]), "+f"(d[O + 25]), "+f"(d[O + 26]), "+f"(d[O + 27]), "+f"(d[O + 28]), "+f"(d[O + 29]), "+f"(d[O + 30]), "+f"(d[O + 31])
        : "r"(a0), "r"(a1), "r"(a2), "r"(a3), "l"(db));
}

constexpr uint64_t kDescHi = (uint64_t)(64u | 0x40000000u) << 32;
template <int MODE>
__device__ __forceinline__ void mma_kblock(float (&acc)[128], uint32_t a_lo, uint32_t b_lo, int keep) {
    constexpr uint32_t HALF = (MODE == 1) ? 12288u : 16384u;
    constexpr bool BN = (MODE == 1 || MODE == 2);
#pragma unroll
    for (int kk = 0; kk < 4; ++kk) {
        const uint32_t ao = (MODE == 3) ? kk * 2048u : kk * 32u;
        const uint32_t bo = BN ? ((kk >> 1) * HALF + (kk & 1) * 2048u) : kk * 32u;
        const uint64_t da = kDescHi | (uint64_t)(a_lo + (ao >> 4) + (1u << 16));
        const uint64_t db = kDescHi | (uint64_t)(b_lo + (bo >> 4) + (BN ? (256u << 16) : (1u << 16)));
        if (MODE == 1) wgmma_n192<0, 1>(acc, da, db, kk == 0 ? keep : 1);
        else wgmma_n256<(MODE == 3), BN>(acc, da, db, kk == 0 ? keep : 1);
    }
}

struct Params {
    Scratch* s;
    const __nv_bfloat16* x;
    const __nv_bfloat16* b_re;
    const __nv_bfloat16* b_im;
    const __nv_bfloat16* gate_w;
    const __nv_bfloat16* lam_re;
    const __nv_bfloat16* lam_im;
    const __nv_bfloat16* log_dt;
    const __nv_bfloat16* dskip;
    const __nv_bfloat16* b1;
    const __nv_bfloat16* b2;
    int swap;
};

#define CMUL(rr, ri, ar, ai, br, bi) do { float _r = (ar) * (br) - (ai) * (bi); float _i = (ar) * (bi) + (ai) * (br); rr = _r; ri = _i; } while (0)
#define CFMA(rr, ri, ar, ai, br, bi) do { float _r = fmaf(-(ai), (bi), fmaf((ar), (br), rr)); float _i = fmaf((ai), (br), fmaf((ar), (bi), ri)); rr = _r; ri = _i; } while (0)

#define KB_OPEN(IT, LAST)                                                                        \
    KT(IT, 0);                                                                                   \
    if (ORDER && (LAST) && wg == 1) bar_sync(7, 256);                                            \
    mbar_wait(bar_full + 8 * ((IT) & 3), ((IT) >> 2) & 1);                                \
    KT(IT, 1);
#define KB_CLOSE(IT, LAST, REL)                                                                  \
    if (ORDER && (LAST) && wg == 0) bar_arrive(7, 256);                                          \
    wgmma_wait<1>();                                                                             \
    if (lane < 2 && (REL)) mbar_arrive_cluster(rel_addr + 8 * (((IT) - 1) & 3));
#define KBLOCK(MODE, IT, FIRST, LAST)                                                            \
    {                                                                                            \
        const uint32_t so = ((IT) & 3) * (kStageBytes >> 4);                                     \
        KB_OPEN(IT, LAST);                                                                       \
        wgmma_fence();                                                                           \
        mma_kblock<MODE>(acc, a_lo + so, b_lo + so, !(FIRST));                                   \
        wgmma_commit();                                                                          \
        KB_CLOSE(IT, LAST, !(FIRST));                                                            \
    }
#define TILE_END() do { wgmma_wait<0>(); if (lane < 2) mbar_arrive_cluster(rel_addr + 24); } while (0)

__global__ void __cluster_dims__(2, 1, 1) __launch_bounds__(384, 1)
fused_kernel(const __grid_constant__ CUtensorMap mB, const __grid_constant__ CUtensorMap mXs, const __grid_constant__ CUtensorMap mXf,
             const __grid_constant__ CUtensorMap mW1b, const __grid_constant__ CUtensorMap mW1a, const __grid_constant__ CUtensorMap mHs,
             const __grid_constant__ CUtensorMap mHf, const __grid_constant__ CUtensorMap mCre, const __grid_constant__ CUtensorMap mCim,
             const __grid_constant__ CUtensorMap mW2, const __grid_constant__ CUtensorMap mW2n, const __grid_constant__ CUtensorMap mW2p,
             const __grid_constant__ CUtensorMap mHf3, const __grid_constant__ CUtensorMap mOut, const Params p) {
    extern __shared__ __align__(1024) uint8_t smem_raw[];
    if (PFTOP) { prefetch_map(&mB); prefetch_map(&mXs); }
    const uint32_t sbase = smem_u32(smem_raw);
    if ((sbase & 0x3ffffu) != kSmemOrg) return;
    const uint32_t bar_full = sbase + kBarOff, bar_empty = bar_full + 32, bar_dep = bar_full + 64;
    const uint32_t bar_x = bar_full + 88, bar_c = bar_full + 96, role_s = bar_full + 104, bar_role = bar_full + 120, tag_s = bar_full + 112 + (threadIdx.x & 1) * 4;

    const int tid = threadIdx.x, lane = tid & 31;
    const int warp = __shfl_sync(0xffffffffu, tid >> 5, 0);
    const uint32_t rank = blockIdx.x & 1;

    int pref;
    {
        unsigned smid;
        asm("mov.u32 %0, %%smid;" : "=r"(smid));
        const int t = smid >> 1, u = t - 32, d = (u * 37) >> 8;
        pref = (t < 32) ? (t & 7) * 8 + (t >> 3) : (t < 60) ? (1 + u - 7 * d) * 8 + 4 + d : ((t - 58) & 7);
    }
    STAMP(tid == 0, 0);
    int role = pref;
#define ROLE_VARS()                                                                                               \
    const int c = role >> 3;                                                             \
    const int j8 = role & 7;                                                        \
    const int cb = j8 * 2 + (int)rank;                                             \
    const int rb = 2 * c + (int)rank;                                               \
    const int kh = j8 >> 2;                 \
    const int colK = (j8 & 3) * 256 + kh * 128, colS = colK ^ 128;    \
    (void)cb; (void)rb; (void)colS;

#define INIT_ALL()                                                                                    \
    if (warp == INITW && elect_one()) {                                                               \
        if (!PFTOP) { prefetch_map(&mB); prefetch_map(&mXs); }                                        \
        _Pragma("unroll") for (int s = 0; s < kStages; ++s) {                                         \
            mbar_init(bar_full + 8 * s, 1);                                                           \
            mbar_init(bar_empty + 8 * s, 16);                                                         \
            mbar_init(bar_dep + 8 * s, 1);                                \
        }                                                                                             \
        mbar_init(bar_c, 96);                                                                         \
        mbar_init(bar_role, 1);                                                                       \
        asm volatile("fence.mbarrier_init.release.cluster;\nfence.proxy.async.shared::cta;" ::: "memory"); \
        mbar_expect_tx(bar_full, 49152);            \
        tma4(sbase, &mB, bar_full, 0, 0, 0, ((pref & 7) * 2 + (int)rank) * 8);                        \
        if (!MC0) {                                                                                   \
        tma5(sbase + kABytes, &mXs, bar_full, 0, 0, 0, 0, pref >> 3);                                 \
        tma5(sbase + kABytes + 16384, &mXs, bar_full, 0, 0, 0, 16, pref >> 3);                        \
        }                                                                                             \
        mbar_expect_tx(bar_x, 2048);                                                                  \
        bulk_load(sbase + kXOff, p.gate_w, 2048, bar_x);                                              \
        mbar_expect_tx(bar_role, 8);                                                                  \
    }
    if (PRODCOND) {
        asm volatile("setmaxnreg.dec.sync.aligned.u32 24;");
        unsigned taken = 0;
        if (tid == 352 && rank == 0) {
            taken = atom_exch(&p.s->claim[pref], 1u);
        }
        __syncwarp();
        cluster_arrive();
        cluster_wait();
        if (warp > 8) {
            if (tid == 352) {
#pragma unroll 1
                for (int i = 0; taken != 0 && i < 64; ++i) { role = i + 256; taken = atom_exch(&p.s->claim[i], 1u); }
                st_async32(mapa(role_s + 4 * rank, 0), role, mapa(bar_role, 0));
                st_async32(mapa(role_s + 4 * rank, 1), role, mapa(bar_role, 1));
            }
            __syncwarp();
            mbar_wait(bar_role, 0);
            role = __shfl_sync(0xffffffffu, (int)lds32(role_s), 0) & 63;
            ROLE_VARS();
            if (warp == 11) {
                if (lane < 12) prefetch_map(&mXf + lane);
#pragma unroll 1
                for (int en = lane; en < 88; en += 32) {
                    const int J = en >> 2;
                    const __nv_bfloat16* src = ((J < 14) ? p.b1 : (J < 18) ? p.dskip : p.b2) + 32 * J + 2 * (en & 3) +
                                               ((J < 6) ? 2048 + 192 * j8 : (J < 14) ? 256 * j8 - 192 : colK - ((J < 18) ? 448 : 576));
                    sts128(sbase + kBiasOff + en * 16, ldg32(src), ldg32(src + 8), ldg32(src + 16), ldg32(src + 24));
                }
                mbar_arrive_local(bar_c);
            } else {
                {
                    sts32(tag_s, ld_relaxed32(&p.s->epoch) + 1);
                    const int ch = cb * 64 + (tid - 288);
                    const uint32_t t_s = sbase + kTabOff + (tid - 288) * 64;
                    const float Lr = bf_lo(ldg16(p.lam_re + ch)), Li = bf_lo(ldg16(p.lam_im + ch));
                    const float dt = bf16_round(expf(bf_lo(ldg16(p.log_dt + ch))));
                    const float ea = expf(dt * Lr);
                    float lr, li;
                    sincospif((dt * Li) * 0.31830988618379067f, &li, &lr);
                    lr *= ea; li *= ea;
                    const float nr = lr - 1.0f, ni = li;
                    const bool big = fabsf(Lr) >= fabsf(Li);
                    const float u = big ? Lr : Li, v = big ? Li : Lr;
                    const float t = v / u, d = 2.0f / fmaf(v, t, u);
                    const float cr = (big ? fmaf(ni, t, nr) : fmaf(nr, t, ni)) * d, ci = (big ? fmaf(-nr, t, ni) : fmaf(ni, t, -nr)) * d;
                    if (p.swap) li = -li;
                    const float m00 = p.swap ? -ci : cr, m01 = p.swap ? cr : -ci, m10 = p.swap ? -cr : -ci, m11 = p.swap ? -ci : -cr;
#pragma unroll
                    for (int q = 0; q < 4; ++q) {
                        sts128f(t_s + q * 16, lr, li, m00, m01);
                        sts128f(t_s + 12288 + q * 16, 0.f, 0.f, 0.f, 0.f);
                    }
#pragma unroll 1
                    for (int i = 0; i < 6; ++i) CMUL(lr, li, lr, li, lr, li);
                    float ar, ai, br, bi;
                    CMUL(ar, ai, lr, li, lr, li);
                    CMUL(br, bi, ar, ai, lr, li);
                    sts128f(t_s + 4096, m10, m11, 0.f, 0.f);
#pragma unroll
                    for (int q = 1; q < 4; ++q) sts128f(t_s + 4096 + q * 16, m10, m11, lr, li);
                    sts128f(t_s + 8192, 0.f, 0.f, 1.f, 0.f);
                    sts128f(t_s + 8192 + 16, 0.f, 0.f, lr, li);
                    sts128f(t_s + 8192 + 32, ar, ai, ar, ai);
                    sts128f(t_s + 8192 + 48, ar, ai, br, bi);
                    CMUL(ar, ai, ar, ai, ar, ai);
                    br = 1.f; bi = 0.f;
#pragma unroll 1
                    for (int k = c - 1; k >= 0; --k) {
                        sts64f(t_s + 12288 + (k & 3) * 16 + (k >> 2) * 8, br, bi);
                        CMUL(br, bi, br, bi, ar, ai);
                    }
                    mbar_arrive_local(bar_c);
                }
                if (warp == 9) {
#pragma unroll 1
                    for (int ev = 0; ev < 3; ++ev) {
                        if (ev == 2) {
                            uint8_t* box = p.s->X + (size_t)(role * 2 + rank) * kXBytes + lane * 16;
#pragma unroll 1
                            for (int i = 0; i < kXBytes; i += 512) stg128(box + i, 0, 0, 0, 0);
                        }
                        bar_sync(3 + ev, 288);
                        if (lane == 0) {
                            unsigned* cnt = &p.s->cnt[(ev == 0 ? c : 16 * ev - 8 + rb) * 32];
                            asm volatile("fence.acq_rel.gpu;\nfence.proxy.async.global;" ::: "memory");
                            asm volatile("red.relaxed.gpu.global.add.u32 [%0], 1;" ::"l"(cnt) : "memory");
                        }
                        __syncwarp();
                    }
                } else if (lane == 0) {
                    const unsigned tag = lds32(tag_s);
#pragma unroll 1
                    for (int ev = 0; ev < 3; ++ev) {
                        wait_counter(&p.s->cnt[(ev == 0 ? c : 16 * ev - 8 + rb) * 32], tag * (ev == 0 ? 16u : 8u));
                        mbar_arrive_local(bar_dep + 8 * ev);
                        if (ev == 0 && atomicInc(&p.s->done, 127u) == 127u) {
                            st_relaxed32(&p.s->epoch, tag);
#pragma unroll 1
                            for (int i = 0; i < 64; i += 4) stg128(&p.s->claim[i], 0, 0, 0, 0);
                        }
                    }
                }
            }
        } else if (elect_one()) {
            int it = 1, again = 15;
            if (MC0) tma5_mc(sbase + kABytes + rank * 16384, &mXs, bar_full, 0, 0, 0, rank * 16, role >> 3);
#define ACQUIRE(BYTES)                                                   \
    const uint32_t st = sbase + (it & 3) * kStageBytes, fb = bar_full + 8 * (it & 3); \
    mbar_wait(bar_empty + 8 * (it & 3), ((it >> 2) & 1) ^ 1);     \
    mbar_expect_tx(fb, BYTES);
#pragma unroll 1
            for (; it < 16; ++it) {
                ACQUIRE(49152);
                tma4(st, &mB, fb, it * 64, 0, 0, ((role & 7) * 2 + (int)rank) * 8);
                tma5_mc(st + kABytes + rank * 16384, &mXs, fb, it * 64, 0, 0, rank * 16, role >> 3);
                if (it == again) {
                    mbar_wait(bar_role, 0);
                    const uint2 fin = lds64(role_s);
                    role = fin.x & 63;
                    if (fin.x != fin.y) { it = -1; again = 16; }
                }
            }
            ROLE_VARS();
#pragma unroll 1
            for (; it < 48; ++it) {
                const bool t1 = it < 32;
                const int k0 = (it & 15) * 64;
                ACQUIRE(t1 ? 40960 : 49152);
                tma5(st, &mXf, fb, k0, 0, 0, rank * 4, c);
                tma3_mc(st + kABytes + rank * (t1 ? 12288 : 16384), t1 ? &mW1b : &mW1a, fb, 0, k0 + rank * 32, t1 ? 32 + 3 * j8 : 4 * j8);
                if ((it & ~2) == XLDKB) {
                    const int h = (it >> 1) & 1;
                    if (h == 0) mbar_expect_tx(bar_x, 32768);
                    tma5(sbase + kXOff + h * 16384, &mXf, bar_x, colK + h * 64, 0, 0, rank * 4, c);
                }
            }
            STAMPA(true, 8);
            mbar_wait(bar_dep, 0);
            asm volatile("fence.proxy.async.global;" ::: "memory");
            STAMPA(true, 9);
#pragma unroll 1
            for (; it < 64; ++it) {
                const int k0 = (it & 15) * 64;
                ACQUIRE(49152);
                tma3(st, &mHs, fb, 0, kh * 1024 + k0, rb * 2);
                tma2_mc(st + kABytes + rank * 16384, kh ? &mCim : &mCre, fb, k0, rank ? colS : colK);
            }
            int f0 = 2048 + 768 * kh;
#pragma unroll 1
            for (; it < 88; ++it, f0 += 64) {
                if (it == 64 || it == 76) {
                    mbar_wait(bar_dep + (it == 64 ? 8 : 16), 0);
                    asm volatile("fence.proxy.async.global;" ::: "memory");
                    if (it == 76) f0 = 1024 * kh;
                }
                if (f0 == 256 * j8) f0 += 256;
                ACQUIRE(49152);
                tma2(st, &mHf, fb, f0, rb * 128);
                tma5_mc(st + kABytes + rank * 16384, &mW2, fb, 0, 0, (f0 >> 3) + 4 * rank, 0, colK >> 6);
                tma5_mc(st + kABytes + rank * 16384 + 8192, &mW2, fb, 0, 0, (f0 >> 3) + 4 * rank, 0, colS >> 6);
                if ((it >> 2) == PFKB / 4) tma2_pf(&mW2n, colK + (it & 2) * 32, 256 * (j8 ^ ((it & 1) * 4)) + 128 * rank);
            }
#pragma unroll 1
            for (; it < kTotal; ++it) {
                const int h = (it & 2) * 32;
                ACQUIRE(49152);
                tma3(st, &mHf3, fb, 0, rb * 128 + h, 4 * (j8 ^ 4) + 2 * (it & 1));
                if (it & 1) tma5_mc(st + kABytes + rank * 16384, &mW2p, fb, colK + h, 0, 0, 0, 8 * (j8 ^ 4) + 4 * rank);
                else tma2_mc(st + kABytes + rank * 16384, &mW2n, fb, colK + h, 256 * j8 + 128 * rank);
            }
        }
    } else {
        INIT_ALL();
        if (warp >= 8 - PF0LINES) {
            const int row = blockIdx.x * 32 + lane;
            const __nv_bfloat16* src = (row < 2048) ? p.x : (row < 3072) ? p.b_re - 2048 * kD : p.b_im - 3072 * kD;
            asm volatile("prefetch.global.L2 [%0];" ::"l"(src + row * kD + (7 - warp) * 64) : "memory");
        }
        __syncwarp();
        cluster_arrive();
        asm volatile("setmaxnreg.inc.sync.aligned.u32 240;");
        const int wg = warp >> 2, w = warp & 3, r = lane >> 2, q = lane & 3, tw = tid & 127;
        uint32_t a_lo = (kSmemOrg + wg * 8192) >> 4;
        constexpr uint32_t b_lo = (kSmemOrg + kABytes) >> 4;
        const uint32_t rel_addr = mapa(bar_empty, (uint32_t)(lane & 1));
        const uint32_t gate_s = sbase + kGateOff;
        float acc[128];
        uint32_t pk[64];
        unsigned tag;
        UNDEF_R(tag);

#pragma unroll
        for (int i = 0; i < 128; ++i) UNDEF_F(acc[i]);
        float gs = 0.f;
        {
            const uint32_t gx_s = sbase + kABytes + (16 * rank + 2 * warp + (lane >> 4)) * 128 +
                                  ((((lane & 15) >> 1) ^ (2 * w + (lane >> 4))) << 4) + (lane & 1) * 8;
            const uint32_t gw_s = sbase + kXOff + (lane & 15) * 8;
            uint32_t again = 15;
            cluster_wait();
#pragma unroll 1
            for (uint32_t it = 0; it < 16; ++it) {
                const uint32_t so = (it & 3) * (kStageBytes >> 4);
                KB_OPEN(it, it == 15);
                wgmma_fence();
                mma_kblock<0>(acc, a_lo + so, b_lo + so, it != 0);
                wgmma_commit();
                KB_CLOSE(it, it == 15, it + again != 15);
                STAMPA(tid == 0 && it == 0, 1);
                mbar_wait(bar_x, 0);
                const uint2 xa = lds64(gx_s + (role & 7) * 4096 + (it & 3) * kStageBytes), wa = lds64(gw_s + it * 128);
                const uint32_t pa = bf2_mul(xa.x, wa.x), pb = bf2_mul(xa.y, wa.y);
                gs += (bf_lo(pa) + bf_hi(pa)) + (bf_lo(pb) + bf_hi(pb));
                if (it == again) {
                    mbar_wait(bar_c, 0);
                    const uint2 fin = lds64(role_s);
                    role = fin.x & 63;
                    if (__shfl_sync(0xffffffffu, fin.x != fin.y, 0)) { it = -1; again = 16; gs = 0.f; }
                }
            }
        }
        role = __shfl_sync(0xffffffffu, role, 0);
        ROLE_VARS();
        {
            tag = lds32(tag_s);
#pragma unroll
            for (int o = 8; o > 0; o >>= 1) gs += __shfl_xor_sync(0xffffffffu, gs, o);
            const float g = bf16_round(__frcp_rn(1.0f + expf(-bf16_round(gs))));
            if ((lane & 15) == 0) st_relaxed64(&p.s->gate[c * 256 + (lane >> 4) + 64 * w + 4 * cb + 2 * wg], __float_as_uint(g), tag);
        }
        const uint32_t tab_s = sbase + kTabOff + tid * 16;
        const float4 k0 = lds128f(tab_s);
        TILE_END();
        STAMPA(tid == 0, 2);
#pragma unroll
        for (int s = 0; s < 64; ++s) pk[s] = pack_bf16_v(acc[4 * (s >> 1) + (s & 1)], acc[4 * (s >> 1) + 2 + (s & 1)]);
#pragma unroll
        for (int i = 0; i < 96; ++i) UNDEF_F(acc[i]);

        const float lr = k0.x, li = k0.y, m00 = k0.z, m01 = k0.w;
        float m10, m11, hr = 0.f, hi = 0.f;
        uint32_t gg[4], orr[4], oii[4];
        const int ch = cb * 64 + warp * 8 + r;
        __nv_bfloat16* hs = p.s->Hs + (size_t)ch * 2048 + c * 256 + q * 8;
#define PASS2(KB)                                                                                      \
    _Pragma("unroll") for (int s = 0; s < 64; s += 2) {                                                \
        if (pass2_kb(s) != (KB)) continue;                                                             \
        if ((s & 7) == 0) {                                                                            \
            const uint4 ga = lds128(gate_s + (q * 72 + s) * 2);                                        \
            gg[0] = ga.x; gg[1] = ga.y; gg[2] = ga.z; gg[3] = ga.w;                                    \
        }                                                                                              \
        float o0[2], o1[2];                                                                            \
        _Pragma("unroll") for (int k = 0; k < 2; ++k) {                                                \
            PIN_R(pk[s + k]);                                                                          \
            float nr = bf_lo(pk[s + k]), ni = bf_hi(pk[s + k]);                                        \
            CFMA(nr, ni, lr, li, hr, hi);                                                              \
            hr = nr; hi = ni;                                                                          \
            o0[k] = fmaf(m00, hr, m01 * hi);                                                           \
            o1[k] = fmaf(m10, hr, m11 * hi);                                                           \
        }                                                                                              \
        orr[(s >> 1) & 3] = bf2_mul(pack_bf16(o0[0], o0[1]), gg[(s >> 1) & 3]);                        \
        oii[(s >> 1) & 3] = bf2_mul(pack_bf16(o1[0], o1[1]), gg[(s >> 1) & 3]);                        \
        if ((s & 7) == 6) {                                                                            \
            stg128(hs + 32 * (s >> 3), orr[0], orr[1], orr[2], orr[3]);                                \
            stg128(hs + 1024 * 2048 + 32 * (s >> 3), oii[0], oii[1], oii[2], oii[3]);                  \
        }                                                                                              \
    }                                                                                                  \
    PIN_F(hr); PIN_F(hi);
        {
            uint4 av0, av1, gv;
            float lqr, lqi;
#pragma unroll
            for (int kb = 0; kb < 16; ++kb) {
                PIN_R(a_lo);
                KBLOCK(1, 16 + kb, kb == 0, kb == 15);
                if (kb < 4) {
#pragma unroll
                    for (int s = kb * 16; s < kb * 16 + 16; ++s) {
                        float nr = bf_lo(pk[s]), ni = bf_hi(pk[s]);
                        CFMA(nr, ni, lr, li, hr, hi);
                        hr = nr; hi = ni;
                    }
                    PIN_F(hr); PIN_F(hi);
                }
                if (kb == 2) gv = ld_relaxed2x64(&p.s->gate[c * 256 + 2 * tw]);
                if (kb == 3) {
                    const float4 k1 = lds128f(tab_s + 4096), k2 = lds128f(tab_s + 8192);
                    m10 = k1.x; m11 = k1.y; lqr = k2.z; lqi = k2.w;
                    float tr = __shfl_up_sync(0xffffffffu, hr, 1, 4), ti = __shfl_up_sync(0xffffffffu, hi, 1, 4);
                    if (q >= 1) CFMA(hr, hi, k1.z, k1.w, tr, ti);
                    tr = __shfl_up_sync(0xffffffffu, hr, 2, 4); ti = __shfl_up_sync(0xffffffffu, hi, 2, 4);
                    if (q >= 2) CFMA(hr, hi, k2.x, k2.y, tr, ti);
                    if (q == 3) st_relaxed2x64(&p.s->agg[c * 1024 + ch], __float_as_uint(hr), tag, __float_as_uint(hi), tag);
                    tr = __shfl_up_sync(0xffffffffu, hr, 1, 4); ti = __shfl_up_sync(0xffffffffu, hi, 1, 4);
                    hr = (q >= 1) ? tr : 0.f; hi = (q >= 1) ? ti : 0.f;
                }
                if (kb == 4) {
                    unsigned spins = 0;
                    while (__any_sync(0xffffffffu, gv.y != tag || gv.w != tag)) {
                        if (++spins > kSpinLimit) break;
                        gv = ld_relaxed2x64(&p.s->gate[c * 256 + 2 * tw]);
                    }
                    sts32(gate_s + ((tw >> 5) * 72 + 2 * lane) * 2, __byte_perm(gv.x, gv.z, 0x7632));
                }
                if (kb == 5) {
                    av0 = make_uint4(0, tag, 0, tag); av1 = av0;
                    if (q < c) av0 = ld_relaxed2x64(&p.s->agg[q * 1024 + ch]);
                    if (q + 4 < c) av1 = ld_relaxed2x64(&p.s->agg[(q + 4) * 1024 + ch]);
                    bar_sync(1 + wg, 128);
                }
                if (kb == 6) {
                    const float4 k3 = lds128f(tab_s + 12288);
                    unsigned spins = 0;
                    while (__any_sync(0xffffffffu, av0.y != tag || av0.w != tag || av1.y != tag || av1.w != tag)) {
                        if (++spins > kSpinLimit) break;
                        if (q < c) av0 = ld_relaxed2x64(&p.s->agg[q * 1024 + ch]);
                        if (q + 4 < c) av1 = ld_relaxed2x64(&p.s->agg[(q + 4) * 1024 + ch]);
                    }
                    float vr, vi;
                    CMUL(vr, vi, k3.x, k3.y, __uint_as_float(av0.x), __uint_as_float(av0.z));
                    CFMA(vr, vi, k3.z, k3.w, __uint_as_float(av1.x), __uint_as_float(av1.z));
                    vr += __shfl_xor_sync(0xffffffffu, vr, 1); vi += __shfl_xor_sync(0xffffffffu, vi, 1);
                    vr += __shfl_xor_sync(0xffffffffu, vr, 2); vi += __shfl_xor_sync(0xffffffffu, vi, 2);
                    CFMA(hr, hi, lqr, lqi, vr, vi);
                }
                if (kb >= 6) { PASS2(kb); }
            }
            TILE_END();
        }
        STAMPA(tid == 0, 3);
#pragma unroll
        for (int i = 0; i < 48; ++i) pk[i] = pack_bf16_v(acc[2 * i], acc[2 * i + 1]);
#pragma unroll
        for (int i = 0; i < 128; ++i) UNDEF_F(acc[i]);

        PIN_R(a_lo);
        KBLOCK(2, 32, true, false);
        PASS2(16);
        PIN_R(a_lo);
        KBLOCK(2, 33, false, false);
        PASS2(17);
        bar_arrive(3, 288);
        const uint32_t gate_row = gate_s + ((2 * (w & 1)) * 72 + 8 * (4 * rank + 2 * wg + (w >> 1)) + r) * 2;
        uint32_t om0, om1;
        {
            const float a = 1.0f - bf_lo(lds16(gate_row)), b = 1.0f - bf_lo(lds16(gate_row + 72 * 2));
            om0 = pack_bf16(a, a); om1 = pack_bf16(b, b);
        }
        __nv_bfloat16* hf = p.s->Hf + (size_t)(rb * 128 + wg * 64 + w * 16 + r) * kF + q * 8 + 2048 + 192 * j8;
        uint32_t bias_s = sbase + kBiasOff + q * 16;
#define FFN_SLICE(J)                                                                                   \
    {                                                                                                  \
        const uint4 bv = lds128(bias_s + (J) * 64);                                                    \
        const uint32_t bb[4] = {bv.x, bv.y, bv.z, bv.w};                                               \
        _Pragma("unroll") for (int jj = 0; jj < 4; ++jj) {                                             \
            const uint32_t r0 = bf2_add_relu(pk[8 * (J) + 2 * jj], bb[jj]), r1 = bf2_add_relu(pk[8 * (J) + 2 * jj + 1], bb[jj]); \
            pk[8 * (J) + 2 * jj] = bf2_mul(bf2_mul(r0, r0), om0);                                      \
            pk[8 * (J) + 2 * jj + 1] = bf2_mul(bf2_mul(r1, r1), om1);                                  \
        }                                                                                              \
        stg128(hf + 32 * (J), pk[8 * (J)], pk[8 * (J) + 2], pk[8 * (J) + 4], pk[8 * (J) + 6]);         \
        stg128(hf + 8 * kF + 32 * (J), pk[8 * (J) + 1], pk[8 * (J) + 3], pk[8 * (J) + 5], pk[8 * (J) + 7]); \
    }
        const uint32_t x_s = sbase + kXOff + (wg * 64 + w * 16 + (lane & 15)) * 128 + (((lane >> 4) ^ (lane & 7)) << 4);
        {
            uint32_t j = 0, nsl = 6;
#pragma unroll 1
            for (uint32_t it = 34; it < 88; ++it, ++j) {
                const uint32_t so = (it & 3) * (kStageBytes >> 4);
                if (wg == 1 && (it == 88 - SKEW || (ORDER && it == 47))) bar_sync(7, 256);
                KB_OPEN(it, false);
                if ((it & ~15u) == 48) {
                    wgmma_fence();
                    mma_kblock<3>(acc, a_lo + so, b_lo + so, it != 48);
                    wgmma_commit();
                } else {
                    wgmma_fence();
                    mma_kblock<2>(acc, a_lo + so, b_lo + so, 1);
                    wgmma_commit();
                }
                if (wg == 0 && (it == 87 || (ORDER && it == 47))) bar_arrive(7, 256);
                KB_CLOSE(it, false, it != 48);
                if (wg == 1 && it == 87) bar_arrive(8, 256);
                if (j < nsl) {
                    if (j & 4) {
                        if (j & 2) { if (j & 1) FFN_SLICE(7) else FFN_SLICE(6) } else { if (j & 1) FFN_SLICE(5) else FFN_SLICE(4) }
                    } else {
                        if (j & 2) { if (j & 1) FFN_SLICE(3) else FFN_SLICE(2) } else { if (j & 1) FFN_SLICE(1) else FFN_SLICE(0) }
                    }
                    if (j + 1 == nsl) bar_arrive(1 + (nsl >> 1), 288);
                } else if (it == 47) {
                    hf += 64 * j8 - 2048;
                    bias_s += 6 * 64;
                    j = -1; nsl = 8;
                    TILE_END();
                    STAMPA(tid == 0, 4);
#pragma unroll
                    for (int i = 0; i < 64; ++i) pk[i] = pack_bf16_v(acc[2 * i], acc[2 * i + 1]);
                } else if ((it >> 2) == ETKB / 4) {
                    mbar_wait(bar_x, 1);
                    const uint32_t xa_s = (x_s ^ ((it & 1) << 6)) + (it & 2) * 8192;
                    const float g0 = bf_lo(lds16(gate_row)), g1 = bf_lo(lds16(gate_row + 72 * 2));
                    const float o0f = bf_lo(om0), o1f = bf_lo(om1);
                    const uint4 dq = lds128(bias_s + (8 + (it & 3)) * 64), bq = lds128(bias_s + (12 + (it & 3)) * 64);
                    const uint4 xa = ldsm4(xa_s), xb = ldsm4(xa_s ^ 32);
                    const uint32_t dv[4] = {dq.x, dq.y, dq.z, dq.w}, bv2[4] = {bq.x, bq.y, bq.z, bq.w};
                    uint32_t xv[8] = {xa.x, xa.y, xa.z, xa.w, xb.x, xb.y, xb.z, xb.w};
#pragma unroll
                    for (int jj = 0; jj < 4; ++jj) {
                        const uint32_t x0 = bf2_mul(xv[2 * jj], dv[jj]), x1 = bf2_mul(xv[2 * jj + 1], dv[jj]);
                        const float bl = bf_lo(bv2[jj]), bh = bf_hi(bv2[jj]);
                        xv[2 * jj] = pack_bf16(fmaf(g0, bf_lo(x0), o0f * bl), fmaf(g0, bf_hi(x0), o0f * bh));
                        xv[2 * jj + 1] = pack_bf16(fmaf(g1, bf_lo(x1), o1f * bl), fmaf(g1, bf_hi(x1), o1f * bh));
                    }
                    sts128(xa_s, xv[0], xv[1], xv[2], xv[3]);
                    sts128(xa_s ^ 32, xv[4], xv[5], xv[6], xv[7]);
                }
            }
        }
#define OWN_MMA(H, P)                                                                                  \
    wgmma_fence();                                                                                     \
    _Pragma("unroll") for (int i = 8 * (P); i < 8 * (P) + 8; ++i)                                      \
        wgmma_n64_rs<32 * (H)>(acc, pk[4 * i], pk[4 * i + 1], pk[4 * i + 2], pk[4 * i + 3],            \
                               kDescHi | (uint64_t)(b_lo + ((2 * (H) * kStageBytes + i * 2048) >> 4) + (256u << 16))); \
    wgmma_commit();
#define OTHER_MMA(H, P)                                                                                \
    PIN_R(a_lo);                                                                                       \
    wgmma_fence();                                                                                     \
    _Pragma("unroll") for (int i = 0; i < 8; ++i)                                                      \
        wgmma_n64<0, 1, 32 * (H)>(acc, kDescHi | (uint64_t)(a_lo + (((P) * kStageBytes + (i >> 2) * 8192 + (i & 3) * 32) >> 4) + (1u << 16)), \
                               kDescHi | (uint64_t)(b_lo + (((2 * (H) + 1) * kStageBytes + (8 * (P) + i) * 2048) >> 4) + (256u << 16)), 1); \
    wgmma_commit();
#define RXLOAD(H)                                                                                      \
    {                                                                                                  \
        if ((H) == 0) rs = ld_relaxed32((const unsigned*)(xi + 4096 - lane * 12));                     \
        _Pragma("unroll") for (int u = 4 * (H); u < 4 * (H) + 4; ++u) rx[u] = ld_relaxed2x64(xi + u * 512); \
    }
#define RXCHECK(H)                                                                                     \
    {                                                                                                  \
        unsigned spins = 0;                                                                            \
        _Pragma("unroll 1") while (true) {                                                             \
            uint32_t ok = rs != 0;                                                                     \
            _Pragma("unroll") for (int u = 4 * (H); u < 4 * (H) + 4; ++u) ok &= rx[u].x & rx[u].z;     \
            if (__all_sync(0xffffffffu, ok) || ++spins > kSpinLimit) break;                            \
            RXLOAD(H);                                                                                 \
            RESPIN();                                                                                  \
        }                                                                                              \
    }
#define UNPACK(H)                                                                                      \
    _Pragma("unroll") for (int u = 0; u < 4; ++u) {                                                    \
        const uint32_t rr[4] = {rx[4 * (H) + u].x, rx[4 * (H) + u].y, rx[4 * (H) + u].z, rx[4 * (H) + u].w}; \
        _Pragma("unroll") for (int k = 0; k < 4; ++k) {                                                \
            const float2 f = __half22float2(*reinterpret_cast<const __half2*>(&rr[k]));                \
            ex[8 * u + 2 * k] = f.x; ex[8 * u + 2 * k + 1] = f.y;                                      \
            PIN_F(ex[8 * u + 2 * k]); PIN_F(ex[8 * u + 2 * k + 1]);                                    \
        }                                                                                              \
    }
#define PUT(H, BASE, STEP)                                                                             \
    _Pragma("unroll") for (int i = 0; i < 32; i += 2) {                                                \
        PIN_F(acc[32 * (H) + i]); PIN_F(acc[32 * (H) + i + 1]);                                        \
        sts64f((BASE) + ((put_o ^ (((i >> 2) & 3) << 5) ^ ((i & 2) * 72)) + (i >> 4) * (STEP)),        \
               fmaf(ex[i], xsc, acc[32 * (H) + i]), fmaf(ex[i + 1], xsc, acc[32 * (H) + i + 1]));      \
    }
#define PUT_GO(H, BASE, STEP)                                                                          \
    fence_async_smem();                                                                                \
    __syncwarp();                                                                                      \
    if (lead) {                                                                                        \
        tma4_store(&mOut, BASE, tb, (colK >> 5) + 2 * (H));                                            \
        tma4_store(&mOut, (BASE) + (STEP), tb, (colK >> 5) + 2 * (H) + 1);                             \
        bulk_commit();                                                                                 \
    }
        TILE_END();
        sched_fence(a_lo);
        {
            const uint8_t* xi = p.s->X + (size_t)(role * 2 + rank) * kXBytes + warp * 4224 + lane * 16;
            uint8_t* xo = const_cast<uint8_t*>(xi) + (kh ? -8 * kXBytes : 8 * kXBytes);
            const uint32_t e_s = sbase + kXOff + warp * 2048;
            const bool lead = lane == 0;
            uint4 rx[8];
            uint32_t rs;
            float ex[32];
            STAMP(tid == 0, 15); STAMPB(tid == 128, 1);
#pragma unroll
            for (int u = 0; u < 8; ++u) rx[u] = lds128((x_s ^ ((u & 3) << 5)) + (u >> 2) * 16384);
            {
                float m[4] = {0.f, 0.f, 0.f, 0.f};
#pragma unroll
                for (int i = 64; i < 128; ++i) m[i & 3] = fmaxf(m[i & 3], fabsf(acc[i]));
                const uint32_t eb = max(__float_as_uint(fmaxf(fmaxf(m[0], m[1]), fmaxf(m[2], m[3]))) >> 23, 15u);
                const float xsc = __uint_as_float((268u - eb) << 23);
                st_relaxed32(xo + 4096 - lane * 12, (eb - 14u) << 23);
                __syncwarp();
#pragma unroll
                for (int u = 0; u < 8; ++u) {
                    const int v = 64 + 8 * u;
                    sts128(e_s + lane * 16 + (u & 3) * 512 + (u >> 2) * 16384,
                           pack_f16(acc[v] * xsc, acc[v + 1] * xsc) | 1, pack_f16(acc[v + 2] * xsc, acc[v + 3] * xsc),
                           pack_f16(acc[v + 4] * xsc, acc[v + 5] * xsc) | 1, pack_f16(acc[v + 6] * xsc, acc[v + 7] * xsc));
                    if ((u & 3) == 3) {
                        fence_async_smem();
                        __syncwarp();
                        if (lead) { bulk_store(xo + (u >> 2) * 2048, e_s + (u >> 2) * 16384, 2048); bulk_commit(); }
                    }
                }
                STAMP(tid == 0, 12); STAMPB(tid == 128, 2);
            }
#pragma unroll
            for (int u = 0; u < 8; ++u) {
                const uint32_t ee[4] = {rx[u].x, rx[u].y, rx[u].z, rx[u].w};
#pragma unroll
                for (int k = 0; k < 4; ++k) {
                    const int v = 8 * u + 2 * k;
                    acc[v] += bf_lo(ee[k]); acc[v + 1] += bf_hi(ee[k]);
                    PIN_F(acc[v]); PIN_F(acc[v + 1]);
                }
            }
            a_lo += wg * ((2 * kStageBytes - 8192) >> 4);
            const int tb = c * 256 + 128 * (w & 1) + 8 * (4 * rank + 2 * wg + (w >> 1));
            const uint32_t put_o = r * 256 + (r & 3) * 32 + q * 8;
            mbar_wait(bar_full, 0);
            if (wg == 1) {
                mbar_wait(bar_full + 16, 0);
                mbar_wait(bar_full + 24, 0);
            }
            bar_sync(8 + wg, 256);
            STAMPB(tid == 128, 3); STAMPB(tid == 0, 9);
            OWN_MMA(0, 0);
            sched_fence(a_lo);
            RXLOAD(0);
            STAMPB(tid == 0, 10);
            sched_fence(a_lo);
            OWN_MMA(0, 1);
            mbar_wait(bar_full + 8, 0);
            OTHER_MMA(0, 0);
            OTHER_MMA(0, 1);
            sched_fence(a_lo);
            RXCHECK(0);
            UNPACK(0);
            STAMP(tid == 0, 13);
            if (lead) bulk_wait_read();
            mbar_wait(bar_full + 16, 0);
            OWN_MMA(1, 0);
            sched_fence(a_lo);
            STAMPB(tid == 0, 11);
            RXLOAD(1);
            const float xsc = __uint_as_float(rs);
            wgmma_wait<1>();
            STAMPB(tid == 128, 8);
            PUT(0, e_s, 16384);
            sched_fence(a_lo);
            OWN_MMA(1, 1);
            sched_fence(a_lo);
            PUT_GO(0, e_s, 16384);
            mbar_wait(bar_full + 24, 0);
            OTHER_MMA(1, 0);
            OTHER_MMA(1, 1);
            if (wg == 0) bar_arrive(9, 256);
            sched_fence(a_lo);
            STAMP(tid == 0, 14);
            RXCHECK(1);
            UNPACK(1);
            sched_fence(a_lo);
            wgmma_wait<0>();
            STAMP(tid == 0, 6); STAMPB(tid == 128, 4);
            const uint32_t o_s = sbase + wg * 2 * kStageBytes + w * 2048;
            PUT(1, o_s, 8192);
            PUT_GO(1, o_s, 8192);
            if (lead) bulk_wait_read();
        }
        STAMP(tid == 0, 7);
        STAMP(tid == 128, 5);
    }
}

typedef CUresult (*EncodeFn)(CUtensorMap*, CUtensorMapDataType, cuuint32_t, void*, const cuuint64_t*, const cuuint64_t*,
                             const cuuint32_t*, const cuuint32_t*, CUtensorMapInterleave, CUtensorMapSwizzle,
                             CUtensorMapL2promotion, CUtensorMapFloatOOBfill);

bool encode(EncodeFn fn, CUtensorMap* m, const void* base, int rank, const cuuint64_t* dims, const cuuint64_t* strides,
            const cuuint32_t* box, CUtensorMapDataType type = CU_TENSOR_MAP_DATA_TYPE_BFLOAT16) {
    cuuint32_t es[5] = {1, 1, 1, 1, 1};
    return fn(m, type, rank, const_cast<void*>(base), dims, strides, box, es,
              CU_TENSOR_MAP_INTERLEAVE_NONE, CU_TENSOR_MAP_SWIZZLE_128B, CU_TENSOR_MAP_L2_PROMOTION_L2_256B,
              CU_TENSOR_MAP_FLOAT_OOB_FILL_NONE) == CUDA_SUCCESS;
}

}

extern "C" void kernel_launch(void* const* d_in, const int* in_sizes, int n_in, void* d_out, int out_size) {
    (void)in_sizes; (void)n_in; (void)out_size;
    typedef const __nv_bfloat16* bp;
    bp x = (bp)d_in[0], lam_re = (bp)d_in[1], lam_im = (bp)d_in[2], B_re = (bp)d_in[3], B_im = (bp)d_in[4];
    bp C_re = (bp)d_in[5], C_im = (bp)d_in[6], log_dt = (bp)d_in[7], dskip = (bp)d_in[8];
    bp w1 = (bp)d_in[10], b1 = (bp)d_in[11], w2 = (bp)d_in[12], b2 = (bp)d_in[13], gate_w = (bp)d_in[14];

    static EncodeFn fn = nullptr;
    static Scratch* ps = nullptr;
    if (!fn) {
        void* f = nullptr;
        cudaDriverEntryPointQueryResult qr;
        cudaGetDriverEntryPoint("cuTensorMapEncodeTiled", &f, cudaEnableDefault, &qr);
        fn = (EncodeFn)f;
        cudaGetSymbolAddress((void**)&ps, g_s);
        cudaFuncSetAttribute(fused_kernel, cudaFuncAttributeMaxDynamicSharedMemorySize, kSmemBytes);
    }
    cudaStream_t stream = cudaStreamPerThread;

    Params p;
    p.x = x; p.lam_re = lam_re; p.lam_im = lam_im; p.log_dt = log_dt; p.dskip = dskip; p.b1 = b1; p.b2 = b2;
    p.gate_w = gate_w; p.b_re = B_re; p.b_im = B_im; p.s = ps;
    char* const pHs = (char*)ps + offsetof(Scratch, Hs);
    char* const pHf = (char*)ps + offsetof(Scratch, Hf);
    char* const pBc = (char*)ps + offsetof(Scratch, Bcopy);

    const char* lo = (const char*)B_re; const char* hi = (const char*)B_im;
    p.swap = 0;
    if (hi < lo) { const char* t = lo; lo = hi; hi = t; p.swap = 1; }
    unsigned long long diff = (unsigned long long)(hi - lo);
    if (diff >= (1ull << 40) || (diff & 15) || diff == 0) {
        cudaMemcpyAsync(pBc, B_re, 2u << 20, cudaMemcpyDeviceToDevice, stream);
        cudaMemcpyAsync((char*)pBc + (2u << 20), B_im, 2u << 20, cudaMemcpyDeviceToDevice, stream);
        lo = (const char*)pBc; diff = 2u << 20; p.swap = 0;
    }

    CUtensorMap mB, mXs, mXf, mW1a, mW1b, mHs, mHf, mCre, mCim, mW2, mW2n, mW2p, mHf3, mOut;
    bool ok = true;
    { cuuint64_t d[4] = {1024, 8, 2, 128}, s[3] = {2048, diff, 16384}; cuuint32_t b[4] = {64, 8, 2, 8};
      ok &= encode(fn, &mB, lo, 4, d, s, b); }
    { cuuint64_t d[5] = {1024, 2, 4, 32, 8}, s[4] = {2048, 64 * 2048, 2 * 2048, 256 * 2048}; cuuint32_t b[5] = {64, 2, 4, 16, 1};
      ok &= encode(fn, &mXs, x, 5, d, s, b); }
    { cuuint64_t d[5] = {1024, 8, 4, 8, 8}, s[4] = {2048, 64 * 2048, 8 * 2048, 256 * 2048}; cuuint32_t b[5] = {64, 8, 4, 4, 1};
      ok &= encode(fn, &mXf, x, 5, d, s, b); }
    { cuuint64_t d[3] = {64, 1024, 56}, s[2] = {7168, 128}; cuuint32_t ba[3] = {64, 32, 4}, bb[3] = {64, 32, 3};
      ok &= encode(fn, &mW1a, w1, 3, d, s, ba); ok &= encode(fn, &mW1b, w1, 3, d, s, bb); }
    { cuuint64_t d[3] = {64, 2048, 32}, s[2] = {4096, 128}; cuuint32_t b[3] = {64, 64, 2};
      ok &= encode(fn, &mHs, pHs, 3, d, s, b); }
    { cuuint64_t d[2] = {3584, 2048}, s[1] = {7168}; cuuint32_t b[2] = {64, 128};
      ok &= encode(fn, &mHf, pHf, 2, d, s, b); }
    { cuuint64_t d[2] = {1024, 1024}, s[1] = {2048}; cuuint32_t b[2] = {64, 128};
      ok &= encode(fn, &mCre, C_re, 2, d, s, b); ok &= encode(fn, &mCim, C_im, 2, d, s, b); }
    { cuuint64_t d[5] = {64, 2, 448, 4, 16}, s[4] = {2048, 8 * 2048, 2 * 2048, 128}; cuuint32_t b[5] = {64, 2, 4, 4, 2};
      ok &= encode(fn, &mW2, w2, 5, d, s, b); }
    { cuuint64_t d[2] = {1024, 3584}, s[1] = {2048}; cuuint32_t b[2] = {64, 128};
      ok &= encode(fn, &mW2n, w2, 2, d, s, b); }
    { cuuint64_t d[5] = {1024, 2, 4, 4, 112}, s[4] = {2048, 8 * 2048, 2 * 2048, 32 * 2048}; cuuint32_t b[5] = {64, 2, 4, 4, 4};
      ok &= encode(fn, &mW2p, w2, 5, d, s, b); }
    { cuuint64_t d[3] = {64, 2048, 56}, s[2] = {7168, 128}; cuuint32_t b[3] = {64, 64, 2};
      ok &= encode(fn, &mHf3, pHf, 3, d, s, b); }
    { cuuint64_t d[4] = {32, 2, 1984, 32}, s[3] = {64 * 4096, 4096, 128}; cuuint32_t b[4] = {32, 2, 8, 1};
      ok &= encode(fn, &mOut, d_out, 4, d, s, b, CU_TENSOR_MAP_DATA_TYPE_FLOAT32); }
    if (!ok) return;

    fused_kernel<<<128, 384, kSmemBytes, stream>>>(mB, mXs, mXf, mW1b, mW1a, mHs, mHf, mCre, mCim, mW2, mW2n, mW2p, mHf3, mOut, p);
}
```

```cpp
#include <cuda_runtime.h>
#include <cuda_bf16.h>
#include <cuda_fp16.h>
#include <cuda.h>
#include <stdint.h>
#include <stddef.h>

#define XLDKB 40
#define PF0LINES 1
#define ETKB 60
#define PFKB 80
#define SKEW 2
#define RXPOS 1
#define MC0 0
#define PFTOP 0
#define INITW 0
#define PRODCOND warp >= 8
#define ORDER 0

namespace {

constexpr int kD = 1024, kF = 3584;
constexpr int kStages = 4;
constexpr int kStageBytes = 49152;
constexpr int kABytes = 16384;
constexpr int kXOff = kStages * kStageBytes;
constexpr int kTabOff = kXOff + 2048;
constexpr int kGateOff = kXOff + 32768;
constexpr int kBiasOff = kGateOff + 4 * 72 * 2;
constexpr int kBarOff = kBiasOff + 88 * 16;
constexpr int kSmemBytes = 232448;
static_assert(kBarOff + 160 <= kSmemBytes, "smem");
constexpr int kXBytes = 33792;
constexpr uint32_t kSmemOrg = 1024;
constexpr unsigned kSpinLimit = 1u << 18;
constexpr int kTotal = 92;

__host__ __device__ constexpr int pass2_kb(int s) {
    return s < 2 ? 6 : s < 8 ? 7 : s < 12 ? 8 : s < 18 ? 9 : s < 22 ? 10 : s < 28 ? 11 : s < 32 ? 12 : s < 38 ? 13 : s < 42 ? 14 : s < 48 ? 15 : s < 56 ? 16 : 17;
}

struct Scratch {
    unsigned claim[64];
    unsigned epoch, pad0[31];
    unsigned done, pad1[31];
    unsigned cnt[40 * 32];
    uint2 gate[2048];
    uint4 agg[8 * 1024];
    __align__(1024) uint8_t X[128 * kXBytes];
    __align__(1024) __nv_bfloat16 Hs[2048 * 2048];
    __align__(1024) __nv_bfloat16 Hf[2048 * 3584];
    __align__(1024) __nv_bfloat16 Bcopy[2 * 1024 * 1024];
};
__device__ Scratch g_s;

#define TRAP() break
#define PIN_F(x) asm volatile("" : "+f"(x))
#define PIN_R(x) asm volatile("" : "+r"(x))
#define UNDEF_F(x) asm volatile("" : "=f"(x))
#define UNDEF_R(x) asm volatile("" : "=r"(x))
#define RESPIN()
__device__ __forceinline__ uint32_t smem_u32(const void* p) { return (uint32_t)__cvta_generic_to_shared(p); }
__device__ __forceinline__ void mbar_init(uint32_t bar, uint32_t count) {
    asm volatile("mbarrier.init.shared::cta.b64 [%0], %1;" ::"r"(bar), "r"(count) : "memory");
}
__device__ __forceinline__ void mbar_expect_tx(uint32_t bar, uint32_t bytes) {
    asm volatile("mbarrier.arrive.expect_tx.shared::cta.b64 _, [%0], %1;" ::"r"(bar), "r"(bytes) : "memory");
}
__device__ __forceinline__ void mbar_wait(uint32_t bar, uint32_t parity) {
    asm volatile(
        "{\n.reg .pred p;\n.reg .u32 n;\n"
        "mbarrier.try_wait.parity.shared::cta.b64 p, [%0], %1;\n"
        "@p bra DONE;\n"
        "mov.u32 n, 0;\n"
        "LOOP:\n"
        "mbarrier.try_wait.parity.shared::cta.b64 p, [%0], %1;\n"
        "@p bra DONE;\n"
        "add.u32 n, n, 1;\n"
        "setp.lt.u32 p, n, %2;\n"
        "@p bra LOOP;\n"
        "DONE:\n}\n"
        ::"r"(bar), "r"(parity), "n"(kSpinLimit) : "memory");
}
__device__ __forceinline__ void sched_fence(uint32_t nonzero) {
    asm volatile("{\n.reg .pred p;\n.reg .u32 n;\nsetp.ne.u32 p, %0, 0;\n@p bra DONE;\nLOOP:\nmov.u32 n, %%clock;\n"
                 "setp.eq.u32 p, n, 0;\n@p bra LOOP;\nDONE:\n}\n" ::"r"(nonzero) : "memory");
}
__device__ __forceinline__ void mbar_arrive_local(uint32_t bar) {
    asm volatile("mbarrier.arrive.shared::cta.b64 _, [%0];" ::"r"(bar) : "memory");
}
__device__ __forceinline__ void mbar_arrive_cluster(uint32_t cluster_addr) {
    asm volatile("mbarrier.arrive.shared::cluster.b64 _, [%0];" ::"r"(cluster_addr) : "memory");
}
__device__ __forceinline__ uint32_t mapa(uint32_t addr, uint32_t rank) {
    uint32_t r;
    asm("mapa.shared::cluster.u32 %0, %1, %2;" : "=r"(r) : "r"(addr), "r"(rank));
    return r;
}
__device__ __forceinline__ void cluster_arrive() { asm volatile("barrier.cluster.arrive.relaxed.aligned;" ::: "memory"); }
__device__ __forceinline__ void cluster_wait() { asm volatile("barrier.cluster.wait.acquire.aligned;" ::: "memory"); }
__device__ __forceinline__ void bar_sync(int id, int n) { asm volatile("bar.sync %0, %1;" ::"r"(id), "r"(n) : "memory"); }
__device__ __forceinline__ void bar_arrive(int id, int n) { asm volatile("bar.arrive %0, %1;" ::"r"(id), "r"(n) : "memory"); }
__device__ __forceinline__ bool elect_one() {
    uint32_t p;
    asm volatile("{\n.reg .pred P;\nelect.sync _|P, 0xffffffff;\nselp.u32 %0, 1, 0, P;\n}\n" : "=r"(p));
    return p != 0;
}

__device__ __forceinline__ void tma2(uint32_t dst, const CUtensorMap* m, uint32_t bar, int c0, int c1) {
    asm volatile("cp.async.bulk.tensor.2d.shared::cluster.global.mbarrier::complete_tx::bytes [%0], [%1, {%3, %4}], [%2];"
                 ::"r"(dst), "l"(m), "r"(bar), "r"(c0), "r"(c1) : "memory");
}
__device__ __forceinline__ void tma3(uint32_t dst, const CUtensorMap* m, uint32_t bar, int c0, int c1, int c2) {
    asm volatile("cp.async.bulk.tensor.3d.shared::cluster.global.mbarrier::complete_tx::bytes [%0], [%1, {%3, %4, %5}], [%2];"
                 ::"r"(dst), "l"(m), "r"(bar), "r"(c0), "r"(c1), "r"(c2) : "memory");
}
__device__ __forceinline__ void tma4(uint32_t dst, const CUtensorMap* m, uint32_t bar, int c0, int c1, int c2, int c3) {
    asm volatile("cp.async.bulk.tensor.4d.shared::cluster.global.mbarrier::complete_tx::bytes [%0], [%1, {%3, %4, %5, %6}], [%2];"
                 ::"r"(dst), "l"(m), "r"(bar), "r"(c0), "r"(c1), "r"(c2), "r"(c3) : "memory");
}
__device__ __forceinline__ void tma5(uint32_t dst, const CUtensorMap* m, uint32_t bar, int c0, int c1, int c2, int c3, int c4) {
    asm volatile("cp.async.bulk.tensor.5d.shared::cluster.global.mbarrier::complete_tx::bytes [%0], [%1, {%3, %4, %5, %6, %7}], [%2];"
                 ::"r"(dst), "l"(m), "r"(bar), "r"(c0), "r"(c1), "r"(c2), "r"(c3), "r"(c4) : "memory");
}
__device__ __forceinline__ void tma2_mc(uint32_t dst, const CUtensorMap* m, uint32_t bar, int c0, int c1) {
    asm volatile("cp.async.bulk.tensor.2d.shared::cluster.global.mbarrier::complete_tx::bytes.multicast::cluster [%0], [%1, {%3, %4}], [%2], %5;"
                 ::"r"(dst), "l"(m), "r"(bar), "r"(c0), "r"(c1), "h"((uint16_t)3) : "memory");
}
__device__ __forceinline__ void tma3_mc(uint32_t dst, const CUtensorMap* m, uint32_t bar, int c0, int c1, int c2) {
    asm volatile("cp.async.bulk.tensor.3d.shared::cluster.global.mbarrier::complete_tx::bytes.multicast::cluster [%0], [%1, {%3, %4, %5}], [%2], %6;"
                 ::"r"(dst), "l"(m), "r"(bar), "r"(c0), "r"(c1), "r"(c2), "h"((uint16_t)3) : "memory");
}
__device__ __forceinline__ void tma5_mc(uint32_t dst, const CUtensorMap* m, uint32_t bar, int c0, int c1, int c2, int c3, int c4) {
    asm volatile("cp.async.bulk.tensor.5d.shared::cluster.global.mbarrier::complete_tx::bytes.multicast::cluster [%0], [%1, {%3, %4, %5, %6, %7}], [%2], %8;"
                 ::"r"(dst), "l"(m), "r"(bar), "r"(c0), "r"(c1), "r"(c2), "r"(c3), "r"(c4), "h"((uint16_t)3) : "memory");
}
__device__ __forceinline__ void tma2_pf(const CUtensorMap* m, int c0, int c1) {
    asm volatile("cp.async.bulk.prefetch.tensor.2d.L2.global [%0, {%1, %2}];" ::"l"(m), "r"(c0), "r"(c1) : "memory");
}
__device__ __forceinline__ void bulk_store(void* dst, uint32_t src, uint32_t bytes) {
    asm volatile("cp.async.bulk.global.shared::cta.bulk_group [%0], [%1], %2;" ::"l"(dst), "r"(src), "r"(bytes) : "memory");
}
__device__ __forceinline__ void tma4_store(const CUtensorMap* m, uint32_t src, int c2, int c3) {
    asm volatile("cp.async.bulk.tensor.4d.global.shared::cta.bulk_group [%0, {%2, %2, %3, %4}], [%1];"
                 ::"l"(m), "r"(src), "r"(0), "r"(c2), "r"(c3) : "memory");
}
__device__ __forceinline__ void bulk_commit() { asm volatile("cp.async.bulk.commit_group;" ::: "memory"); }
__device__ __forceinline__ void bulk_wait_read() { asm volatile("cp.async.bulk.wait_group.read 0;" ::: "memory"); }
__device__ __forceinline__ void fence_async_smem() { asm volatile("fence.proxy.async.shared::cta;" ::: "memory"); }
__device__ __forceinline__ void bulk_load(uint32_t dst, const void* src, uint32_t bytes, uint32_t bar) {
    asm volatile("cp.async.bulk.shared::cluster.global.mbarrier::complete_tx::bytes [%0], [%1], %2, [%3];"
                 ::"r"(dst), "l"(src), "r"(bytes), "r"(bar) : "memory");
}
__device__ __forceinline__ unsigned atom_exch(unsigned* p, unsigned v) {
    unsigned r;
    asm volatile("atom.relaxed.gpu.global.exch.b32 %0, [%1], %2;" : "=r"(r) : "l"(p), "r"(v) : "memory");
    return r;
}
__device__ __forceinline__ void st_async32(uint32_t a, uint32_t v, uint32_t bar) {
    asm volatile("st.async.shared::cluster.mbarrier::complete_tx::bytes.u32 [%0], %1, [%2];" ::"r"(a), "r"(v), "r"(bar) : "memory");
}
__device__ __forceinline__ void sts128f(uint32_t a, float x, float y, float z, float w) {
    asm volatile("st.shared.v4.f32 [%0], {%1, %2, %3, %4};" ::"r"(a), "f"(x), "f"(y), "f"(z), "f"(w) : "memory");
}
__device__ __forceinline__ void prefetch_map(const CUtensorMap* m) {
    asm volatile("prefetch.tensormap [%0];" ::"l"(m) : "memory");
}

__device__ __forceinline__ void prefetch_l2(const void* p, uint32_t bytes) {
    asm volatile("cp.async.bulk.prefetch.L2.global [%0], %1;" ::"l"(p), "r"(bytes) : "memory");
}

__device__ __forceinline__ void wgmma_fence() { asm volatile("wgmma.fence.sync.aligned;" ::: "memory"); }
__device__ __forceinline__ void wgmma_commit() { asm volatile("wgmma.commit_group.sync.aligned;" ::: "memory"); }
template <int N>
__device__ __forceinline__ void wgmma_wait() { asm volatile("wgmma.wait_group.sync.aligned %0;" ::"n"(N) : "memory"); }

__device__ __forceinline__ uint32_t pack_bf16(float lo, float hi) {
    uint32_t r;
    asm("cvt.rn.bf16x2.f32 %0, %1, %2;" : "=r"(r) : "f"(hi), "f"(lo));
    return r;
}
__device__ __forceinline__ uint32_t pack_f16(float lo, float hi) {
    uint32_t r;
    asm("cvt.rn.f16x2.f32 %0, %1, %2;" : "=r"(r) : "f"(hi), "f"(lo));
    return r;
}
__device__ __forceinline__ uint32_t pack_bf16_v(float lo, float hi) {
    uint32_t r;
    asm volatile("cvt.rn.bf16x2.f32 %0, %1, %2;" : "=r"(r) : "f"(hi), "f"(lo));
    return r;
}
template <int LUT>
__device__ __forceinline__ uint32_t lop3(uint32_t a, uint32_t b, uint32_t c) {
    uint32_t r;
    asm("lop3.b32 %0, %1, %2, %3, %4;" : "=r"(r) : "r"(a), "r"(b), "r"(c), "n"(LUT));
    return r;
}
__device__ __forceinline__ float bf_lo(uint32_t v) { return __uint_as_float(v << 16); }
__device__ __forceinline__ float bf_hi(uint32_t v) { return __uint_as_float(v & 0xffff0000u); }
__device__ __forceinline__ float bf16_round(float v) { return __bfloat162float(__float2bfloat16_rn(v)); }
__device__ __forceinline__ uint32_t bf2_mul(uint32_t a, uint32_t b) {
    uint32_t r;
    asm("mul.rn.bf16x2 %0, %1, %2;" : "=r"(r) : "r"(a), "r"(b));
    return r;
}
__device__ __forceinline__ uint32_t bf2_add_relu(uint32_t a, uint32_t b) {
    uint32_t r;
    asm("fma.rn.relu.bf16x2 %0, %1, %2, %3;" : "=r"(r) : "r"(a), "r"(0x3f803f80u), "r"(b));
    return r;
}
__device__ __forceinline__ uint4 ldg128(const void* p) {
    uint4 v;
    asm volatile("ld.global.nc.v4.u32 {%0, %1, %2, %3}, [%4];" : "=r"(v.x), "=r"(v.y), "=r"(v.z), "=r"(v.w) : "l"(p));
    return v;
}
__device__ __forceinline__ uint32_t ldg32(const void* p) {
    uint32_t v;
    asm volatile("ld.global.nc.u32 %0, [%1];" : "=r"(v) : "l"(p));
    return v;
}
__device__ __forceinline__ uint32_t ldg32na(const void* p) {
    uint32_t v;
    asm volatile("ld.global.nc.L1::no_allocate.u32 %0, [%1];" : "=r"(v) : "l"(p));
    return v;
}
__device__ __forceinline__ uint32_t ldg16(const __nv_bfloat16* p) {
    uint32_t v;
    asm volatile("ld.global.nc.u16 %0, [%1];" : "=r"(v) : "l"(p));
    return v;
}
__device__ __forceinline__ uint4 ld_relaxed128(const void* p) {
    uint4 v;
    asm volatile("ld.relaxed.gpu.global.v4.u32 {%0, %1, %2, %3}, [%4];" : "=r"(v.x), "=r"(v.y), "=r"(v.z), "=r"(v.w) : "l"(p) : "memory");
    return v;
}
__device__ __forceinline__ uint2 ld_relaxed64(const void* p) {
    unsigned long long v;
    asm volatile("ld.relaxed.gpu.global.u64 %0, [%1];" : "=l"(v) : "l"(p) : "memory");
    return make_uint2((uint32_t)v, (uint32_t)(v >> 32));
}
__device__ __forceinline__ void st_relaxed64(void* p, uint32_t lo, uint32_t hi) {
    unsigned long long v = ((unsigned long long)hi << 32) | lo;
    asm volatile("st.relaxed.gpu.global.u64 [%0], %1;" ::"l"(p), "l"(v) : "memory");
}
__device__ __forceinline__ void st_relaxed2x64(void* p, uint32_t a, uint32_t b, uint32_t c, uint32_t d) {
    unsigned long long v0 = ((unsigned long long)b << 32) | a, v1 = ((unsigned long long)d << 32) | c;
    asm volatile("st.relaxed.gpu.global.v2.u64 [%0], {%1, %2};" ::"l"(p), "l"(v0), "l"(v1) : "memory");
}
__device__ __forceinline__ uint4 ld_relaxed2x64(const void* p) {
    unsigned long long v0, v1;
    asm volatile("ld.relaxed.gpu.global.v2.u64 {%0, %1}, [%2];" : "=l"(v0), "=l"(v1) : "l"(p) : "memory");
    return make_uint4((uint32_t)v0, (uint32_t)(v0 >> 32), (uint32_t)v1, (uint32_t)(v1 >> 32));
}
__device__ __forceinline__ void stg128(void* p, uint32_t a, uint32_t b, uint32_t c, uint32_t d) {
    asm volatile("st.global.v4.u32 [%0], {%1, %2, %3, %4};" ::"l"(p), "r"(a), "r"(b), "r"(c), "r"(d) : "memory");
}
__device__ __forceinline__ void stg64f(void* p, float a, float b) {
    asm volatile("st.global.v2.f32 [%0], {%1, %2};" ::"l"(p), "f"(a), "f"(b) : "memory");
}
__device__ __forceinline__ uint4 lds128(uint32_t a) {
    uint4 v;
    asm volatile("ld.shared.v4.u32 {%0, %1, %2, %3}, [%4];" : "=r"(v.x), "=r"(v.y), "=r"(v.z), "=r"(v.w) : "r"(a) : "memory");
    return v;
}
__device__ __forceinline__ uint2 lds64(uint32_t a) {
    uint2 v;
    asm volatile("ld.shared.v2.u32 {%0, %1}, [%2];" : "=r"(v.x), "=r"(v.y) : "r"(a) : "memory");
    return v;
}
__device__ __forceinline__ uint4 ldsm4(uint32_t a) {
    uint4 v;
    asm volatile("ldmatrix.sync.aligned.m8n8.x4.shared.b16 {%0, %1, %2, %3}, [%4];" : "=r"(v.x), "=r"(v.y), "=r"(v.z), "=r"(v.w) : "r"(a) : "memory");
    return v;
}
__device__ __forceinline__ uint32_t lds16(uint32_t a) {
    uint32_t v;
    asm volatile("ld.shared.u16 %0, [%1];" : "=r"(v) : "r"(a) : "memory");
    return v;
}
__device__ __forceinline__ void sts16(uint32_t a, uint32_t x) {
    asm volatile("st.shared.u16 [%0], %1;" ::"r"(a), "h"((uint16_t)x) : "memory");
}
__device__ __forceinline__ void st_relaxed32(void* p, uint32_t v) {
    asm volatile("st.relaxed.gpu.global.u32 [%0], %1;" ::"l"(p), "r"(v) : "memory");
}
__device__ __forceinline__ float lds32f(uint32_t a) {
    float v;
    asm volatile("ld.shared.f32 %0, [%1];" : "=f"(v) : "r"(a) : "memory");
    return v;
}
__device__ __forceinline__ void sts128(uint32_t a, uint32_t x, uint32_t y, uint32_t z, uint32_t w) {
    asm volatile("st.shared.v4.u32 [%0], {%1, %2, %3, %4};" ::"r"(a), "r"(x), "r"(y), "r"(z), "r"(w) : "memory");
}
__device__ __forceinline__ void sts64f(uint32_t a, float x, float y) {
    asm volatile("st.shared.v2.f32 [%0], {%1, %2};" ::"r"(a), "f"(x), "f"(y) : "memory");
}
__device__ __forceinline__ float4 lds128f(uint32_t a) {
    float4 v;
    asm volatile("ld.shared.v4.f32 {%0, %1, %2, %3}, [%4];" : "=f"(v.x), "=f"(v.y), "=f"(v.z), "=f"(v.w) : "r"(a) : "memory");
    return v;
}
__device__ __forceinline__ uint32_t lds32(uint32_t a) {
    uint32_t v;
    asm volatile("ld.shared.u32 %0, [%1];" : "=r"(v) : "r"(a) : "memory");
    return v;
}
__device__ __forceinline__ void sts32(uint32_t a, uint32_t x) {
    asm volatile("st.shared.u32 [%0], %1;" ::"r"(a), "r"(x) : "memory");
}
__device__ __forceinline__ void stg128f(void* p, float a, float b, float c, float d) {
    asm volatile("st.global.v4.f32 [%0], {%1, %2, %3, %4};" ::"l"(p), "f"(a), "f"(b), "f"(c), "f"(d) : "memory");
}
__device__ __forceinline__ unsigned ld_relaxed32(const unsigned* p) {
    unsigned v;
    asm volatile("ld.relaxed.gpu.global.u32 %0, [%1];" : "=r"(v) : "l"(p) : "memory");
    return v;
}
__device__ __forceinline__ void wait_counter(const unsigned* p, unsigned target) {
    unsigned n = 0, v;
    while (true) {
        asm volatile("ld.acquire.gpu.global.u32 %0, [%1];" : "=r"(v) : "l"(p) : "memory");
        if ((int)(v - target) >= 0) break;
        if (++n > kSpinLimit) TRAP();
        __nanosleep(32);
    }
}
#define KT(IT, W) do { } while (0)
#define STAMP(cond, slot) do { } while (0)
#define STAMPA(cond, slot) STAMP(cond, slot)
#define STAMPB(cond, slot) do { } while (0)

#define STAMPC(cond, slot) do { } while (0)
#define STAMPD(cond, slot) do { } while (0)
template <int TA, int TB>
__device__ __forceinline__ void wgmma_n256(float (&d)[128], uint64_t da, uint64_t db, int keep) {
    asm volatile(
        "{\n.reg .pred p;\nsetp.ne.b32 p, %132, 0;\n"
        "wgmma.mma_async.sync.aligned.m64n256k16.f32.bf16.bf16 "
        "{%0, %1, %2, %3, %4, %5, %6, %7, %8, %9, %10, %11, %12, %13, %14, %15, "
        "%16, %17, %18, %19, %20, %21, %22, %23, %24, %25, %26, %27, %28, %29, %30, %31, "
        "%32, %33, %34, %35, %36, %37, %38, %39, %40, %41, %42, %43, %44, %45, %46, %47, "
        "%48, %49, %50, %51, %52, %53, %54, %55, %56, %57, %58, %59, %60, %61, %62, %63, "
        "%64, %65, %66, %67, %68, %69, %70, %71, %72, %73, %74, %75, %76, %77, %78, %79, "
        "%80, %81, %82, %83, %84, %85, %86, %87, %88, %89, %90, %91, %92, %93, %94, %95, "
        "%96, %97, %98, %99, %100, %101, %102, %103, %104, %105, %106, %107, %108, %109, %110, %111, "
        "%112, %113, %114, %115, %116, %117, %118, %119, %120, %121, %122, %123, %124, %125, %126, %127}, "
        "%128, %129, p, 1, 1, %130, %131;\n}\n"
        : "+f"(d[0]), "+f"(d[1]), "+f"(d[2]), "+f"(d[3]), "+f"(d[4]), "+f"(d[5]), "+f"(d[6]), "+f"(d[7]),
          "+f"(d[8]), "+f"(d[9]), "+f"(d[10]), "+f"(d[11]), "+f"(d[12]), "+f"(d[13]), "+f"(d[14]), "+f"(d[15]),
          "+f"(d[16]), "+f"(d[17]), "+f"(d[18]), "+f"(d[19]), "+f"(d[20]), "+f"(d[21]), "+f"(d[22]), "+f"(d[23]),
          "+f"(d[24]), "+f"(d[25]), "+f"(d[26]), "+f"(d[27]), "+f"(d[28]), "+f"(d[29]), "+f"(d[30]), "+f"(d[31]),
          "+f"(d[32]), "+f"(d[33]), "+f"(d[34]), "+f"(d[35]), "+f"(d[36]), "+f"(d[37]), "+f"(d[38]), "+f"(d[39]),
          "+f"(d[40]), "+f"(d[41]), "+f"(d[42]), "+f"(d[43]), "+f"(d[44]), "+f"(d[45]), "+f"(d[46]), "+f"(d[47]),
          "+f"(d[48]), "+f"(d[49]), "+f"(d[50]), "+f"(d[51]), "+f"(d[52]), "+f"(d[53]), "+f"(d[54]), "+f"(d[55]),
          "+f"(d[56]), "+f"(d[57]), "+f"(d[58]), "+f"(d[59]), "+f"(d[60]), "+f"(d[61]), "+f"(d[62]), "+f"(d[63]),
          "+f"(d[64]), "+f"(d[65]), "+f"(d[66]), "+f"(d[67]), "+f"(d[68]), "+f"(d[69]), "+f"(d[70]), "+f"(d[71]),
          "+f"(d[72]), "+f"(d[73]), "+f"(d[74]), "+f"(d[75]), "+f"(d[76]), "+f"(d[77]), "+f"(d[78]), "+f"(d[79]),
          "+f"(d[80]), "+f"(d[81]), "+f"(d[82]), "+f"(d[83]), "+f"(d[84]), "+f"(d[85]), "+f"(d[86]), "+f"(d[87]),
          "+f"(d[88]), "+f"(d[89]), "+f"(d[90]), "+f"(d[91]), "+f"(d[92]), "+f"(d[93]), "+f"(d[94]), "+f"(d[95]),
          "+f"(d[96]), "+f"(d[97]), "+f"(d[98]), "+f"(d[99]), "+f"(d[100]), "+f"(d[101]), "+f"(d[102]), "+f"(d[103]),
          "+f"(d[104]), "+f"(d[105]), "+f"(d[106]), "+f"(d[107]), "+f"(d[108]), "+f"(d[109]), "+f"(d[110]), "+f"(d[111]),
          "+f"(d[112]), "+f"(d[113]), "+f"(d[114]), "+f"(d[115]), "+f"(d[116]), "+f"(d[117]), "+f"(d[118]), "+f"(d[119]),
          "+f"(d[120]), "+f"(d[121]), "+f"(d[122]), "+f"(d[123]), "+f"(d[124]), "+f"(d[125]), "+f"(d[126]), "+f"(d[127])
        : "l"(da), "l"(db), "n"(TA), "n"(TB), "r"(keep));
}
template <int TA, int TB>
__device__ __forceinline__ void wgmma_n192(float (&d)[128], uint64_t da, uint64_t db, int keep) {
    asm volatile(
        "{\n.reg .pred p;\nsetp.ne.b32 p, %100, 0;\n"
        "wgmma.mma_async.sync.aligned.m64n192k16.f32.bf16.bf16 "
        "{%0, %1, %2, %3, %4, %5, %6, %7, %8, %9, %10, %11, %12, %13, %14, %15, "
        "%16, %17, %18, %19, %20, %21, %22, %23, %24, %25, %26, %27, %28, %29, %30, %31, "
        "%32, %33, %34, %35, %36, %37, %38, %39, %40, %41, %42, %43, %44, %45, %46, %47, "
        "%48, %49, %50, %51, %52, %53, %54, %55, %56, %57, %58, %59, %60, %61, %62, %63, "
        "%64, %65, %66, %67, %68, %69, %70, %71, %72, %73, %74, %75, %76, %77, %78, %79, "
        "%80, %81, %82, %83, %84, %85, %86, %87, %88, %89, %90, %91, %92, %93, %94, %95}, "
        "%96, %97, p, 1, 1, %98, %99;\n}\n"
        : "+f"(d[0]), "+f"(d[1]), "+f"(d[2]), "+f"(d[3]), "+f"(d[4]), "+f"(d[5]), "+f"(d[6]), "+f"(d[7]),
          "+f"(d[8]), "+f"(d[9]), "+f"(d[10]), "+f"(d[11]), "+f"(d[12]), "+f"(d[13]), "+f"(d[14]), "+f"(d[15]),
          "+f"(d[16]), "+f"(d[17]), "+f"(d[18]), "+f"(d[19]), "+f"(d[20]), "+f"(d[21]), "+f"(d[22]), "+f"(d[23]),
          "+f"(d[24]), "+f"(d[25]), "+f"(d[26]), "+f"(d[27]), "+f"(d[28]), "+f"(d[29]), "+f"(d[30]), "+f"(d[31]),
          "+f"(d[32]), "+f"(d[33]), "+f"(d[34]), "+f"(d[35]), "+f"(d[36]), "+f"(d[37]), "+f"(d[38]), "+f"(d[39]),
          "+f"(d[40]), "+f"(d[41]), "+f"(d[42]), "+f"(d[43]), "+f"(d[44]), "+f"(d[45]), "+f"(d[46]), "+f"(d[47]),
          "+f"(d[48]), "+f"(d[49]), "+f"(d[50]), "+f"(d[51]), "+f"(d[52]), "+f"(d[53]), "+f"(d[54]), "+f"(d[55]),
          "+f"(d[56]), "+f"(d[57]), "+f"(d[58]), "+f"(d[59]), "+f"(d[60]), "+f"(d[61]), "+f"(d[62]), "+f"(d[63]),
          "+f"(d[64]), "+f"(d[65]), "+f"(d[66]), "+f"(d[67]), "+f"(d[68]), "+f"(d[69]), "+f"(d[70]), "+f"(d[71]),
          "+f"(d[72]), "+f"(d[73]), "+f"(d[74]), "+f"(d[75]), "+f"(d[76]), "+f"(d[77]), "+f"(d[78]), "+f"(d[79]),
          "+f"(d[80]), "+f"(d[81]), "+f"(d[82]), "+f"(d[83]), "+f"(d[84]), "+f"(d[85]), "+f"(d[86]), "+f"(d[87]),
          "+f"(d[88]), "+f"(d[89]), "+f"(d[90]), "+f"(d[91]), "+f"(d[92]), "+f"(d[93]), "+f"(d[94]), "+f"(d[95])
        : "l"(da), "l"(db), "n"(TA), "n"(TB), "r"(keep));
}
template <int TA, int TB, int O>
__device__ __forceinline__ void wgmma_n64(float (&d)[128], uint64_t da, uint64_t db, int keep) {
    asm volatile(
        "{\n.reg .pred p;\nsetp.ne.b32 p, %36, 0;\n"
        "wgmma.mma_async.sync.aligned.m64n64k16.f32.bf16.bf16 "
        "{%0, %1, %2, %3, %4, %5, %6, %7, %8, %9, %10, %11, %12, %13, %14, %15, "
        "%16, %17, %18, %19, %20, %21, %22, %23, %24, %25, %26, %27, %28, %29, %30, %31}, "
        "%32, %33, p, 1, 1, %34, %35;\n}\n"
        : "+f"(d[O + 0]), "+f"(d[O + 1]), "+f"(d[O + 2]), "+f"(d[O + 3]), "+f"(d[O + 4]), "+f"(d[O + 5]), "+f"(d[O + 6]), "+f"(d[O + 7]),
          "+f"(d[O + 8]), "+f"(d[O + 9]), "+f"(d[O + 10]), "+f"(d[O + 11]), "+f"(d[O + 12]), "+f"(d[O + 13]), "+f"(d[O + 14]), "+f"(d[O + 15]),
          "+f"(d[O + 16]), "+f"(d[O + 17]), "+f"(d[O + 18]), "+f"(d[O + 19]), "+f"(d[O + 20]), "+f"(d[O + 21]), "+f"(d[O + 22]), "+f"(d[O + 23]),
          "+f"(d[O + 24]), "+f"(d[O + 25]), "+f"(d[O + 26]), "+f"(d[O + 27]), "+f"(d[O + 28]), "+f"(d[O + 29]), "+f"(d[O + 30]), "+f"(d[O + 31])
        : "l"(da), "l"(db), "n"(TA), "n"(TB), "r"(keep));
}
template <int O>
__device__ __forceinline__ void wgmma_n64_rs(float (&d)[128], uint32_t a0, uint32_t a1, uint32_t a2, uint32_t a3, uint64_t db) {
    asm volatile(
        "{\n.reg .pred p;\nsetp.ne.b32 p, 1, 0;\n"
        "wgmma.mma_async.sync.aligned.m64n64k16.f32.bf16.bf16 "
        "{%0, %1, %2, %3, %4, %5, %6, %7, %8, %9, %10, %11, %12, %13, %14, %15, "
        "%16, %17, %18, %19, %20, %21, %22, %23, %24, %25, %26, %27, %28, %29, %30, %31}, "
        "{%32, %33, %34, %35}, %36, p, 1, 1, 1;\n}\n"
        : "+f"(d[O + 0]), "+f"(d[O + 1]), "+f"(d[O + 2]), "+f"(d[O + 3]), "+f"(d[O + 4]), "+f"(d[O + 5]), "+f"(d[O + 6]), "+f"(d[O + 7]),
          "+f"(d[O + 8]), "+f"(d[O + 9]), "+f"(d[O + 10]), "+f"(d[O + 11]), "+f"(d[O + 12]), "+f"(d[O + 13]), "+f"(d[O + 14]), "+f"(d[O + 15]),
          "+f"(d[O + 16]), "+f"(d[O + 17]), "+f"(d[O + 18]), "+f"(d[O + 19]), "+f"(d[O + 20]), "+f"(d[O + 21]), "+f"(d[O + 22]), "+f"(d[O + 23]),
          "+f"(d[O + 24]), "+f"(d[O + 25]), "+f"(d[O + 26]), "+f"(d[O + 27]), "+f"(d[O + 28]), "+f"(d[O + 29]), "+f"(d[O + 30]), "+f"(d[O + 31])
        : "r"(a0), "r"(a1), "r"(a2), "r"(a3), "l"(db));
}

constexpr uint64_t kDescHi = (uint64_t)(64u | 0x40000000u) << 32;
template <int MODE>
__device__ __forceinline__ void mma_kblock(float (&acc)[128], uint32_t a_lo, uint32_t b_lo, int keep) {
    constexpr uint32_t HALF = (MODE == 1) ? 12288u : 16384u;
    constexpr bool BN = (MODE == 1 || MODE == 2);
#pragma unroll
    for (int kk = 0; kk < 4; ++kk) {
        const uint32_t ao = (MODE == 3) ? kk * 2048u : kk * 32u;
        const uint32_t bo = BN ? ((kk >> 1) * HALF + (kk & 1) * 2048u) : kk * 32u;
        const uint64_t da = kDescHi | (uint64_t)(a_lo + (ao >> 4) + (1u << 16));
        const uint64_t db = kDescHi | (uint64_t)(b_lo + (bo >> 4) + (BN ? (256u << 16) : (1u << 16)));
        if (MODE == 1) wgmma_n192<0, 1>(acc, da, db, kk == 0 ? keep : 1);
        else wgmma_n256<(MODE == 3), BN>(acc, da, db, kk == 0 ? keep : 1);
    }
}

struct Params {
    Scratch* s;
    const __nv_bfloat16* x;
    const __nv_bfloat16* b_re;
    const __nv_bfloat16* b_im;
    const __nv_bfloat16* gate_w;
    const __nv_bfloat16* lam_re;
    const __nv_bfloat16* lam_im;
    const __nv_bfloat16* log_dt;
    const __nv_bfloat16* dskip;
    const __nv_bfloat16* b1;
    const __nv_bfloat16* b2;
    int swap;
};

#define CMUL(rr, ri, ar, ai, br, bi) do { float _r = (ar) * (br) - (ai) * (bi); float _i = (ar) * (bi) + (ai) * (br); rr = _r; ri = _i; } while (0)
#define CFMA(rr, ri, ar, ai, br, bi) do { float _r = fmaf(-(ai), (bi), fmaf((ar), (br), rr)); float _i = fmaf((ai), (br), fmaf((ar), (bi), ri)); rr = _r; ri = _i; } while (0)

#define KB_OPEN(IT, LAST)                                                                        \
    KT(IT, 0);                                                                                   \
    if (ORDER && (LAST) && wg == 1) bar_sync(7, 256);                                            \
    mbar_wait(bar_full + 8 * ((IT) & 3), ((IT) >> 2) & 1);                                \
    KT(IT, 1);
#define KB_CLOSE(IT, LAST, REL)                                                                  \
    if (ORDER && (LAST) && wg == 0) bar_arrive(7, 256);                                          \
    wgmma_wait<1>();                                                                             \
    if (lane < 2 && (REL)) mbar_arrive_cluster(rel_addr + 8 * (((IT) - 1) & 3));
#define KBLOCK(MODE, IT, FIRST, LAST)                                                            \
    {                                                                                            \
        const uint32_t so = ((IT) & 3) * (kStageBytes >> 4);                                     \
        KB_OPEN(IT, LAST);                                                                       \
        wgmma_fence();                                                                           \
        mma_kblock<MODE>(acc, a_lo + so, b_lo + so, !(FIRST));                                   \
        wgmma_commit();                                                                          \
        KB_CLOSE(IT, LAST, !(FIRST));                                                            \
    }
#define TILE_END() do { wgmma_wait<0>(); if (lane < 2) mbar_arrive_cluster(rel_addr + 24); } while (0)

__global__ void __cluster_dims__(2, 1, 1) __launch_bounds__(384, 1)
fused_kernel(const __grid_constant__ CUtensorMap mB, const __grid_constant__ CUtensorMap mXs, const __grid_constant__ CUtensorMap mXf,
             const __grid_constant__ CUtensorMap mW1b, const __grid_constant__ CUtensorMap mW1a, const __grid_constant__ CUtensorMap mHs,
             const __grid_constant__ CUtensorMap mHf, const __grid_constant__ CUtensorMap mCre, const __grid_constant__ CUtensorMap mCim,
             const __grid_constant__ CUtensorMap mW2, const __grid_constant__ CUtensorMap mW2n, const __grid_constant__ CUtensorMap mW2p,
             const __grid_constant__ CUtensorMap mHf3, const __grid_constant__ CUtensorMap mOut, const Params p) {
    extern __shared__ __align__(1024) uint8_t smem_raw[];
    if (PFTOP) { prefetch_map(&mB); prefetch_map(&mXs); }
    const uint32_t sbase = smem_u32(smem_raw);
    if ((sbase & 0x3ffffu) != kSmemOrg) return;
    const uint32_t bar_full = sbase + kBarOff, bar_empty = bar_full + 32, bar_dep = bar_full + 64;
    const uint32_t bar_x = bar_full + 88, bar_c = bar_full + 96, role_s = bar_full + 104, bar_role = bar_full + 120, tag_s = bar_full + 112 + (threadIdx.x & 1) * 4;

    const int tid = threadIdx.x, lane = tid & 31;
    const int warp = __shfl_sync(0xffffffffu, tid >> 5, 0);
    const uint32_t rank = blockIdx.x & 1;

    int pref;
    {
        unsigned smid;
        asm("mov.u32 %0, %%smid;" : "=r"(smid));
        const int t = smid >> 1, u = t - 32, d = (u * 37) >> 8;
        pref = (t < 32) ? (t & 7) * 8 + (t >> 3) : (t < 60) ? (1 + u - 7 * d) * 8 + 4 + d : ((t - 58) & 7);
    }
    STAMP(tid == 0, 0);
    int role = pref;
#define ROLE_VARS()                                                                                               \
    const int c = role >> 3;                                                             \
    const int j8 = role & 7;                                                        \
    const int cb = j8 * 2 + (int)rank;                                             \
    const int rb = 2 * c + (int)rank;                                               \
    const int kh = j8 >> 2;                 \
    const int colK = (j8 & 3) * 256 + kh * 128, colS = colK ^ 128;    \
    (void)cb; (void)rb; (void)colS;

#define INIT_ALL()                                                                                    \
    if (warp == INITW && elect_one()) {                                                               \
        if (!PFTOP) { prefetch_map(&mB); prefetch_map(&mXs); }                                        \
        _Pragma("unroll") for (int s = 0; s < kStages; ++s) {                                         \
            mbar_init(bar_full + 8 * s, 1);                                                           \
            mbar_init(bar_empty + 8 * s, 16);                                                         \
            mbar_init(bar_dep + 8 * s, 1);                                \
        }                                                                                             \
        mbar_init(bar_c, 96);                                                                         \
        mbar_init(bar_role, 1);                                                                       \
        asm volatile("fence.mbarrier_init.release.cluster;\nfence.proxy.async.shared::cta;" ::: "memory"); \
        mbar_expect_tx(bar_full, 49152);            \
        tma4(sbase, &mB, bar_full, 0, 0, 0, ((pref & 7) * 2 + (int)rank) * 8);                        \
        if (!MC0) {                                                                                   \
        tma5(sbase + kABytes, &mXs, bar_full, 0, 0, 0, 0, pref >> 3);                                 \
        tma5(sbase + kABytes + 16384, &mXs, bar_full, 0, 0, 0, 16, pref >> 3);                        \
        }                                                                                             \
        mbar_expect_tx(bar_x, 2048);                                                                  \
        bulk_load(sbase + kXOff, p.gate_w, 2048, bar_x);                                              \
        mbar_expect_tx(bar_role, 8);                                                                  \
    }
    if (PRODCOND) {
        asm volatile("setmaxnreg.dec.sync.aligned.u32 24;");
        unsigned taken = 0;
        if (tid == 352 && rank == 0) {
            taken = atom_exch(&p.s->claim[pref], 1u);
        }
        __syncwarp();
        cluster_arrive();
        cluster_wait();
        if (warp > 8) {
            if (tid == 352) {
#pragma unroll 1
                for (int i = 0; taken != 0 && i < 64; ++i) { role = i + 256; taken = atom_exch(&p.s->claim[i], 1u); }
                st_async32(mapa(role_s + 4 * rank, 0), role, mapa(bar_role, 0));
                st_async32(mapa(role_s + 4 * rank, 1), role, mapa(bar_role, 1));
            }
            __syncwarp();
            mbar_wait(bar_role, 0);
            role = __shfl_sync(0xffffffffu, (int)lds32(role_s), 0) & 63;
            ROLE_VARS();
            if (warp == 11) {
                if (lane < 12) prefetch_map(&mXf + lane);
#pragma unroll 1
                for (int en = lane; en < 88; en += 32) {
                    const int J = en >> 2;
                    const __nv_bfloat16* src = ((J < 14) ? p.b1 : (J < 18) ? p.dskip : p.b2) + 32 * J + 2 * (en & 3) +
                                               ((J < 6) ? 2048 + 192 * j8 : (J < 14) ? 256 * j8 - 192 : colK - ((J < 18) ? 448 : 576));
                    sts128(sbase + kBiasOff + en * 16, ldg32(src), ldg32(src + 8), ldg32(src + 16), ldg32(src + 24));
                }
                mbar_arrive_local(bar_c);
            } else {
                {
                    sts32(tag_s, ld_relaxed32(&p.s->epoch) + 1);
                    const int ch = cb * 64 + (tid - 288);
                    const uint32_t t_s = sbase + kTabOff + (tid - 288) * 64;
                    const float Lr = bf_lo(ldg16(p.lam_re + ch)), Li = bf_lo(ldg16(p.lam_im + ch));
                    const float dt = bf16_round(expf(bf_lo(ldg16(p.log_dt + ch))));
                    const float ea = expf(dt * Lr);
                    float lr, li;
                    sincospif((dt * Li) * 0.31830988618379067f, &li, &lr);
                    lr *= ea; li *= ea;
                    const float nr = lr - 1.0f, ni = li;
                    const bool big = fabsf(Lr) >= fabsf(Li);
                    const float u = big ? Lr : Li, v = big ? Li : Lr;
                    const float t = v / u, d = 2.0f / fmaf(v, t, u);
                    const float cr = (big ? fmaf(ni, t, nr) : fmaf(nr, t, ni)) * d, ci = (big ? fmaf(-nr, t, ni) : fmaf(ni, t, -nr)) * d;
                    if (p.swap) li = -li;
                    const float m00 = p.swap ? -ci : cr, m01 = p.swap ? cr : -ci, m10 = p.swap ? -cr : -ci, m11 = p.swap ? -ci : -cr;
#pragma unroll
                    for (int q = 0; q < 4; ++q) {
                        sts128f(t_s + q * 16, lr, li, m00, m01);
                        sts128f(t_s + 12288 + q * 16, 0.f, 0.f, 0.f, 0.f);
                    }
#pragma unroll 1
                    for (int i = 0; i < 6; ++i) CMUL(lr, li, lr, li, lr, li);
                    float ar, ai, br, bi;
                    CMUL(ar, ai, lr, li, lr, li);
                    CMUL(br, bi, ar, ai, lr, li);
                    sts128f(t_s + 4096, m10, m11, 0.f, 0.f);
#pragma unroll
                    for (int q = 1; q < 4; ++q) sts128f(t_s + 4096 + q * 16, m10, m11, lr, li);
                    sts128f(t_s + 8192, 0.f, 0.f, 1.f, 0.f);
                    sts128f(t_s + 8192 + 16, 0.f, 0.f, lr, li);
                    sts128f(t_s + 8192 + 32, ar, ai, ar, ai);
                    sts128f(t_s + 8192 + 48, ar, ai, br, bi);
                    CMUL(ar, ai, ar, ai, ar, ai);
                    br = 1.f; bi = 0.f;
#pragma unroll 1
                    for (int k = c - 1; k >= 0; --k) {
                        sts64f(t_s + 12288 + (k & 3) * 16 + (k >> 2) * 8, br, bi);
                        CMUL(br, bi, br, bi, ar, ai);
                    }
                    mbar_arrive_local(bar_c);
                }
                if (warp == 9) {
#pragma unroll 1
                    for (int ev = 0; ev < 3; ++ev) {
                        if (ev == 2) {
                            uint8_t* box = p.s->X + (size_t)(role * 2 + rank) * kXBytes + lane * 16;
#pragma unroll 1
                            for (int i = 0; i < kXBytes; i += 512) stg128(box + i, 0, 0, 0, 0);
                        }
                        bar_sync(3 + ev, 288);
                        if (lane == 0) {
                            unsigned* cnt = &p.s->cnt[(ev == 0 ? c : 16 * ev - 8 + rb) * 32];
                            asm volatile("fence.acq_rel.gpu;\nfence.proxy.async.global;" ::: "memory");
                            asm volatile("red.relaxed.gpu.global.add.u32 [%0], 1;" ::"l"(cnt) : "memory");
                        }
                        __syncwarp();
                    }
                } else if (lane == 0) {
                    const unsigned tag = lds32(tag_s);
#pragma unroll 1
                    for (int ev = 0; ev < 3; ++ev) {
                        wait_counter(&p.s->cnt[(ev == 0 ? c : 16 * ev - 8 + rb) * 32], tag * (ev == 0 ? 16u : 8u));
                        mbar_arrive_local(bar_dep + 8 * ev);
                        if (ev == 0 && atomicInc(&p.s->done, 127u) == 127u) {
                            st_relaxed32(&p.s->epoch, tag);
#pragma unroll 1
                            for (int i = 0; i < 64; i += 4) stg128(&p.s->claim[i], 0, 0, 0, 0);
                        }
                    }
                }
            }
        } else if (elect_one()) {
            int it = 1, again = 15;
            if (MC0) tma5_mc(sbase + kABytes + rank * 16384, &mXs, bar_full, 0, 0, 0, rank * 16, role >> 3);
#define ACQUIRE(BYTES)                                                   \
    const uint32_t st = sbase + (it & 3) * kStageBytes, fb = bar_full + 8 * (it & 3); \
    mbar_wait(bar_empty + 8 * (it & 3), ((it >> 2) & 1) ^ 1);     \
    mbar_expect_tx(fb, BYTES);
#pragma unroll 1
            for (; it < 16; ++it) {
                ACQUIRE(49152);
                tma4(st, &mB, fb, it * 64, 0, 0, ((role & 7) * 2 + (int)rank) * 8);
                tma5_mc(st + kABytes + rank * 16384, &mXs, fb, it * 64, 0, 0, rank * 16, role >> 3);
                if (it == again) {
                    mbar_wait(bar_role, 0);
                    const uint2 fin = lds64(role_s);
                    role = fin.x & 63;
                    if (fin.x != fin.y) { it = -1; again = 16; }
                }
            }
            ROLE_VARS();
#pragma unroll 1
            for (; it < 48; ++it) {
                const bool t1 = it < 32;
                const int k0 = (it & 15) * 64;
                ACQUIRE(t1 ? 40960 : 49152);
                tma5(st, &mXf, fb, k0, 0, 0, rank * 4, c);
                tma3_mc(st + kABytes + rank * (t1 ? 12288 : 16384), t1 ? &mW1b : &mW1a, fb, 0, k0 + rank * 32, t1 ? 32 + 3 * j8 : 4 * j8);
                if ((it & ~2) == XLDKB) {
                    const int h = (it >> 1) & 1;
                    if (h == 0) mbar_expect_tx(bar_x, 32768);
                    tma5(sbase + kXOff + h * 16384, &mXf, bar_x, colK + h * 64, 0, 0, rank * 4, c);
                }
            }
            STAMPA(true, 8);
            mbar_wait(bar_dep, 0);
            asm volatile("fence.proxy.async.global;" ::: "memory");
            STAMPA(true, 9);
#pragma unroll 1
            for (; it < 64; ++it) {
                const int k0 = (it & 15) * 64;
                ACQUIRE(49152);
                tma3(st, &mHs, fb, 0, kh * 1024 + k0, rb * 2);
                tma2_mc(st + kABytes + rank * 16384, kh ? &mCim : &mCre, fb, k0, rank ? colS : colK);
            }
            int f0 = 2048 + 768 * kh;
#pragma unroll 1
            for (; it < 88; ++it, f0 += 64) {
                if (it == 64 || it == 76) {
                    mbar_wait(bar_dep + (it == 64 ? 8 : 16), 0);
                    asm volatile("fence.proxy.async.global;" ::: "memory");
                    if (it == 76) f0 = 1024 * kh;
                }
                if (f0 == 256 * j8) f0 += 256;
                ACQUIRE(49152);
                tma2(st, &mHf, fb, f0, rb * 128);
                tma5_mc(st + kABytes + rank * 16384, &mW2, fb, 0, 0, (f0 >> 3) + 4 * rank, 0, colK >> 6);
                tma5_mc(st + kABytes + rank * 16384 + 8192, &mW2, fb, 0, 0, (f0 >> 3) + 4 * rank, 0, colS >> 6);
                if ((it >> 2) == PFKB / 4) tma2_pf(&mW2n, colK + (it & 2) * 32, 256 * (j8 ^ ((it & 1) * 4)) + 128 * rank);
            }
#pragma unroll 1
            for (; it < kTotal; ++it) {
                const int h = (it & 2) * 32;
                ACQUIRE(49152);
                STAMPD(it > 88, it - 87);
                if (it < 91) tma3(st, &mHf3, fb, 0, rb * 128 + h, 4 * (j8 ^ 4) + 2 * (it & 1));
                if (it == 90) tma3(st + kABytes, &mHf3, fb, 0, rb * 128 + h, 4 * (j8 ^ 4) + 2);
                if (it & 1) tma5_mc(st + kABytes + rank * 16384, &mW2p, fb, colK + h, 0, 0, 0, 8 * (j8 ^ 4) + 4 * rank);
                if (it == 88 || it == 90 + rank)
                    tma2_mc(sbase + kABytes + rank * 16384 + h * ((2 * kStageBytes + 16384) / 64), &mW2n, fb, colK + h, 256 * j8 + 128 * rank);
            }
        }
    } else {
        INIT_ALL();
        if (warp >= 8 - PF0LINES) {
            const int row = blockIdx.x * 32 + lane;
            const __nv_bfloat16* src = (row < 2048) ? p.x : (row < 3072) ? p.b_re - 2048 * kD : p.b_im - 3072 * kD;
            asm volatile("prefetch.global.L2 [%0];" ::"l"(src + row * kD + (7 - warp) * 64) : "memory");
        }
        __syncwarp();
        cluster_arrive();
        asm volatile("setmaxnreg.inc.sync.aligned.u32 240;");
        const int wg = warp >> 2, w = warp & 3, r = lane >> 2, q = lane & 3, tw = tid & 127;
        uint32_t a_lo = (kSmemOrg + wg * 8192) >> 4;
        constexpr uint32_t b_lo = (kSmemOrg + kABytes) >> 4;
        const uint32_t rel_addr = mapa(bar_empty, (uint32_t)(lane & 1));
        const uint32_t gate_s = sbase + kGateOff;
        float acc[128];
        uint32_t pk[64];
        unsigned tag;
        UNDEF_R(tag);

#pragma unroll
        for (int i = 0; i < 128; ++i) UNDEF_F(acc[i]);
        float gs = 0.f;
        {
            const uint32_t gx_s = sbase + kABytes + (16 * rank + 2 * warp + (lane >> 4)) * 128 +
                                  ((((lane & 15) >> 1) ^ (2 * w + (lane >> 4))) << 4) + (lane & 1) * 8;
            const uint32_t gw_s = sbase + kXOff + (lane & 15) * 8;
            uint32_t again = 15;
            cluster_wait();
#pragma unroll 1
            for (uint32_t it = 0; it < 16; ++it) {
                const uint32_t so = (it & 3) * (kStageBytes >> 4);
                KB_OPEN(it, it == 15);
                wgmma_fence();
                mma_kblock<0>(acc, a_lo + so, b_lo + so, it != 0);
                wgmma_commit();
                KB_CLOSE(it, it == 15, it + again != 15);
                STAMPA(tid == 0 && it == 0, 1);
                mbar_wait(bar_x, 0);
                const uint2 xa = lds64(gx_s + (role & 7) * 4096 + (it & 3) * kStageBytes), wa = lds64(gw_s + it * 128);
                const uint32_t pa = bf2_mul(xa.x, wa.x), pb = bf2_mul(xa.y, wa.y);
                gs += (bf_lo(pa) + bf_hi(pa)) + (bf_lo(pb) + bf_hi(pb));
                if (it == again) {
                    mbar_wait(bar_c, 0);
                    const uint2 fin = lds64(role_s);
                    role = fin.x & 63;
                    if (__shfl_sync(0xffffffffu, fin.x != fin.y, 0)) { it = -1; again = 16; gs = 0.f; }
                }
            }
        }
        role = __shfl_sync(0xffffffffu, role, 0);
        ROLE_VARS();
        {
            tag = lds32(tag_s);
#pragma unroll
            for (int o = 8; o > 0; o >>= 1) gs += __shfl_xor_sync(0xffffffffu, gs, o);
            const float g = bf16_round(__frcp_rn(1.0f + expf(-bf16_round(gs))));
            if ((lane & 15) == 0) st_relaxed64(&p.s->gate[c * 256 + (lane >> 4) + 64 * w + 4 * cb + 2 * wg], __float_as_uint(g), tag);
        }
        const uint32_t tab_s = sbase + kTabOff + tid * 16;
        const float4 k0 = lds128f(tab_s);
        TILE_END();
        STAMPA(tid == 0, 2);
#pragma unroll
        for (int s = 0; s < 64; ++s) pk[s] = pack_bf16_v(acc[4 * (s >> 1) + (s & 1)], acc[4 * (s >> 1) + 2 + (s & 1)]);
#pragma unroll
        for (int i = 0; i < 96; ++i) UNDEF_F(acc[i]);

        const float lr = k0.x, li = k0.y, m00 = k0.z, m01 = k0.w;
        float m10, m11, hr = 0.f, hi = 0.f;
        uint32_t gg[4], orr[4], oii[4];
        const int ch = cb * 64 + warp * 8 + r;
        __nv_bfloat16* hs = p.s->Hs + (size_t)ch * 2048 + c * 256 + q * 8;
#define PASS2(KB)                                                                                      \
    _Pragma("unroll") for (int s = 0; s < 64; s += 2) {                                                \
        if (pass2_kb(s) != (KB)) continue;                                                             \
        if ((s & 7) == 0) {                                                                            \
            const uint4 ga = lds128(gate_s + (q * 72 + s) * 2);                                        \
            gg[0] = ga.x; gg[1] = ga.y; gg[2] = ga.z; gg[3] = ga.w;                                    \
        }                                                                                              \
        float o0[2], o1[2];                                                                            \
        _Pragma("unroll") for (int k = 0; k < 2; ++k) {                                                \
            PIN_R(pk[s + k]);                                                                          \
            float nr = bf_lo(pk[s + k]), ni = bf_hi(pk[s + k]);                                        \
            CFMA(nr, ni, lr, li, hr, hi);                                                              \
            hr = nr; hi = ni;                                                                          \
            o0[k] = fmaf(m00, hr, m01 * hi);                                                           \
            o1[k] = fmaf(m10, hr, m11 * hi);                                                           \
        }                                                                                              \
        orr[(s >> 1) & 3] = bf2_mul(pack_bf16(o0[0], o0[1]), gg[(s >> 1) & 3]);                        \
        oii[(s >> 1) & 3] = bf2_mul(pack_bf16(o1[0], o1[1]), gg[(s >> 1) & 3]);                        \
        if ((s & 7) == 6) {                                                                            \
            stg128(hs + 32 * (s >> 3), orr[0], orr[1], orr[2], orr[3]);                                \
            stg128(hs + 1024 * 2048 + 32 * (s >> 3), oii[0], oii[1], oii[2], oii[3]);                  \
        }                                                                                              \
    }                                                                                                  \
    PIN_F(hr); PIN_F(hi);
        {
            uint4 av0, av1, gv;
            float lqr, lqi;
#pragma unroll
            for (int kb = 0; kb < 16; ++kb) {
                PIN_R(a_lo);
                KBLOCK(1, 16 + kb, kb == 0, kb == 15);
                if (kb < 4) {
#pragma unroll
                    for (int s = kb * 16; s < kb * 16 + 16; ++s) {
                        float nr = bf_lo(pk[s]), ni = bf_hi(pk[s]);
                        CFMA(nr, ni, lr, li, hr, hi);
                        hr = nr; hi = ni;
                    }
                    PIN_F(hr); PIN_F(hi);
                }
                if (kb == 2) gv = ld_relaxed2x64(&p.s->gate[c * 256 + 2 * tw]);
                if (kb == 3) {
                    const float4 k1 = lds128f(tab_s + 4096), k2 = lds128f(tab_s + 8192);
                    m10 = k1.x; m11 = k1.y; lqr = k2.z; lqi = k2.w;
                    float tr = __shfl_up_sync(0xffffffffu, hr, 1, 4), ti = __shfl_up_sync(0xffffffffu, hi, 1, 4);
                    if (q >= 1) CFMA(hr, hi, k1.z, k1.w, tr, ti);
                    tr = __shfl_up_sync(0xffffffffu, hr, 2, 4); ti = __shfl_up_sync(0xffffffffu, hi, 2, 4);
                    if (q >= 2) CFMA(hr, hi, k2.x, k2.y, tr, ti);
                    if (q == 3) st_relaxed2x64(&p.s->agg[c * 1024 + ch], __float_as_uint(hr), tag, __float_as_uint(hi), tag);
                    tr = __shfl_up_sync(0xffffffffu, hr, 1, 4); ti = __shfl_up_sync(0xffffffffu, hi, 1, 4);
                    hr = (q >= 1) ? tr : 0.f; hi = (q >= 1) ? ti : 0.f;
                }
                if (kb == 4) {
                    unsigned spins = 0;
                    while (__any_sync(0xffffffffu, gv.y != tag || gv.w != tag)) {
                        if (++spins > kSpinLimit) break;
                        gv = ld_relaxed2x64(&p.s->gate[c * 256 + 2 * tw]);
                    }
                    sts32(gate_s + ((tw >> 5) * 72 + 2 * lane) * 2, __byte_perm(gv.x, gv.z, 0x7632));
                }
                if (kb == 5) {
                    av0 = make_uint4(0, tag, 0, tag); av1 = av0;
                    if (q < c) av0 = ld_relaxed2x64(&p.s->agg[q * 1024 + ch]);
                    if (q + 4 < c) av1 = ld_relaxed2x64(&p.s->agg[(q + 4) * 1024 + ch]);
                    bar_sync(1 + wg, 128);
                }
                if (kb == 6) {
                    const float4 k3 = lds128f(tab_s + 12288);
                    unsigned spins = 0;
                    while (__any_sync(0xffffffffu, av0.y != tag || av0.w != tag || av1.y != tag || av1.w != tag)) {
                        if (++spins > kSpinLimit) break;
                        if (q < c) av0 = ld_relaxed2x64(&p.s->agg[q * 1024 + ch]);
                        if (q + 4 < c) av1 = ld_relaxed2x64(&p.s->agg[(q + 4) * 1024 + ch]);
                    }
                    float vr, vi;
                    CMUL(vr, vi, k3.x, k3.y, __uint_as_float(av0.x), __uint_as_float(av0.z));
                    CFMA(vr, vi, k3.z, k3.w, __uint_as_float(av1.x), __uint_as_float(av1.z));
                    vr += __shfl_xor_sync(0xffffffffu, vr, 1); vi += __shfl_xor_sync(0xffffffffu, vi, 1);
                    vr += __shfl_xor_sync(0xffffffffu, vr, 2); vi += __shfl_xor_sync(0xffffffffu, vi, 2);
                    CFMA(hr, hi, lqr, lqi, vr, vi);
                }
                if (kb >= 6) { PASS2(kb); }
            }
            TILE_END();
        }
        STAMPA(tid == 0, 3);
#pragma unroll
        for (int i = 0; i < 48; ++i) pk[i] = pack_bf16_v(acc[2 * i], acc[2 * i + 1]);
#pragma unroll
        for (int i = 0; i < 128; ++i) UNDEF_F(acc[i]);

        PIN_R(a_lo);
        KBLOCK(2, 32, true, false);
        PASS2(16);
        PIN_R(a_lo);
        KBLOCK(2, 33, false, false);
        PASS2(17);
        bar_arrive(3, 288);
        const uint32_t gate_row = gate_s + ((2 * (w & 1)) * 72 + 8 * (4 * rank + 2 * wg + (w >> 1)) + r) * 2;
        uint32_t om0, om1;
        {
            const float a = 1.0f - bf_lo(lds16(gate_row)), b = 1.0f - bf_lo(lds16(gate_row + 72 * 2));
            om0 = pack_bf16(a, a); om1 = pack_bf16(b, b);
        }
        __nv_bfloat16* hf = p.s->Hf + (size_t)(rb * 128 + wg * 64 + w * 16 + r) * kF + q * 8 + 2048 + 192 * j8;
        uint32_t bias_s = sbase + kBiasOff + q * 16;
#define FFN_SLICE(J)                                                                                   \
    {                                                                                                  \
        const uint4 bv = lds128(bias_s + (J) * 64);                                                    \
        const uint32_t bb[4] = {bv.x, bv.y, bv.z, bv.w};                                               \
        _Pragma("unroll") for (int jj = 0; jj < 4; ++jj) {                                             \
            const uint32_t r0 = bf2_add_relu(pk[8 * (J) + 2 * jj], bb[jj]), r1 = bf2_add_relu(pk[8 * (J) + 2 * jj + 1], bb[jj]); \
            pk[8 * (J) + 2 * jj] = bf2_mul(bf2_mul(r0, r0), om0);                                      \
            pk[8 * (J) + 2 * jj + 1] = bf2_mul(bf2_mul(r1, r1), om1);                                  \
        }                                                                                              \
        stg128(hf + 32 * (J), pk[8 * (J)], pk[8 * (J) + 2], pk[8 * (J) + 4], pk[8 * (J) + 6]);         \
        stg128(hf + 8 * kF + 32 * (J), pk[8 * (J) + 1], pk[8 * (J) + 3], pk[8 * (J) + 5], pk[8 * (J) + 7]); \
    }
        const uint32_t x_s = sbase + kXOff + (wg * 64 + w * 16 + (lane & 15)) * 128 + (((lane >> 4) ^ (lane & 7)) << 4);
        {
            uint32_t j = 0, nsl = 6;
#pragma unroll 1
            for (uint32_t it = 34; it < 88; ++it, ++j) {
                const uint32_t so = (it & 3) * (kStageBytes >> 4);
                if (wg == 1 && (it == 88 - SKEW || (ORDER && it == 47))) bar_sync(7, 256);
                KB_OPEN(it, false);
                if ((it & ~15u) == 48) {
                    wgmma_fence();
                    mma_kblock<3>(acc, a_lo + so, b_lo + so, it != 48);
                    wgmma_commit();
                } else {
                    wgmma_fence();
                    mma_kblock<2>(acc, a_lo + so, b_lo + so, 1);
                    wgmma_commit();
                }
                if (wg == 0 && (it == 87 || (ORDER && it == 47))) bar_arrive(7, 256);
                KB_CLOSE(it, false, it != 48);
                if (j < nsl) {
                    if (j & 4) {
                        if (j & 2) { if (j & 1) FFN_SLICE(7) else FFN_SLICE(6) } else { if (j & 1) FFN_SLICE(5) else FFN_SLICE(4) }
                    } else {
                        if (j & 2) { if (j & 1) FFN_SLICE(3) else FFN_SLICE(2) } else { if (j & 1) FFN_SLICE(1) else FFN_SLICE(0) }
                    }
                    if (j + 1 == nsl) bar_arrive(1 + (nsl >> 1), 288);
                } else if (it == 47) {
                    hf += 64 * j8 - 2048;
                    bias_s += 6 * 64;
                    j = -1; nsl = 8;
                    TILE_END();
                    STAMPA(tid == 0, 4);
#pragma unroll
                    for (int i = 0; i < 64; ++i) pk[i] = pack_bf16_v(acc[2 * i], acc[2 * i + 1]);
                } else if ((it >> 2) == ETKB / 4) {
                    mbar_wait(bar_x, 1);
                    const uint32_t xa_s = (x_s ^ ((it & 1) << 6)) + (it & 2) * 8192;
                    const float g0 = bf_lo(lds16(gate_row)), g1 = bf_lo(lds16(gate_row + 72 * 2));
                    const float o0f = bf_lo(om0), o1f = bf_lo(om1);
                    const uint4 dq = lds128(bias_s + (8 + (it & 3)) * 64), bq = lds128(bias_s + (12 + (it & 3)) * 64);
                    const uint4 xa = ldsm4(xa_s), xb = ldsm4(xa_s ^ 32);
                    const uint32_t dv[4] = {dq.x, dq.y, dq.z, dq.w}, bv2[4] = {bq.x, bq.y, bq.z, bq.w};
                    uint32_t xv[8] = {xa.x, xa.y, xa.z, xa.w, xb.x, xb.y, xb.z, xb.w};
#pragma unroll
                    for (int jj = 0; jj < 4; ++jj) {
                        const uint32_t x0 = bf2_mul(xv[2 * jj], dv[jj]), x1 = bf2_mul(xv[2 * jj + 1], dv[jj]);
                        const float bl = bf_lo(bv2[jj]), bh = bf_hi(bv2[jj]);
                        xv[2 * jj] = pack_bf16(fmaf(g0, bf_lo(x0), o0f * bl), fmaf(g0, bf_hi(x0), o0f * bh));
                        xv[2 * jj + 1] = pack_bf16(fmaf(g1, bf_lo(x1), o1f * bl), fmaf(g1, bf_hi(x1), o1f * bh));
                    }
                    sts128(xa_s, xv[0], xv[1], xv[2], xv[3]);
                    sts128(xa_s ^ 32, xv[4], xv[5], xv[6], xv[7]);
                }
            }
        }
#define OWN_MMA(H, P)                                                                                  \
    wgmma_fence();                                                                                     \
    _Pragma("unroll") for (int i = 8 * (P); i < 8 * (P) + 8; ++i)                                      \
        wgmma_n64_rs<32 * (H)>(acc, pk[4 * i], pk[4 * i + 1], pk[4 * i + 2], pk[4 * i + 3],            \
                               kDescHi | (uint64_t)(b_lo + (((H) * (2 * kStageBytes + 16384) + i * 2048) >> 4) + (256u << 16))); \
    wgmma_commit();
#define OTHER_MMA(H, P)                                                                                \
    PIN_R(a_lo); PIN_R(a_hi);                                                                          \
    wgmma_fence();                                                                                     \
    _Pragma("unroll") for (int i = 0; i < 8; ++i)                                                      \
        wgmma_n64<0, 1, 32 * (H)>(acc, kDescHi | (uint64_t)(((P) ? a_hi : a_lo) + (((i >> 2) * 8192 + (i & 3) * 32) >> 4) + (1u << 16)), \
                               kDescHi | (uint64_t)(b_lo + (((2 * (H) + 1) * kStageBytes + (8 * (P) + i) * 2048) >> 4) + (256u << 16)), 1); \
    wgmma_commit();
#define RXLOAD(H)                                                                                      \
    {                                                                                                  \
        if ((H) == 0) rs = ld_relaxed32((const unsigned*)(xi + 4096 - lane * 12));                     \
        _Pragma("unroll") for (int u = 0; u < 4; ++u) rx[u] = ld_relaxed2x64(xi + (4 * (H) + u) * 512); \
    }
#define RXCHECK(H)                                                                                     \
    {                                                                                                  \
        unsigned spins = 0;                                                                            \
        _Pragma("unroll 1") while (true) {                                                             \
            uint32_t ok = rs != 0;                                                                     \
            _Pragma("unroll") for (int u = 0; u < 4; ++u) ok &= rx[u].x & rx[u].z;                     \
            if (__all_sync(0xffffffffu, ok) || ++spins > kSpinLimit) break;                            \
            RXLOAD(H);                                                                                 \
            RESPIN();                                                                                  \
        }                                                                                              \
    }
#define UNPACK(H)                                                                                      \
    _Pragma("unroll") for (int u = 0; u < 4; ++u) {                                                    \
        const uint32_t rr[4] = {rx[u].x, rx[u].y, rx[u].z, rx[u].w}, ee[4] = {ev[u].x, ev[u].y, ev[u].z, ev[u].w}; \
        _Pragma("unroll") for (int k = 0; k < 4; ++k) {                                                \
            const float2 f = __half22float2(*reinterpret_cast<const __half2*>(&rr[k]));                \
            ex[8 * u + 2 * k] = (H) ? f.x : fmaf(f.x, xsc, bf_lo(ee[k]));                              \
            ex[8 * u + 2 * k + 1] = (H) ? f.y : fmaf(f.y, xsc, bf_hi(ee[k]));                          \
            PIN_F(ex[8 * u + 2 * k]); PIN_F(ex[8 * u + 2 * k + 1]);                                    \
        }                                                                                              \
    }
#define PUT(H, BASE, STEP)                                                                             \
    _Pragma("unroll") for (int i = 0; i < 32; i += 2) {                                                \
        PIN_F(acc[32 * (H) + i]); PIN_F(acc[32 * (H) + i + 1]);                                        \
        sts64f((BASE) + ((put_o ^ (((i >> 2) & 3) << 5) ^ ((i & 2) * 72)) + (i >> 4) * (STEP)),        \
               fmaf(ex[i], (H) ? xsc : 1.0f, acc[32 * (H) + i]), fmaf(ex[i + 1], (H) ? xsc : 1.0f, acc[32 * (H) + i + 1])); \
    }
#define PUT_GO(H, BASE, STEP)                                                                          \
    fence_async_smem();                                                                                \
    __syncwarp();                                                                                      \
    if (lead) {                                                                                        \
        tma4_store(&mOut, BASE, tb, (colK >> 5) + 2 * (H));                                            \
        tma4_store(&mOut, (BASE) + (STEP), tb, (colK >> 5) + 2 * (H) + 1);                             \
        bulk_commit();                                                                                 \
    }
        TILE_END();
        sched_fence(a_lo);
        {
            const uint8_t* xi = p.s->X + (size_t)(role * 2 + rank) * kXBytes + warp * 4224 + lane * 16;
            uint8_t* xo = const_cast<uint8_t*>(xi) + (kh ? -8 * kXBytes : 8 * kXBytes);
            const uint32_t e_s = sbase + kXOff + warp * 2048;
            const bool lead = lane == 0;
            uint4 rx[4], ev[8];
            uint32_t rs;
            float ex[32];
            STAMP(tid == 0, 15); STAMPB(tid == 128, 1);
            mbar_wait(bar_full, 0);
#pragma unroll
            for (int u = 0; u < 8; ++u) ev[u] = lds128((x_s ^ ((u & 3) << 5)) + (u >> 2) * 16384);
            sched_fence(a_lo);
            {
                float m[4] = {0.f, 0.f, 0.f, 0.f};
#pragma unroll
                for (int i = 64; i < 128; ++i) m[i & 3] = fmaxf(m[i & 3], fabsf(acc[i]));
                const uint32_t eb = max(__float_as_uint(fmaxf(fmaxf(m[0], m[1]), fmaxf(m[2], m[3]))) >> 23, 15u);
                const float xsc = __uint_as_float((268u - eb) << 23);
                st_relaxed32(xo + 4096 - lane * 12, (eb - 14u) << 23);
#pragma unroll
                for (int u = 0; u < 8; ++u) {
                    const int v = 64 + 8 * u;
                    st_relaxed2x64(xo + u * 512, pack_f16(acc[v] * xsc, acc[v + 1] * xsc) | 1, pack_f16(acc[v + 2] * xsc, acc[v + 3] * xsc),
                                   pack_f16(acc[v + 4] * xsc, acc[v + 5] * xsc) | 1, pack_f16(acc[v + 6] * xsc, acc[v + 7] * xsc));
                }
                STAMP(tid == 0, 12); STAMPB(tid == 128, 2);
            }
            a_lo += wg * ((2 * kStageBytes - 8192) >> 4);
            uint32_t a_hi = a_lo + (wg ? 16384 >> 4 : kStageBytes >> 4);
            const int tb = c * 256 + 128 * (w & 1) + 8 * (4 * rank + 2 * wg + (w >> 1));
            const uint32_t put_o = r * 256 + (r & 3) * 32 + q * 8;
            if (wg == 1) bar_sync(9, 256);
            sched_fence(a_lo);
            STAMPB(tid == 128, 3);
            OWN_MMA(0, 0);
            if (RXPOS == 0) { sched_fence(a_lo); RXLOAD(0); sched_fence(a_lo); }
            OWN_MMA(0, 1);
            STAMPB(tid == 0, 9);
            mbar_wait(bar_full + 8 + 8 * wg, 0);
            if (RXPOS == 1) { RXLOAD(0); sched_fence(a_lo); }
            OTHER_MMA(0, 0);
            if (RXPOS == 2) { sched_fence(a_lo); RXLOAD(0); sched_fence(a_lo); }
            OTHER_MMA(0, 1);
            bar_arrive(9 - wg, 256);
            sched_fence(a_lo);
            STAMPB(tid == 0, 10);
            if (RXPOS == 3) RXLOAD(0);
#pragma unroll
            for (int u = 4; u < 8; ++u) {
                const uint32_t ee[4] = {ev[u].x, ev[u].y, ev[u].z, ev[u].w};
#pragma unroll
                for (int k = 0; k < 4; ++k) {
                    const int v = 8 * u + 2 * k;
                    acc[v] += bf_lo(ee[k]); acc[v + 1] += bf_hi(ee[k]);
                    PIN_F(acc[v]); PIN_F(acc[v + 1]);
                }
            }
            RXCHECK(0);
            STAMP(tid == 0, 13);
            const float xsc = __uint_as_float(rs);
            UNPACK(0);
            sched_fence(a_lo);
            wgmma_wait<0>();
            STAMPB(tid == 0, 11); STAMPB(tid == 128, 8);
            PUT(0, e_s, 16384);
            PUT_GO(0, e_s, 16384);
            RXLOAD(1);
            STAMP(tid == 0, 14);
            bar_sync(8 + 2 * wg, 256);
            sched_fence(a_lo);
            OWN_MMA(1, 0);
            mbar_wait(bar_full + 24, 0);
            OWN_MMA(1, 1);
            OTHER_MMA(1, 0);
            OTHER_MMA(1, 1);
            if (wg == 0) bar_arrive(10, 256);
            sched_fence(a_lo);
            RXCHECK(1);
            UNPACK(1);
            sched_fence(a_lo);
            wgmma_wait<0>();
            STAMP(tid == 0, 6); STAMPB(tid == 128, 4);
            const uint32_t o_s = sbase + wg * 2 * kStageBytes + w * 2048;
            PUT(1, o_s, 8192);
            PUT_GO(1, o_s, 8192);
            if (lead) bulk_wait_read();
        }
        STAMP(tid == 0, 7);
        STAMP(tid == 128, 5);
    }
}

typedef CUresult (*EncodeFn)(CUtensorMap*, CUtensorMapDataType, cuuint32_t, void*, const cuuint64_t*, const cuuint64_t*,
                             const cuuint32_t*, const cuuint32_t*, CUtensorMapInterleave, CUtensorMapSwizzle,
                             CUtensorMapL2promotion, CUtensorMapFloatOOBfill);

bool encode(EncodeFn fn, CUtensorMap* m, const void* base, int rank, const cuuint64_t* dims, const cuuint64_t* strides,
            const cuuint32_t* box, CUtensorMapDataType type = CU_TENSOR_MAP_DATA_TYPE_BFLOAT16) {
    cuuint32_t es[5] = {1, 1, 1, 1, 1};
    return fn(m, type, rank, const_cast<void*>(base), dims, strides, box, es,
              CU_TENSOR_MAP_INTERLEAVE_NONE, CU_TENSOR_MAP_SWIZZLE_128B, CU_TENSOR_MAP_L2_PROMOTION_L2_256B,
              CU_TENSOR_MAP_FLOAT_OOB_FILL_NONE) == CUDA_SUCCESS;
}

}

extern "C" void kernel_launch(void* const* d_in, const int* in_sizes, int n_in, void* d_out, int out_size) {
    (void)in_sizes; (void)n_in; (void)out_size;
    typedef const __nv_bfloat16* bp;
    bp x = (bp)d_in[0], lam_re = (bp)d_in[1], lam_im = (bp)d_in[2], B_re = (bp)d_in[3], B_im = (bp)d_in[4];
    bp C_re = (bp)d_in[5], C_im = (bp)d_in[6], log_dt = (bp)d_in[7], dskip = (bp)d_in[8];
    bp w1 = (bp)d_in[10], b1 = (bp)d_in[11], w2 = (bp)d_in[12], b2 = (bp)d_in[13], gate_w = (bp)d_in[14];

    static EncodeFn fn = nullptr;
    static Scratch* ps = nullptr;
    if (!fn) {
        void* f = nullptr;
        cudaDriverEntryPointQueryResult qr;
        cudaGetDriverEntryPoint("cuTensorMapEncodeTiled", &f, cudaEnableDefault, &qr);
        fn = (EncodeFn)f;
        cudaGetSymbolAddress((void**)&ps, g_s);
        cudaFuncSetAttribute(fused_kernel, cudaFuncAttributeMaxDynamicSharedMemorySize, kSmemBytes);
    }
    cudaStream_t stream = cudaStreamPerThread;

    Params p;
    p.x = x; p.lam_re = lam_re; p.lam_im = lam_im; p.log_dt = log_dt; p.dskip = dskip; p.b1 = b1; p.b2 = b2;
    p.gate_w = gate_w; p.b_re = B_re; p.b_im = B_im; p.s = ps;
    char* const pHs = (char*)ps + offsetof(Scratch, Hs);
    char* const pHf = (char*)ps + offsetof(Scratch, Hf);
    char* const pBc = (char*)ps + offsetof(Scratch, Bcopy);

    const char* lo = (const char*)B_re; const char* hi = (const char*)B_im;
    p.swap = 0;
    if (hi < lo) { const char* t = lo; lo = hi; hi = t; p.swap = 1; }
    unsigned long long diff = (unsigned long long)(hi - lo);
    if (diff >= (1ull << 40) || (diff & 15) || diff == 0) {
        cudaMemcpyAsync(pBc, B_re, 2u << 20, cudaMemcpyDeviceToDevice, stream);
        cudaMemcpyAsync((char*)pBc + (2u << 20), B_im, 2u << 20, cudaMemcpyDeviceToDevice, stream);
        lo = (const char*)pBc; diff = 2u << 20; p.swap = 0;
    }

    CUtensorMap mB, mXs, mXf, mW1a, mW1b, mHs, mHf, mCre, mCim, mW2, mW2n, mW2p, mHf3, mOut;
    bool ok = true;
    { cuuint64_t d[4] = {1024, 8, 2, 128}, s[3] = {2048, diff, 16384}; cuuint32_t b[4] = {64, 8, 2, 8};
      ok &= encode(fn, &mB, lo, 4, d, s, b); }
    { cuuint64_t d[5] = {1024, 2, 4, 32, 8}, s[4] = {2048, 64 * 2048, 2 * 2048, 256 * 2048}; cuuint32_t b[5] = {64, 2, 4, 16, 1};
      ok &= encode(fn, &mXs, x, 5, d, s, b); }
    { cuuint64_t d[5] = {1024, 8, 4, 8, 8}, s[4] = {2048, 64 * 2048, 8 * 2048, 256 * 2048}; cuuint32_t b[5] = {64, 8, 4, 4, 1};
      ok &= encode(fn, &mXf, x, 5, d, s, b); }
    { cuuint64_t d[3] = {64, 1024, 56}, s[2] = {7168, 128}; cuuint32_t ba[3] = {64, 32, 4}, bb[3] = {64, 32, 3};
      ok &= encode(fn, &mW1a, w1, 3, d, s, ba); ok &= encode(fn, &mW1b, w1, 3, d, s, bb); }
    { cuuint64_t d[3] = {64, 2048, 32}, s[2] = {4096, 128}; cuuint32_t b[3] = {64, 64, 2};
      ok &= encode(fn, &mHs, pHs, 3, d, s, b); }
    { cuuint64_t d[2] = {3584, 2048}, s[1] = {7168}; cuuint32_t b[2] = {64, 128};
      ok &= encode(fn, &mHf, pHf, 2, d, s, b); }
    { cuuint64_t d[2] = {1024, 1024}, s[1] = {2048}; cuuint32_t b[2] = {64, 128};
      ok &= encode(fn, &mCre, C_re, 2, d, s, b); ok &= encode(fn, &mCim, C_im, 2, d, s, b); }
    { cuuint64_t d[5] = {64, 2, 448, 4, 16}, s[4] = {2048, 8 * 2048, 2 * 2048, 128}; cuuint32_t b[5] = {64, 2, 4, 4, 2};
      ok &= encode(fn, &mW2, w2, 5, d, s, b); }
    { cuuint64_t d[2] = {1024, 3584}, s[1] = {2048}; cuuint32_t b[2] = {64, 128};
      ok &= encode(fn, &mW2n, w2, 2, d, s, b); }
    { cuuint64_t d[5] = {1024, 2, 4, 4, 112}, s[4] = {2048, 8 * 2048, 2 * 2048, 32 * 2048}; cuuint32_t b[5] = {64, 2, 4, 4, 4};
      ok &= encode(fn, &mW2p, w2, 5, d, s, b); }
    { cuuint64_t d[3] = {64, 2048, 56}, s[2] = {7168, 128}; cuuint32_t b[3] = {64, 64, 2};
      ok &= encode(fn, &mHf3, pHf, 3, d, s, b); }
    { cuuint64_t d[4] = {32, 2, 1984, 32}, s[3] = {64 * 4096, 4096, 128}; cuuint32_t b[4] = {32, 2, 8, 1};
      ok &= encode(fn, &mOut, d_out, 4, d, s, b, CU_TENSOR_MAP_DATA_TYPE_FLOAT32); }
    if (!ok) return;

    fused_kernel<<<128, 384, kSmemBytes, stream>>>(mB, mXs, mXf, mW1b, mW1a, mHs, mHf, mCre, mCim, mW2, mW2n, mW2p, mHf3, mOut, p);
}
```

```cpp
#include <cuda_runtime.h>
#include <cuda_bf16.h>
#include <cuda_fp16.h>
#include <cuda.h>
#include <stdint.h>
#include <stddef.h>

#define XLDKB 40
#define PF0LINES 1
#define PFKB 80
#define SKEW 2
#define BACKOFF 100
#define RXPOS 1
#define MC0 0
#define PFTOP 0
#define INITW 0
#define PRODCOND warp >= 8
#define ORDER 0

namespace {

constexpr int kD = 1024, kF = 3584;
constexpr int kStages = 4;
constexpr int kStageBytes = 49152;
constexpr int kABytes = 16384;
constexpr int kXOff = kStages * kStageBytes;
constexpr int kTabOff = kXOff + 2048;
constexpr int kGateOff = kXOff + 32768;
constexpr int kBiasOff = kGateOff + 4 * 72 * 2;
constexpr int kBarOff = kBiasOff + 56 * 16;
constexpr int kSmemBytes = 232448;
static_assert(kBarOff + 160 <= kSmemBytes, "smem");
constexpr int kXBytes = 33792;
constexpr uint32_t kSmemOrg = 1024;
constexpr unsigned kSpinLimit = 1u << 18;
constexpr int kTotal = 92;

__host__ __device__ constexpr int pass2_kb(int s) {
    return s < 2 ? 6 : s < 8 ? 7 : s < 12 ? 8 : s < 18 ? 9 : s < 22 ? 10 : s < 28 ? 11 : s < 32 ? 12 : s < 38 ? 13 : s < 42 ? 14 : s < 48 ? 15 : s < 56 ? 16 : 17;
}

struct Scratch {
    unsigned claim[64];
    unsigned epoch, pad0[31];
    unsigned done, pad1[31];
    unsigned cnt[40 * 32];
    uint2 gate[2048];
    uint4 agg[8 * 1024];
    __align__(1024) uint8_t X[128 * kXBytes];
    __align__(1024) __nv_bfloat16 Hs[2048 * 2048];
    __align__(1024) __nv_bfloat16 Hf[2048 * 3584];
    __align__(1024) __nv_bfloat16 Bcopy[2 * 1024 * 1024];
};
__device__ Scratch g_s;

#define TRAP() break
#define PIN_F(x) asm volatile("" : "+f"(x))
#define PIN_R(x) asm volatile("" : "+r"(x))
#define UNDEF_F(x) asm volatile("" : "=f"(x))
#define UNDEF_R(x) asm volatile("" : "=r"(x))
#define RESPIN()
__device__ __forceinline__ uint32_t smem_u32(const void* p) { return (uint32_t)__cvta_generic_to_shared(p); }
__device__ __forceinline__ void mbar_init(uint32_t bar, uint32_t count) {
    asm volatile("mbarrier.init.shared::cta.b64 [%0], %1;" ::"r"(bar), "r"(count) : "memory");
}
__device__ __forceinline__ void mbar_expect_tx(uint32_t bar, uint32_t bytes) {
    asm volatile("mbarrier.arrive.expect_tx.shared::cta.b64 _, [%0], %1;" ::"r"(bar), "r"(bytes) : "memory");
}
__device__ __forceinline__ void mbar_wait(uint32_t bar, uint32_t parity) {
    asm volatile(
        "{\n.reg .pred p;\n.reg .u32 n;\n"
        "mbarrier.try_wait.parity.shared::cta.b64 p, [%0], %1;\n"
        "@p bra DONE;\n"
        "mov.u32 n, 0;\n"
        "LOOP:\n"
        "mbarrier.try_wait.parity.shared::cta.b64 p, [%0], %1;\n"
        "@p bra DONE;\n"
        "add.u32 n, n, 1;\n"
        "setp.lt.u32 p, n, %2;\n"
        "@p bra LOOP;\n"
        "DONE:\n}\n"
        ::"r"(bar), "r"(parity), "n"(kSpinLimit) : "memory");
}
__device__ __forceinline__ void sched_fence(uint32_t nonzero) {
    asm volatile("{\n.reg .pred p;\n.reg .u32 n;\nsetp.ne.u32 p, %0, 0;\n@p bra DONE;\nLOOP:\nmov.u32 n, %%clock;\n"
                 "setp.eq.u32 p, n, 0;\n@p bra LOOP;\nDONE:\n}\n" ::"r"(nonzero) : "memory");
}
__device__ __forceinline__ void mbar_arrive_local(uint32_t bar) {
    asm volatile("mbarrier.arrive.shared::cta.b64 _, [%0];" ::"r"(bar) : "memory");
}
__device__ __forceinline__ void mbar_arrive_cluster(uint32_t cluster_addr) {
    asm volatile("mbarrier.arrive.shared::cluster.b64 _, [%0];" ::"r"(cluster_addr) : "memory");
}
__device__ __forceinline__ uint32_t mapa(uint32_t addr, uint32_t rank) {
    uint32_t r;
    asm("mapa.shared::cluster.u32 %0, %1, %2;" : "=r"(r) : "r"(addr), "r"(rank));
    return r;
}
__device__ __forceinline__ void cluster_arrive() { asm volatile("barrier.cluster.arrive.relaxed.aligned;" ::: "memory"); }
__device__ __forceinline__ void cluster_wait() { asm volatile("barrier.cluster.wait.acquire.aligned;" ::: "memory"); }
__device__ __forceinline__ void bar_sync(int id, int n) { asm volatile("bar.sync %0, %1;" ::"r"(id), "r"(n) : "memory"); }
__device__ __forceinline__ void bar_arrive(int id, int n) { asm volatile("bar.arrive %0, %1;" ::"r"(id), "r"(n) : "memory"); }
__device__ __forceinline__ bool elect_one() {
    uint32_t p;
    asm volatile("{\n.reg .pred P;\nelect.sync _|P, 0xffffffff;\nselp.u32 %0, 1, 0, P;\n}\n" : "=r"(p));
    return p != 0;
}

__device__ __forceinline__ void tma2(uint32_t dst, const CUtensorMap* m, uint32_t bar, int c0, int c1) {
    asm volatile("cp.async.bulk.tensor.2d.shared::cluster.global.mbarrier::complete_tx::bytes [%0], [%1, {%3, %4}], [%2];"
                 ::"r"(dst), "l"(m), "r"(bar), "r"(c0), "r"(c1) : "memory");
}
__device__ __forceinline__ void tma3(uint32_t dst, const CUtensorMap* m, uint32_t bar, int c0, int c1, int c2) {
    asm volatile("cp.async.bulk.tensor.3d.shared::cluster.global.mbarrier::complete_tx::bytes [%0], [%1, {%3, %4, %5}], [%2];"
                 ::"r"(dst), "l"(m), "r"(bar), "r"(c0), "r"(c1), "r"(c2) : "memory");
}
__device__ __forceinline__ void tma4(uint32_t dst, const CUtensorMap* m, uint32_t bar, int c0, int c1, int c2, int c3) {
    asm volatile("cp.async.bulk.tensor.4d.shared::cluster.global.mbarrier::complete_tx::bytes [%0], [%1, {%3, %4, %5, %6}], [%2];"
                 ::"r"(dst), "l"(m), "r"(bar), "r"(c0), "r"(c1), "r"(c2), "r"(c3) : "memory");
}
__device__ __forceinline__ void tma5(uint32_t dst, const CUtensorMap* m, uint32_t bar, int c0, int c1, int c2, int c3, int c4) {
    asm volatile("cp.async.bulk.tensor.5d.shared::cluster.global.mbarrier::complete_tx::bytes [%0], [%1, {%3, %4, %5, %6, %7}], [%2];"
                 ::"r"(dst), "l"(m), "r"(bar), "r"(c0), "r"(c1), "r"(c2), "r"(c3), "r"(c4) : "memory");
}
__device__ __forceinline__ void tma2_mc(uint32_t dst, const CUtensorMap* m, uint32_t bar, int c0, int c1) {
    asm volatile("cp.async.bulk.tensor.2d.shared::cluster.global.mbarrier::complete_tx::bytes.multicast::cluster [%0], [%1, {%3, %4}], [%2], %5;"
                 ::"r"(dst), "l"(m), "r"(bar), "r"(c0), "r"(c1), "h"((uint16_t)3) : "memory");
}
__device__ __forceinline__ void tma3_mc(uint32_t dst, const CUtensorMap* m, uint32_t bar, int c0, int c1, int c2) {
    asm volatile("cp.async.bulk.tensor.3d.shared::cluster.global.mbarrier::complete_tx::bytes.multicast::cluster [%0], [%1, {%3, %4, %5}], [%2], %6;"
                 ::"r"(dst), "l"(m), "r"(bar), "r"(c0), "r"(c1), "r"(c2), "h"((uint16_t)3) : "memory");
}
__device__ __forceinline__ void tma5_mc(uint32_t dst, const CUtensorMap* m, uint32_t bar, int c0, int c1, int c2, int c3, int c4) {
    asm volatile("cp.async.bulk.tensor.5d.shared::cluster.global.mbarrier::complete_tx::bytes.multicast::cluster [%0], [%1, {%3, %4, %5, %6, %7}], [%2], %8;"
                 ::"r"(dst), "l"(m), "r"(bar), "r"(c0), "r"(c1), "r"(c2), "r"(c3), "r"(c4), "h"((uint16_t)3) : "memory");
}
__device__ __forceinline__ void tma3_pf(const CUtensorMap* m, int c0, int c1, int c2) {
    asm volatile("cp.async.bulk.prefetch.tensor.3d.L2.global [%0, {%1, %2, %3}];" ::"l"(m), "r"(c0), "r"(c1), "r"(c2) : "memory");
}
__device__ __forceinline__ void tma2_pf(const CUtensorMap* m, int c0, int c1) {
    asm volatile("cp.async.bulk.prefetch.tensor.2d.L2.global [%0, {%1, %2}];" ::"l"(m), "r"(c0), "r"(c1) : "memory");
}
__device__ __forceinline__ void bulk_store(void* dst, uint32_t src, uint32_t bytes) {
    asm volatile("cp.async.bulk.global.shared::cta.bulk_group [%0], [%1], %2;" ::"l"(dst), "r"(src), "r"(bytes) : "memory");
}
__device__ __forceinline__ void tma4_store(const CUtensorMap* m, uint32_t src, int c2, int c3) {
    asm volatile("cp.async.bulk.tensor.4d.global.shared::cta.bulk_group [%0, {%2, %2, %3, %4}], [%1];"
                 ::"l"(m), "r"(src), "r"(0), "r"(c2), "r"(c3) : "memory");
}
__device__ __forceinline__ void bulk_commit() { asm volatile("cp.async.bulk.commit_group;" ::: "memory"); }
__device__ __forceinline__ void bulk_wait_read() { asm volatile("cp.async.bulk.wait_group.read 0;" ::: "memory"); }
__device__ __forceinline__ void fence_async_smem() { asm volatile("fence.proxy.async.shared::cta;" ::: "memory"); }
__device__ __forceinline__ void bulk_load(uint32_t dst, const void* src, uint32_t bytes, uint32_t bar) {
    asm volatile("cp.async.bulk.shared::cluster.global.mbarrier::complete_tx::bytes [%0], [%1], %2, [%3];"
                 ::"r"(dst), "l"(src), "r"(bytes), "r"(bar) : "memory");
}
__device__ __forceinline__ unsigned atom_exch(unsigned* p, unsigned v) {
    unsigned r;
    asm volatile("atom.relaxed.gpu.global.exch.b32 %0, [%1], %2;" : "=r"(r) : "l"(p), "r"(v) : "memory");
    return r;
}
__device__ __forceinline__ void st_async32(uint32_t a, uint32_t v, uint32_t bar) {
    asm volatile("st.async.shared::cluster.mbarrier::complete_tx::bytes.u32 [%0], %1, [%2];" ::"r"(a), "r"(v), "r"(bar) : "memory");
}
__device__ __forceinline__ void sts128f(uint32_t a, float x, float y, float z, float w) {
    asm volatile("st.shared.v4.f32 [%0], {%1, %2, %3, %4};" ::"r"(a), "f"(x), "f"(y), "f"(z), "f"(w) : "memory");
}
__device__ __forceinline__ void prefetch_map(const CUtensorMap* m) {
    asm volatile("prefetch.tensormap [%0];" ::"l"(m) : "memory");
}

__device__ __forceinline__ void prefetch_l2(const void* p, uint32_t bytes) {
    asm volatile("cp.async.bulk.prefetch.L2.global [%0], %1;" ::"l"(p), "r"(bytes) : "memory");
}

__device__ __forceinline__ void wgmma_fence() { asm volatile("wgmma.fence.sync.aligned;" ::: "memory"); }
__device__ __forceinline__ void wgmma_commit() { asm volatile("wgmma.commit_group.sync.aligned;" ::: "memory"); }
template <int N>
__device__ __forceinline__ void wgmma_wait() { asm volatile("wgmma.wait_group.sync.aligned %0;" ::"n"(N) : "memory"); }

__device__ __forceinline__ uint32_t pack_bf16(float lo, float hi) {
    uint32_t r;
    asm("cvt.rn.bf16x2.f32 %0, %1, %2;" : "=r"(r) : "f"(hi), "f"(lo));
    return r;
}
__device__ __forceinline__ uint32_t pack_f16(float lo, float hi) {
    uint32_t r;
    asm("cvt.rn.f16x2.f32 %0, %1, %2;" : "=r"(r) : "f"(hi), "f"(lo));
    return r;
}
__device__ __forceinline__ uint32_t pack_bf16_v(float lo, float hi) {
    uint32_t r;
    asm volatile("cvt.rn.bf16x2.f32 %0, %1, %2;" : "=r"(r) : "f"(hi), "f"(lo));
    return r;
}
template <int LUT>
__device__ __forceinline__ uint32_t lop3(uint32_t a, uint32_t b, uint32_t c) {
    uint32_t r;
    asm("lop3.b32 %0, %1, %2, %3, %4;" : "=r"(r) : "r"(a), "r"(b), "r"(c), "n"(LUT));
    return r;
}
__device__ __forceinline__ float bf_lo(uint32_t v) { return __uint_as_float(v << 16); }
__device__ __forceinline__ float bf_hi(uint32_t v) { return __uint_as_float(v & 0xffff0000u); }
__device__ __forceinline__ float bf16_round(float v) { return __bfloat162float(__float2bfloat16_rn(v)); }
__device__ __forceinline__ uint32_t bf2_mul(uint32_t a, uint32_t b) {
    uint32_t r;
    asm("mul.rn.bf16x2 %0, %1, %2;" : "=r"(r) : "r"(a), "r"(b));
    return r;
}
__device__ __forceinline__ uint32_t bf2_add_relu(uint32_t a, uint32_t b) {
    uint32_t r;
    asm("fma.rn.relu.bf16x2 %0, %1, %2, %3;" : "=r"(r) : "r"(a), "r"(0x3f803f80u), "r"(b));
    return r;
}
__device__ __forceinline__ uint4 ldg128(const void* p) {
    uint4 v;
    asm volatile("ld.global.nc.v4.u32 {%0, %1, %2, %3}, [%4];" : "=r"(v.x), "=r"(v.y), "=r"(v.z), "=r"(v.w) : "l"(p));
    return v;
}
__device__ __forceinline__ uint32_t ldg32(const void* p) {
    uint32_t v;
    asm volatile("ld.global.nc.u32 %0, [%1];" : "=r"(v) : "l"(p));
    return v;
}
__device__ __forceinline__ uint32_t ldg32na(const void* p) {
    uint32_t v;
    asm volatile("ld.global.nc.L1::no_allocate.u32 %0, [%1];" : "=r"(v) : "l"(p));
    return v;
}
__device__ __forceinline__ uint32_t ldg16(const __nv_bfloat16* p) {
    uint32_t v;
    asm volatile("ld.global.nc.u16 %0, [%1];" : "=r"(v) : "l"(p));
    return v;
}
__device__ __forceinline__ uint4 ld_relaxed128(const void* p) {
    uint4 v;
    asm volatile("ld.relaxed.gpu.global.v4.u32 {%0, %1, %2, %3}, [%4];" : "=r"(v.x), "=r"(v.y), "=r"(v.z), "=r"(v.w) : "l"(p) : "memory");
    return v;
}
__device__ __forceinline__ uint2 ld_relaxed64(const void* p) {
    unsigned long long v;
    asm volatile("ld.relaxed.gpu.global.u64 %0, [%1];" : "=l"(v) : "l"(p) : "memory");
    return make_uint2((uint32_t)v, (uint32_t)(v >> 32));
}
__device__ __forceinline__ void st_relaxed64(void* p, uint32_t lo, uint32_t hi) {
    unsigned long long v = ((unsigned long long)hi << 32) | lo;
    asm volatile("st.relaxed.gpu.global.u64 [%0], %1;" ::"l"(p), "l"(v) : "memory");
}
__device__ __forceinline__ void st_relaxed2x64(void* p, uint32_t a, uint32_t b, uint32_t c, uint32_t d) {
    unsigned long long v0 = ((unsigned long long)b << 32) | a, v1 = ((unsigned long long)d << 32) | c;
    asm volatile("st.relaxed.gpu.global.v2.u64 [%0], {%1, %2};" ::"l"(p), "l"(v0), "l"(v1) : "memory");
}
__device__ __forceinline__ uint4 ld_relaxed2x64(const void* p) {
    unsigned long long v0, v1;
    asm volatile("ld.relaxed.gpu.global.v2.u64 {%0, %1}, [%2];" : "=l"(v0), "=l"(v1) : "l"(p) : "memory");
    return make_uint4((uint32_t)v0, (uint32_t)(v0 >> 32), (uint32_t)v1, (uint32_t)(v1 >> 32));
}
__device__ __forceinline__ void stg128(void* p, uint32_t a, uint32_t b, uint32_t c, uint32_t d) {
    asm volatile("st.global.v4.u32 [%0], {%1, %2, %3, %4};" ::"l"(p), "r"(a), "r"(b), "r"(c), "r"(d) : "memory");
}
__device__ __forceinline__ void stg64f(void* p, float a, float b) {
    asm volatile("st.global.v2.f32 [%0], {%1, %2};" ::"l"(p), "f"(a), "f"(b) : "memory");
}
__device__ __forceinline__ uint4 lds128(uint32_t a) {
    uint4 v;
    asm volatile("ld.shared.v4.u32 {%0, %1, %2, %3}, [%4];" : "=r"(v.x), "=r"(v.y), "=r"(v.z), "=r"(v.w) : "r"(a) : "memory");
    return v;
}
__device__ __forceinline__ uint2 lds64(uint32_t a) {
    uint2 v;
    asm volatile("ld.shared.v2.u32 {%0, %1}, [%2];" : "=r"(v.x), "=r"(v.y) : "r"(a) : "memory");
    return v;
}
__device__ __forceinline__ uint4 ldsm4(uint32_t a) {
    uint4 v;
    asm volatile("ldmatrix.sync.aligned.m8n8.x4.shared.b16 {%0, %1, %2, %3}, [%4];" : "=r"(v.x), "=r"(v.y), "=r"(v.z), "=r"(v.w) : "r"(a) : "memory");
    return v;
}
__device__ __forceinline__ uint32_t lds16(uint32_t a) {
    uint32_t v;
    asm volatile("ld.shared.u16 %0, [%1];" : "=r"(v) : "r"(a) : "memory");
    return v;
}
__device__ __forceinline__ void sts16(uint32_t a, uint32_t x) {
    asm volatile("st.shared.u16 [%0], %1;" ::"r"(a), "h"((uint16_t)x) : "memory");
}
__device__ __forceinline__ void st_relaxed32(void* p, uint32_t v) {
    asm volatile("st.relaxed.gpu.global.u32 [%0], %1;" ::"l"(p), "r"(v) : "memory");
}
__device__ __forceinline__ float lds32f(uint32_t a) {
    float v;
    asm volatile("ld.shared.f32 %0, [%1];" : "=f"(v) : "r"(a) : "memory");
    return v;
}
__device__ __forceinline__ void sts128(uint32_t a, uint32_t x, uint32_t y, uint32_t z, uint32_t w) {
    asm volatile("st.shared.v4.u32 [%0], {%1, %2, %3, %4};" ::"r"(a), "r"(x), "r"(y), "r"(z), "r"(w) : "memory");
}
__device__ __forceinline__ void sts64f(uint32_t a, float x, float y) {
    asm volatile("st.shared.v2.f32 [%0], {%1, %2};" ::"r"(a), "f"(x), "f"(y) : "memory");
}
__device__ __forceinline__ float4 lds128f(uint32_t a) {
    float4 v;
    asm volatile("ld.shared.v4.f32 {%0, %1, %2, %3}, [%4];" : "=f"(v.x), "=f"(v.y), "=f"(v.z), "=f"(v.w) : "r"(a) : "memory");
    return v;
}
__device__ __forceinline__ uint32_t lds32(uint32_t a) {
    uint32_t v;
    asm volatile("ld.shared.u32 %0, [%1];" : "=r"(v) : "r"(a) : "memory");
    return v;
}
__device__ __forceinline__ void sts32(uint32_t a, uint32_t x) {
    asm volatile("st.shared.u32 [%0], %1;" ::"r"(a), "r"(x) : "memory");
}
__device__ __forceinline__ void stg128f(void* p, float a, float b, float c, float d) {
    asm volatile("st.global.v4.f32 [%0], {%1, %2, %3, %4};" ::"l"(p), "f"(a), "f"(b), "f"(c), "f"(d) : "memory");
}
__device__ __forceinline__ unsigned ld_relaxed32(const unsigned* p) {
    unsigned v;
    asm volatile("ld.relaxed.gpu.global.u32 %0, [%1];" : "=r"(v) : "l"(p) : "memory");
    return v;
}
__device__ __forceinline__ void wait_counter(const unsigned* p, unsigned target) {
    unsigned n = 0, v;
    while (true) {
        asm volatile("ld.acquire.gpu.global.u32 %0, [%1];" : "=r"(v) : "l"(p) : "memory");
        if ((int)(v - target) >= 0) break;
        if (++n > kSpinLimit) TRAP();
        __nanosleep(32);
    }
}
#define KT(IT, W) do { } while (0)
#define STAMP(cond, slot) do { } while (0)
#define STAMPA(cond, slot) STAMP(cond, slot)
#define STAMPB(cond, slot) do { } while (0)

#define STAMPC(cond, slot) do { } while (0)
#define STAMPD(cond, slot) do { } while (0)
template <int TA, int TB>
__device__ __forceinline__ void wgmma_n256(float (&d)[128], uint64_t da, uint64_t db, int keep) {
    asm volatile(
        "{\n.reg .pred p;\nsetp.ne.b32 p, %132, 0;\n"
        "wgmma.mma_async.sync.aligned.m64n256k16.f32.bf16.bf16 "
        "{%0, %1, %2, %3, %4, %5, %6, %7, %8, %9, %10, %11, %12, %13, %14, %15, "
        "%16, %17, %18, %19, %20, %21, %22, %23, %24, %25, %26, %27, %28, %29, %30, %31, "
        "%32, %33, %34, %35, %36, %37, %38, %39, %40, %41, %42, %43, %44, %45, %46, %47, "
        "%48, %49, %50, %51, %52, %53, %54, %55, %56, %57, %58, %59, %60, %61, %62, %63, "
        "%64, %65, %66, %67, %68, %69, %70, %71, %72, %73, %74, %75, %76, %77, %78, %79, "
        "%80, %81, %82, %83, %84, %85, %86, %87, %88, %89, %90, %91, %92, %93, %94, %95, "
        "%96, %97, %98, %99, %100, %101, %102, %103, %104, %105, %106, %107, %108, %109, %110, %111, "
        "%112, %113, %114, %115, %116, %117, %118, %119, %120, %121, %122, %123, %124, %125, %126, %127}, "
        "%128, %129, p, 1, 1, %130, %131;\n}\n"
        : "+f"(d[0]), "+f"(d[1]), "+f"(d[2]), "+f"(d[3]), "+f"(d[4]), "+f"(d[5]), "+f"(d[6]), "+f"(d[7]),
          "+f"(d[8]), "+f"(d[9]), "+f"(d[10]), "+f"(d[11]), "+f"(d[12]), "+f"(d[13]), "+f"(d[14]), "+f"(d[15]),
          "+f"(d[16]), "+f"(d[17]), "+f"(d[18]), "+f"(d[19]), "+f"(d[20]), "+f"(d[21]), "+f"(d[22]), "+f"(d[23]),
          "+f"(d[24]), "+f"(d[25]), "+f"(d[26]), "+f"(d[27]), "+f"(d[28]), "+f"(d[29]), "+f"(d[30]), "+f"(d[31]),
          "+f"(d[32]), "+f"(d[33]), "+f"(d[34]), "+f"(d[35]), "+f"(d[36]), "+f"(d[37]), "+f"(d[38]), "+f"(d[39]),
          "+f"(d[40]), "+f"(d[41]), "+f"(d[42]), "+f"(d[43]), "+f"(d[44]), "+f"(d[45]), "+f"(d[46]), "+f"(d[47]),
          "+f"(d[48]), "+f"(d[49]), "+f"(d[50]), "+f"(d[51]), "+f"(d[52]), "+f"(d[53]), "+f"(d[54]), "+f"(d[55]),
          "+f"(d[56]), "+f"(d[57]), "+f"(d[58]), "+f"(d[59]), "+f"(d[60]), "+f"(d[61]), "+f"(d[62]), "+f"(d[63]),
          "+f"(d[64]), "+f"(d[65]), "+f"(d[66]), "+f"(d[67]), "+f"(d[68]), "+f"(d[69]), "+f"(d[70]), "+f"(d[71]),
          "+f"(d[72]), "+f"(d[73]), "+f"(d[74]), "+f"(d[75]), "+f"(d[76]), "+f"(d[77]), "+f"(d[78]), "+f"(d[79]),
          "+f"(d[80]), "+f"(d[81]), "+f"(d[82]), "+f"(d[83]), "+f"(d[84]), "+f"(d[85]), "+f"(d[86]), "+f"(d[87]),
          "+f"(d[88]), "+f"(d[89]), "+f"(d[90]), "+f"(d[91]), "+f"(d[92]), "+f"(d[93]), "+f"(d[94]), "+f"(d[95]),
          "+f"(d[96]), "+f"(d[97]), "+f"(d[98]), "+f"(d[99]), "+f"(d[100]), "+f"(d[101]), "+f"(d[102]), "+f"(d[103]),
          "+f"(d[104]), "+f"(d[105]), "+f"(d[106]), "+f"(d[107]), "+f"(d[108]), "+f"(d[109]), "+f"(d[110]), "+f"(d[111]),
          "+f"(d[112]), "+f"(d[113]), "+f"(d[114]), "+f"(d[115]), "+f"(d[116]), "+f"(d[117]), "+f"(d[118]), "+f"(d[119]),
          "+f"(d[120]), "+f"(d[121]), "+f"(d[122]), "+f"(d[123]), "+f"(d[124]), "+f"(d[125]), "+f"(d[126]), "+f"(d[127])
        : "l"(da), "l"(db), "n"(TA), "n"(TB), "r"(keep));
}
template <int TA, int TB>
__device__ __forceinline__ void wgmma_n192(float (&d)[128], uint64_t da, uint64_t db, int keep) {
    asm volatile(
        "{\n.reg .pred p;\nsetp.ne.b32 p, %100, 0;\n"
        "wgmma.mma_async.sync.aligned.m64n192k16.f32.bf16.bf16 "
        "{%0, %1, %2, %3, %4, %5, %6, %7, %8, %9, %10, %11, %12, %13, %14, %15, "
        "%16, %17, %18, %19, %20, %21, %22, %23, %24, %25, %26, %27, %28, %29, %30, %31, "
        "%32, %33, %34, %35, %36, %37, %38, %39, %40, %41, %42, %43, %44, %45, %46, %47, "
        "%48, %49, %50, %51, %52, %53, %54, %55, %56, %57, %58, %59, %60, %61, %62, %63, "
        "%64, %65, %66, %67, %68, %69, %70, %71, %72, %73, %74, %75, %76, %77, %78, %79, "
        "%80, %81, %82, %83, %84, %85, %86, %87, %88, %89, %90, %91, %92, %93, %94, %95}, "
        "%96, %97, p, 1, 1, %98, %99;\n}\n"
        : "+f"(d[0]), "+f"(d[1]), "+f"(d[2]), "+f"(d[3]), "+f"(d[4]), "+f"(d[5]), "+f"(d[6]), "+f"(d[7]),
          "+f"(d[8]), "+f"(d[9]), "+f"(d[10]), "+f"(d[11]), "+f"(d[12]), "+f"(d[13]), "+f"(d[14]), "+f"(d[15]),
          "+f"(d[16]), "+f"(d[17]), "+f"(d[18]), "+f"(d[19]), "+f"(d[20]), "+f"(d[21]), "+f"(d[22]), "+f"(d[23]),
          "+f"(d[24]), "+f"(d[25]), "+f"(d[26]), "+f"(d[27]), "+f"(d[28]), "+f"(d[29]), "+f"(d[30]), "+f"(d[31]),
          "+f"(d[32]), "+f"(d[33]), "+f"(d[34]), "+f"(d[35]), "+f"(d[36]), "+f"(d[37]), "+f"(d[38]), "+f"(d[39]),
          "+f"(d[40]), "+f"(d[41]), "+f"(d[42]), "+f"(d[43]), "+f"(d[44]), "+f"(d[45]), "+f"(d[46]), "+f"(d[47]),
          "+f"(d[48]), "+f"(d[49]), "+f"(d[50]), "+f"(d[51]), "+f"(d[52]), "+f"(d[53]), "+f"(d[54]), "+f"(d[55]),
          "+f"(d[56]), "+f"(d[57]), "+f"(d[58]), "+f"(d[59]), "+f"(d[60]), "+f"(d[61]), "+f"(d[62]), "+f"(d[63]),
          "+f"(d[64]), "+f"(d[65]), "+f"(d[66]), "+f"(d[67]), "+f"(d[68]), "+f"(d[69]), "+f"(d[70]), "+f"(d[71]),
          "+f"(d[72]), "+f"(d[73]), "+f"(d[74]), "+f"(d[75]), "+f"(d[76]), "+f"(d[77]), "+f"(d[78]), "+f"(d[79]),
          "+f"(d[80]), "+f"(d[81]), "+f"(d[82]), "+f"(d[83]), "+f"(d[84]), "+f"(d[85]), "+f"(d[86]), "+f"(d[87]),
          "+f"(d[88]), "+f"(d[89]), "+f"(d[90]), "+f"(d[91]), "+f"(d[92]), "+f"(d[93]), "+f"(d[94]), "+f"(d[95])
        : "l"(da), "l"(db), "n"(TA), "n"(TB), "r"(keep));
}
template <int TA, int TB>
__device__ __forceinline__ void wgmma_n128(float (&d)[128], uint64_t da, uint64_t db, int keep) {
    asm volatile(
        "{\n.reg .pred p;\nsetp.ne.b32 p, %68, 0;\n"
        "wgmma.mma_async.sync.aligned.m64n128k16.f32.bf16.bf16 "
        "{%0, %1, %2, %3, %4, %5, %6, %7, %8, %9, %10, %11, %12, %13, %14, %15, "
        "%16, %17, %18, %19, %20, %21, %22, %23, %24, %25, %26, %27, %28, %29, %30, %31, "
        "%32, %33, %34, %35, %36, %37, %38, %39, %40, %41, %42, %43, %44, %45, %46, %47, "
        "%48, %49, %50, %51, %52, %53, %54, %55, %56, %57, %58, %59, %60, %61, %62, %63}, "
        "%64, %65, p, 1, 1, %66, %67;\n}\n"
        : "+f"(d[0]), "+f"(d[1]), "+f"(d[2]), "+f"(d[3]), "+f"(d[4]), "+f"(d[5]), "+f"(d[6]), "+f"(d[7]),
          "+f"(d[8]), "+f"(d[9]), "+f"(d[10]), "+f"(d[11]), "+f"(d[12]), "+f"(d[13]), "+f"(d[14]), "+f"(d[15]),
          "+f"(d[16]), "+f"(d[17]), "+f"(d[18]), "+f"(d[19]), "+f"(d[20]), "+f"(d[21]), "+f"(d[22]), "+f"(d[23]),
          "+f"(d[24]), "+f"(d[25]), "+f"(d[26]), "+f"(d[27]), "+f"(d[28]), "+f"(d[29]), "+f"(d[30]), "+f"(d[31]),
          "+f"(d[32]), "+f"(d[33]), "+f"(d[34]), "+f"(d[35]), "+f"(d[36]), "+f"(d[37]), "+f"(d[38]), "+f"(d[39]),
          "+f"(d[40]), "+f"(d[41]), "+f"(d[42]), "+f"(d[43]), "+f"(d[44]), "+f"(d[45]), "+f"(d[46]), "+f"(d[47]),
          "+f"(d[48]), "+f"(d[49]), "+f"(d[50]), "+f"(d[51]), "+f"(d[52]), "+f"(d[53]), "+f"(d[54]), "+f"(d[55]),
          "+f"(d[56]), "+f"(d[57]), "+f"(d[58]), "+f"(d[59]), "+f"(d[60]), "+f"(d[61]), "+f"(d[62]), "+f"(d[63])
        : "l"(da), "l"(db), "n"(TA), "n"(TB), "r"(keep));
}
__device__ __forceinline__ void wgmma_n128_rs(float (&d)[128], uint32_t a0, uint32_t a1, uint32_t a2, uint32_t a3, uint64_t db) {
    asm volatile(
        "{\n.reg .pred p;\nsetp.ne.b32 p, 1, 0;\n"
        "wgmma.mma_async.sync.aligned.m64n128k16.f32.bf16.bf16 "
        "{%0, %1, %2, %3, %4, %5, %6, %7, %8, %9, %10, %11, %12, %13, %14, %15, "
        "%16, %17, %18, %19, %20, %21, %22, %23, %24, %25, %26, %27, %28, %29, %30, %31, "
        "%32, %33, %34, %35, %36, %37, %38, %39, %40, %41, %42, %43, %44, %45, %46, %47, "
        "%48, %49, %50, %51, %52, %53, %54, %55, %56, %57, %58, %59, %60, %61, %62, %63}, "
        "{%64, %65, %66, %67}, %68, p, 1, 1, 1;\n}\n"
        : "+f"(d[0]), "+f"(d[1]), "+f"(d[2]), "+f"(d[3]), "+f"(d[4]), "+f"(d[5]), "+f"(d[6]), "+f"(d[7]),
          "+f"(d[8]), "+f"(d[9]), "+f"(d[10]), "+f"(d[11]), "+f"(d[12]), "+f"(d[13]), "+f"(d[14]), "+f"(d[15]),
          "+f"(d[16]), "+f"(d[17]), "+f"(d[18]), "+f"(d[19]), "+f"(d[20]), "+f"(d[21]), "+f"(d[22]), "+f"(d[23]),
          "+f"(d[24]), "+f"(d[25]), "+f"(d[26]), "+f"(d[27]), "+f"(d[28]), "+f"(d[29]), "+f"(d[30]), "+f"(d[31]),
          "+f"(d[32]), "+f"(d[33]), "+f"(d[34]), "+f"(d[35]), "+f"(d[36]), "+f"(d[37]), "+f"(d[38]), "+f"(d[39]),
          "+f"(d[40]), "+f"(d[41]), "+f"(d[42]), "+f"(d[43]), "+f"(d[44]), "+f"(d[45]), "+f"(d[46]), "+f"(d[47]),
          "+f"(d[48]), "+f"(d[49]), "+f"(d[50]), "+f"(d[51]), "+f"(d[52]), "+f"(d[53]), "+f"(d[54]), "+f"(d[55]),
          "+f"(d[56]), "+f"(d[57]), "+f"(d[58]), "+f"(d[59]), "+f"(d[60]), "+f"(d[61]), "+f"(d[62]), "+f"(d[63])
        : "r"(a0), "r"(a1), "r"(a2), "r"(a3), "l"(db));
}

constexpr uint64_t kDescHi = (uint64_t)(64u | 0x40000000u) << 32;
template <int MODE>
__device__ __forceinline__ void mma_kblock(float (&acc)[128], uint32_t a_lo, uint32_t b_lo, int keep) {
    constexpr uint32_t HALF = (MODE == 1) ? 12288u : 16384u;
    constexpr bool BN = (MODE == 1 || MODE == 2 || MODE == 4);
#pragma unroll
    for (int kk = 0; kk < 4; ++kk) {
        const uint32_t ao = (MODE == 3) ? kk * 2048u : kk * 32u;
        const uint32_t bo = BN ? ((kk >> 1) * HALF + (kk & 1) * 2048u) : kk * 32u;
        const uint64_t da = kDescHi | (uint64_t)(a_lo + (ao >> 4) + (1u << 16));
        const uint64_t db = kDescHi | (uint64_t)(b_lo + (bo >> 4) + (BN ? (256u << 16) : (1u << 16)));
        if (MODE == 1) wgmma_n192<0, 1>(acc, da, db, kk == 0 ? keep : 1);
        else if (MODE == 4) wgmma_n128<0, 1>(acc, da, db, 1);
        else wgmma_n256<(MODE == 3), BN>(acc, da, db, kk == 0 ? keep : 1);
    }
}

struct Params {
    Scratch* s;
    const __nv_bfloat16* x;
    const __nv_bfloat16* b_re;
    const __nv_bfloat16* b_im;
    const __nv_bfloat16* gate_w;
    const __nv_bfloat16* lam_re;
    const __nv_bfloat16* lam_im;
    const __nv_bfloat16* log_dt;
    const __nv_bfloat16* dskip;
    const __nv_bfloat16* b1;
    const __nv_bfloat16* b2;
    float* out;
    int swap;
};

#define CMUL(rr, ri, ar, ai, br, bi) do { float _r = (ar) * (br) - (ai) * (bi); float _i = (ar) * (bi) + (ai) * (br); rr = _r; ri = _i; } while (0)
#define CFMA(rr, ri, ar, ai, br, bi) do { float _r = fmaf(-(ai), (bi), fmaf((ar), (br), rr)); float _i = fmaf((ai), (br), fmaf((ar), (bi), ri)); rr = _r; ri = _i; } while (0)

#define KB_OPEN(IT, LAST)                                                                        \
    KT(IT, 0);                                                                                   \
    if (ORDER && (LAST) && wg == 1) bar_sync(7, 256);                                            \
    mbar_wait(bar_full + 8 * ((IT) & 3), ((IT) >> 2) & 1);                                \
    KT(IT, 1);
#define KB_CLOSE(IT, LAST, REL)                                                                  \
    if (ORDER && (LAST) && wg == 0) bar_arrive(7, 256);                                          \
    wgmma_wait<1>();                                                                             \
    if (lane < 2 && (REL)) mbar_arrive_cluster(rel_addr + 8 * (((IT) - 1) & 3));
#define KBLOCK(MODE, IT, FIRST, LAST)                                                            \
    {                                                                                            \
        const uint32_t so = ((IT) & 3) * (kStageBytes >> 4);                                     \
        KB_OPEN(IT, LAST);                                                                       \
        wgmma_fence();                                                                           \
        mma_kblock<MODE>(acc, a_lo + so, b_lo + so, !(FIRST));                                   \
        wgmma_commit();                                                                          \
        KB_CLOSE(IT, LAST, !(FIRST));                                                            \
    }
#define TILE_END() do { wgmma_wait<0>(); if (lane < 2) mbar_arrive_cluster(rel_addr + 24); } while (0)

__global__ void __cluster_dims__(2, 1, 1) __launch_bounds__(384, 1)
fused_kernel(const __grid_constant__ CUtensorMap mB, const __grid_constant__ CUtensorMap mXs, const __grid_constant__ CUtensorMap mXf,
             const __grid_constant__ CUtensorMap mW1b, const __grid_constant__ CUtensorMap mW1a, const __grid_constant__ CUtensorMap mHs,
             const __grid_constant__ CUtensorMap mHf, const __grid_constant__ CUtensorMap mCre, const __grid_constant__ CUtensorMap mCim,
             const __grid_constant__ CUtensorMap mW2, const __grid_constant__ CUtensorMap mW2n, const Params p) {
    extern __shared__ __align__(1024) uint8_t smem_raw[];
    if (PFTOP) { prefetch_map(&mB); prefetch_map(&mXs); }
    const uint32_t sbase = smem_u32(smem_raw);
    if ((sbase & 0x3ffffu) != kSmemOrg) return;
    const uint32_t bar_full = sbase + kBarOff, bar_empty = bar_full + 32, bar_dep = bar_full + 64;
    const uint32_t bar_x = bar_full + 88, bar_c = bar_full + 96, role_s = bar_full + 104, bar_role = bar_full + 120, bar_e = bar_full + 128, tag_s = bar_full + 112 + (threadIdx.x & 1) * 4;

    const int tid = threadIdx.x, lane = tid & 31;
    const int warp = __shfl_sync(0xffffffffu, tid >> 5, 0);
    const uint32_t rank = blockIdx.x & 1;

    int pref;
    {
        unsigned smid;
        asm("mov.u32 %0, %%smid;" : "=r"(smid));
        const int t = smid >> 1, u = t - 32, d = (u * 37) >> 8;
        pref = (t < 32) ? (t & 7) * 8 + (t >> 3) : (t < 60) ? (1 + u - 7 * d) * 8 + 4 + d : ((t - 58) & 7);
    }
    STAMP(tid == 0, 0);
    int role = pref;
#define ROLE_VARS()                                                                                               \
    const int c = role >> 3;                                                             \
    const int j8 = role & 7;                                                        \
    const int cb = j8 * 2 + (int)rank;                                             \
    const int rb = 2 * c + (int)rank;                                               \
    const int kh = j8 >> 2;                 \
    const int colK = (j8 & 3) * 256 + kh * 128, colS = colK ^ 128;    \
    (void)cb; (void)rb; (void)colS;

#define INIT_ALL()                                                                                    \
    if (warp == INITW && elect_one()) {                                                               \
        if (!PFTOP) { prefetch_map(&mB); prefetch_map(&mXs); }                                        \
        _Pragma("unroll") for (int s = 0; s < kStages; ++s) {                                         \
            mbar_init(bar_full + 8 * s, 1);                                                           \
            mbar_init(bar_empty + 8 * s, 16);                                                         \
            mbar_init(bar_dep + 8 * s, 1);                                \
        }                                                                                             \
        mbar_init(bar_c, 96);                                                                         \
        mbar_init(bar_role, 1);                                                                       \
        mbar_init(bar_e, 32);                                                                         \
        asm volatile("fence.mbarrier_init.release.cluster;\nfence.proxy.async.shared::cta;" ::: "memory"); \
        mbar_expect_tx(bar_full, 49152);            \
        tma4(sbase, &mB, bar_full, 0, 0, 0, ((pref & 7) * 2 + (int)rank) * 8);                        \
        if (!MC0) {                                                                                   \
        tma5(sbase + kABytes, &mXs, bar_full, 0, 0, 0, 0, pref >> 3);                                 \
        tma5(sbase + kABytes + 16384, &mXs, bar_full, 0, 0, 0, 16, pref >> 3);                        \
        }                                                                                             \
        mbar_expect_tx(bar_x, 2048);                                                                  \
        bulk_load(sbase + kXOff, p.gate_w, 2048, bar_x);                                              \
        mbar_expect_tx(bar_role, 8);                                                                  \
    }
    if (PRODCOND) {
        asm volatile("setmaxnreg.dec.sync.aligned.u32 24;");
        unsigned taken = 0;
        if (tid == 352 && rank == 0) {
            taken = atom_exch(&p.s->claim[pref], 1u);
        }
        __syncwarp();
        cluster_arrive();
        cluster_wait();
        if (warp > 8) {
            if (tid == 352) {
#pragma unroll 1
                for (int i = 0; taken != 0 && i < 64; ++i) { role = i + 256; taken = atom_exch(&p.s->claim[i], 1u); }
                st_async32(mapa(role_s + 4 * rank, 0), role, mapa(bar_role, 0));
                st_async32(mapa(role_s + 4 * rank, 1), role, mapa(bar_role, 1));
            }
            __syncwarp();
            mbar_wait(bar_role, 0);
            role = __shfl_sync(0xffffffffu, (int)lds32(role_s), 0) & 63;
            ROLE_VARS();
            if (warp == 11) {
                if (lane < 9) prefetch_map(&mXf + lane);
#pragma unroll 1
                for (int en = lane; en < 56; en += 32) {
                    const int J = en >> 2;
                    const __nv_bfloat16* src = p.b1 + 32 * J + 2 * (en & 3) + ((J < 6) ? 2048 + 192 * j8 : 256 * j8 - 192);
                    sts128(sbase + kBiasOff + en * 16, ldg32(src), ldg32(src + 8), ldg32(src + 16), ldg32(src + 24));
                }
                mbar_arrive_local(bar_c);
                const uint4 dq = ldg128(p.dskip + colK + (lane & 15) * 8);
                uint4 bq = ldg128(p.b2 + colK + (lane & 15) * 8);
                mbar_wait(bar_x, 0);
                mbar_wait(bar_x, 1);
#pragma unroll 1
                for (int i = lane >> 4; i < 128; i += 2) {
                    const uint32_t xa_s = sbase + kXOff + (lane & 8) * 2048 + i * 128 + (((lane ^ i) & 7) << 4);
                    const uint4 xq = lds128(xa_s);
                    const float g = bf_lo(lds16(sbase + kGateOff + (((i >> 3) & 3) * 72 + 8 * (4 * rank + (i >> 5)) + (i & 7)) * 2));
                    const float om = bf16_round(1.0f - g);
                    PIN_R(bq.x); PIN_R(bq.y); PIN_R(bq.z); PIN_R(bq.w);
                    const uint32_t dv[4] = {dq.x, dq.y, dq.z, dq.w}, bv[4] = {bq.x, bq.y, bq.z, bq.w};
                    uint32_t xv[4] = {xq.x, xq.y, xq.z, xq.w};
#pragma unroll
                    for (int k = 0; k < 4; ++k) {
                        const uint32_t xd = bf2_mul(xv[k], dv[k]);
                        xv[k] = pack_bf16(fmaf(g, bf_lo(xd), om * bf_lo(bv[k])), fmaf(g, bf_hi(xd), om * bf_hi(bv[k])));
                    }
                    sts128(xa_s, xv[0], xv[1], xv[2], xv[3]);
                }
                mbar_arrive_local(bar_e);
                STAMPA(lane == 0, 10);
            } else {
                {
                    sts32(tag_s, ld_relaxed32(&p.s->epoch) + 1);
                    const int ch = cb * 64 + (tid - 288);
                    const uint32_t t_s = sbase + kTabOff + (tid - 288) * 64;
                    const float Lr = bf_lo(ldg16(p.lam_re + ch)), Li = bf_lo(ldg16(p.lam_im + ch));
                    const float dt = bf16_round(expf(bf_lo(ldg16(p.log_dt + ch))));
                    const float ea = expf(dt * Lr);
                    float lr, li;
                    sincospif((dt * Li) * 0.31830988618379067f, &li, &lr);
                    lr *= ea; li *= ea;
                    const float nr = lr - 1.0f, ni = li;
                    const bool big = fabsf(Lr) >= fabsf(Li);
                    const float u = big ? Lr : Li, v = big ? Li : Lr;
                    const float t = v / u, d = 2.0f / fmaf(v, t, u);
                    const float cr = (big ? fmaf(ni, t, nr) : fmaf(nr, t, ni)) * d, ci = (big ? fmaf(-nr, t, ni) : fmaf(ni, t, -nr)) * d;
                    if (p.swap) li = -li;
                    const float m00 = p.swap ? -ci : cr, m01 = p.swap ? cr : -ci, m10 = p.swap ? -cr : -ci, m11 = p.swap ? -ci : -cr;
#pragma unroll
                    for (int q = 0; q < 4; ++q) {
                        sts128f(t_s + q * 16, lr, li, m00, m01);
                        sts128f(t_s + 12288 + q * 16, 0.f, 0.f, 0.f, 0.f);
                    }
#pragma unroll 1
                    for (int i = 0; i < 6; ++i) CMUL(lr, li, lr, li, lr, li);
                    float ar, ai, br, bi;
                    CMUL(ar, ai, lr, li, lr, li);
                    CMUL(br, bi, ar, ai, lr, li);
                    sts128f(t_s + 4096, m10, m11, 0.f, 0.f);
#pragma unroll
                    for (int q = 1; q < 4; ++q) sts128f(t_s + 4096 + q * 16, m10, m11, lr, li);
                    sts128f(t_s + 8192, 0.f, 0.f, 1.f, 0.f);
                    sts128f(t_s + 8192 + 16, 0.f, 0.f, lr, li);
                    sts128f(t_s + 8192 + 32, ar, ai, ar, ai);
                    sts128f(t_s + 8192 + 48, ar, ai, br, bi);
                    CMUL(ar, ai, ar, ai, ar, ai);
                    br = 1.f; bi = 0.f;
#pragma unroll 1
                    for (int k = c - 1; k >= 0; --k) {
                        sts64f(t_s + 12288 + (k & 3) * 16 + (k >> 2) * 8, br, bi);
                        CMUL(br, bi, br, bi, ar, ai);
                    }
                    mbar_arrive_local(bar_c);
                }
                if (warp == 9) {
#pragma unroll 1
                    for (int ev = 0; ev < 3; ++ev) {
                        if (ev == 2) {
                            uint8_t* box = p.s->X + (size_t)(role * 2 + rank) * kXBytes + lane * 16;
#pragma unroll 1
                            for (int i = 0; i < kXBytes; i += 512) stg128(box + i, 0, 0, 0, 0);
                        }
                        bar_sync(3 + ev, 288);
                        if (lane == 0) {
                            unsigned* cnt = &p.s->cnt[(ev == 0 ? c : 16 * ev - 8 + rb) * 32];
                            asm volatile("fence.acq_rel.gpu;\nfence.proxy.async.global;" ::: "memory");
                            asm volatile("red.relaxed.gpu.global.add.u32 [%0], 1;" ::"l"(cnt) : "memory");
                        }
                        __syncwarp();
                    }
                } else if (lane == 0) {
                    const unsigned tag = lds32(tag_s);
#pragma unroll 1
                    for (int ev = 0; ev < 3; ++ev) {
                        wait_counter(&p.s->cnt[(ev == 0 ? c : 16 * ev - 8 + rb) * 32], tag * (ev == 0 ? 16u : 8u));
                        mbar_arrive_local(bar_dep + 8 * ev);
                        if (ev == 0 && atomicInc(&p.s->done, 127u) == 127u) {
                            st_relaxed32(&p.s->epoch, tag);
#pragma unroll 1
                            for (int i = 0; i < 64; i += 4) stg128(&p.s->claim[i], 0, 0, 0, 0);
                        }
                    }
                }
            }
        } else if (elect_one()) {
            int it = 1, again = 15;
            if (MC0) tma5_mc(sbase + kABytes + rank * 16384, &mXs, bar_full, 0, 0, 0, rank * 16, role >> 3);
#define ACQUIRE(BYTES)                                                   \
    const uint32_t st = sbase + (it & 3) * kStageBytes, fb = bar_full + 8 * (it & 3); \
    mbar_wait(bar_empty + 8 * (it & 3), ((it >> 2) & 1) ^ 1);     \
    mbar_expect_tx(fb, BYTES);
#pragma unroll 1
            for (; it < 16; ++it) {
                ACQUIRE(49152);
                tma4(st, &mB, fb, it * 64, 0, 0, ((role & 7) * 2 + (int)rank) * 8);
                tma5_mc(st + kABytes + rank * 16384, &mXs, fb, it * 64, 0, 0, rank * 16, role >> 3);
                if (it == again) {
                    mbar_wait(bar_role, 0);
                    const uint2 fin = lds64(role_s);
                    role = fin.x & 63;
                    if (fin.x != fin.y) { it = -1; again = 16; }
                }
            }
            ROLE_VARS();
#pragma unroll 1
            for (; it < 48; ++it) {
                const bool t1 = it < 32;
                const int k0 = (it & 15) * 64;
                ACQUIRE(t1 ? 40960 : 49152);
                tma5(st, &mXf, fb, k0, 0, 0, rank * 4, c);
                tma3_mc(st + kABytes + rank * (t1 ? 12288 : 16384), t1 ? &mW1b : &mW1a, fb, 0, k0 + rank * 32, t1 ? 32 + 3 * j8 : 4 * j8);
                if ((it & ~2) == XLDKB) {
                    const int h = (it >> 1) & 1;
                    if (h == 0) mbar_expect_tx(bar_x, 32768);
                    tma5(sbase + kXOff + h * 16384, &mXf, bar_x, colK + h * 64, 0, 0, rank * 4, c);
                }
            }
            STAMPA(true, 8);
            mbar_wait(bar_dep, 0);
            asm volatile("fence.proxy.async.global;" ::: "memory");
            STAMPA(true, 9);
#pragma unroll 1
            for (; it < 64; ++it) {
                const int k0 = (it & 15) * 64;
                ACQUIRE(49152);
                tma3(st, &mHs, fb, 0, kh * 1024 + k0, rb * 2);
                tma2_mc(st + kABytes + rank * 16384, kh ? &mCim : &mCre, fb, k0, rank ? colS : colK);
            }
            int f0 = 2048 + 768 * kh;
#pragma unroll 1
            for (; it < kTotal; ++it, f0 += 64) {
                if (it == 64 || it == 76) {
                    mbar_wait(bar_dep + (it == 64 ? 8 : 16), 0);
                    asm volatile("fence.proxy.async.global;" ::: "memory");
                    if (it == 76) f0 = 1024 * kh;
                }
                if (f0 == 256 * j8) f0 += 256;
                if (it == 88) f0 = 256 * (j8 ^ 4);
                ACQUIRE(49152);
                tma2(st, &mHf, fb, f0, rb * 128);
                tma5_mc(st + kABytes + rank * 16384, &mW2, fb, 0, 0, (f0 >> 3) + 4 * rank, 0, colK >> 6);
                if (it < 88) tma5_mc(st + kABytes + rank * 16384 + 8192, &mW2, fb, 0, 0, (f0 >> 3) + 4 * rank, 0, colS >> 6);
                else tma3_mc(st + kABytes + rank * 16384 + 8192, &mW2n, fb, 0, (f0 ^ 1024) + 32 * rank, colK >> 6);
                if ((it >> 3) == PFKB / 8) tma3_pf(&mW2n, 0, 256 * (j8 & 3) + (it & 4) * 256 + (it & 3) * 64 + 32 * rank, colK >> 6);
            }
        }
    } else {
        INIT_ALL();
        if (warp >= 8 - PF0LINES) {
            const int row = blockIdx.x * 32 + lane;
            const __nv_bfloat16* src = (row < 2048) ? p.x : (row < 3072) ? p.b_re - 2048 * kD : p.b_im - 3072 * kD;
            asm volatile("prefetch.global.L2 [%0];" ::"l"(src + row * kD + (7 - warp) * 64) : "memory");
        }
        __syncwarp();
        cluster_arrive();
        asm volatile("setmaxnreg.inc.sync.aligned.u32 240;");
        const int wg = warp >> 2, w = warp & 3, r = lane >> 2, q = lane & 3, tw = tid & 127;
        uint32_t a_lo = (kSmemOrg + wg * 8192) >> 4;
        constexpr uint32_t b_lo = (kSmemOrg + kABytes) >> 4;
        const uint32_t rel_addr = mapa(bar_empty, (uint32_t)(lane & 1));
        const uint32_t gate_s = sbase + kGateOff;
        float acc[128];
        uint32_t pk[64];
        unsigned tag;
        UNDEF_R(tag);

#pragma unroll
        for (int i = 0; i < 128; ++i) UNDEF_F(acc[i]);
        float gs = 0.f;
        {
            const uint32_t gx_s = sbase + kABytes + (16 * rank + 2 * warp + (lane >> 4)) * 128 +
                                  ((((lane & 15) >> 1) ^ (2 * w + (lane >> 4))) << 4) + (lane & 1) * 8;
            const uint32_t gw_s = sbase + kXOff + (lane & 15) * 8;
            uint32_t again = 15;
            cluster_wait();
#pragma unroll 1
            for (uint32_t it = 0; it < 16; ++it) {
                const uint32_t so = (it & 3) * (kStageBytes >> 4);
                KB_OPEN(it, it == 15);
                wgmma_fence();
                mma_kblock<0>(acc, a_lo + so, b_lo + so, it != 0);
                wgmma_commit();
                KB_CLOSE(it, it == 15, it + again != 15);
                STAMPA(tid == 0 && it == 0, 1);
                mbar_wait(bar_x, 0);
                const uint2 xa = lds64(gx_s + (role & 7) * 4096 + (it & 3) * kStageBytes), wa = lds64(gw_s + it * 128);
                const uint32_t pa = bf2_mul(xa.x, wa.x), pb = bf2_mul(xa.y, wa.y);
                gs += (bf_lo(pa) + bf_hi(pa)) + (bf_lo(pb) + bf_hi(pb));
                if (it == again) {
                    mbar_wait(bar_c, 0);
                    const uint2 fin = lds64(role_s);
                    role = fin.x & 63;
                    if (__shfl_sync(0xffffffffu, fin.x != fin.y, 0)) { it = -1; again = 16; gs = 0.f; }
                }
            }
        }
        role = __shfl_sync(0xffffffffu, role, 0);
        ROLE_VARS();
        {
            tag = lds32(tag_s);
#pragma unroll
            for (int o = 8; o > 0; o >>= 1) gs += __shfl_xor_sync(0xffffffffu, gs, o);
            const float g = bf16_round(__frcp_rn(1.0f + expf(-bf16_round(gs))));
            if ((lane & 15) == 0) st_relaxed64(&p.s->gate[c * 256 + (lane >> 4) + 64 * w + 4 * cb + 2 * wg], __float_as_uint(g), tag);
        }
        const uint32_t tab_s = sbase + kTabOff + tid * 16;
        const float4 k0 = lds128f(tab_s);
        TILE_END();
        STAMPA(tid == 0, 2);
#pragma unroll
        for (int s = 0; s < 64; ++s) pk[s] = pack_bf16_v(acc[4 * (s >> 1) + (s & 1)], acc[4 * (s >> 1) + 2 + (s & 1)]);
#pragma unroll
        for (int i = 0; i < 96; ++i) UNDEF_F(acc[i]);

        const float lr = k0.x, li = k0.y, m00 = k0.z, m01 = k0.w;
        float m10, m11, hr = 0.f, hi = 0.f;
        uint32_t gg[4], orr[4], oii[4];
        const int ch = cb * 64 + warp * 8 + r;
        __nv_bfloat16* hs = p.s->Hs + (size_t)ch * 2048 + c * 256 + q * 8;
#define PASS2(KB)                                                                                      \
    _Pragma("unroll") for (int s = 0; s < 64; s += 2) {                                                \
        if (pass2_kb(s) != (KB)) continue;                                                             \
        if ((s & 7) == 0) {                                                                            \
            const uint4 ga = lds128(gate_s + (q * 72 + s) * 2);                                        \
            gg[0] = ga.x; gg[1] = ga.y; gg[2] = ga.z; gg[3] = ga.w;                                    \
        }                                                                                              \
        float o0[2], o1[2];                                                                            \
        _Pragma("unroll") for (int k = 0; k < 2; ++k) {                                                \
            PIN_R(pk[s + k]);                                                                          \
            float nr = bf_lo(pk[s + k]), ni = bf_hi(pk[s + k]);                                        \
            CFMA(nr, ni, lr, li, hr, hi);                                                              \
            hr = nr; hi = ni;                                                                          \
            o0[k] = fmaf(m00, hr, m01 * hi);                                                           \
            o1[k] = fmaf(m10, hr, m11 * hi);                                                           \
        }                                                                                              \
        orr[(s >> 1) & 3] = bf2_mul(pack_bf16(o0[0], o0[1]), gg[(s >> 1) & 3]);                        \
        oii[(s >> 1) & 3] = bf2_mul(pack_bf16(o1[0], o1[1]), gg[(s >> 1) & 3]);                        \
        if ((s & 7) == 6) {                                                                            \
            stg128(hs + 32 * (s >> 3), orr[0], orr[1], orr[2], orr[3]);                                \
            stg128(hs + 1024 * 2048 + 32 * (s >> 3), oii[0], oii[1], oii[2], oii[3]);                  \
        }                                                                                              \
    }                                                                                                  \
    PIN_F(hr); PIN_F(hi);
        {
            uint4 av0, av1, gv;
            float lqr, lqi;
#pragma unroll
            for (int kb = 0; kb < 16; ++kb) {
                PIN_R(a_lo);
                KBLOCK(1, 16 + kb, kb == 0, kb == 15);
                if (kb < 4) {
#pragma unroll
                    for (int s = kb * 16; s < kb * 16 + 16; ++s) {
                        float nr = bf_lo(pk[s]), ni = bf_hi(pk[s]);
                        CFMA(nr, ni, lr, li, hr, hi);
                        hr = nr; hi = ni;
                    }
                    PIN_F(hr); PIN_F(hi);
                }
                if (kb == 2) gv = ld_relaxed2x64(&p.s->gate[c * 256 + 2 * tw]);
                if (kb == 3) {
                    const float4 k1 = lds128f(tab_s + 4096), k2 = lds128f(tab_s + 8192);
                    m10 = k1.x; m11 = k1.y; lqr = k2.z; lqi = k2.w;
                    float tr = __shfl_up_sync(0xffffffffu, hr, 1, 4), ti = __shfl_up_sync(0xffffffffu, hi, 1, 4);
                    if (q >= 1) CFMA(hr, hi, k1.z, k1.w, tr, ti);
                    tr = __shfl_up_sync(0xffffffffu, hr, 2, 4); ti = __shfl_up_sync(0xffffffffu, hi, 2, 4);
                    if (q >= 2) CFMA(hr, hi, k2.x, k2.y, tr, ti);
                    if (q == 3) st_relaxed2x64(&p.s->agg[c * 1024 + ch], __float_as_uint(hr), tag, __float_as_uint(hi), tag);
                    tr = __shfl_up_sync(0xffffffffu, hr, 1, 4); ti = __shfl_up_sync(0xffffffffu, hi, 1, 4);
                    hr = (q >= 1) ? tr : 0.f; hi = (q >= 1) ? ti : 0.f;
                }
                if (kb == 4) {
                    unsigned spins = 0;
                    while (__any_sync(0xffffffffu, gv.y != tag || gv.w != tag)) {
                        if (++spins > kSpinLimit) break;
                        gv = ld_relaxed2x64(&p.s->gate[c * 256 + 2 * tw]);
                    }
                    sts32(gate_s + ((tw >> 5) * 72 + 2 * lane) * 2, __byte_perm(gv.x, gv.z, 0x7632));
                }
                if (kb == 5) {
                    av0 = make_uint4(0, tag, 0, tag); av1 = av0;
                    if (q < c) av0 = ld_relaxed2x64(&p.s->agg[q * 1024 + ch]);
                    if (q + 4 < c) av1 = ld_relaxed2x64(&p.s->agg[(q + 4) * 1024 + ch]);
                    bar_sync(1 + wg, 128);
                }
                if (kb == 6) {
                    const float4 k3 = lds128f(tab_s + 12288);
                    unsigned spins = 0;
                    while (__any_sync(0xffffffffu, av0.y != tag || av0.w != tag || av1.y != tag || av1.w != tag)) {
                        if (++spins > kSpinLimit) break;
                        if (q < c) av0 = ld_relaxed2x64(&p.s->agg[q * 1024 + ch]);
                        if (q + 4 < c) av1 = ld_relaxed2x64(&p.s->agg[(q + 4) * 1024 + ch]);
                    }
                    float vr, vi;
                    CMUL(vr, vi, k3.x, k3.y, __uint_as_float(av0.x), __uint_as_float(av0.z));
                    CFMA(vr, vi, k3.z, k3.w, __uint_as_float(av1.x), __uint_as_float(av1.z));
                    vr += __shfl_xor_sync(0xffffffffu, vr, 1); vi += __shfl_xor_sync(0xffffffffu, vi, 1);
                    vr += __shfl_xor_sync(0xffffffffu, vr, 2); vi += __shfl_xor_sync(0xffffffffu, vi, 2);
                    CFMA(hr, hi, lqr, lqi, vr, vi);
                }
                if (kb >= 6) { PASS2(kb); }
            }
            TILE_END();
        }
        STAMPA(tid == 0, 3);
#pragma unroll
        for (int i = 0; i < 48; ++i) pk[i] = pack_bf16_v(acc[2 * i], acc[2 * i + 1]);
#pragma unroll
        for (int i = 0; i < 128; ++i) UNDEF_F(acc[i]);

        PIN_R(a_lo);
        KBLOCK(2, 32, true, false);
        PASS2(16);
        PIN_R(a_lo);
        KBLOCK(2, 33, false, false);
        PASS2(17);
        bar_arrive(3, 288);
        const uint32_t gate_row = gate_s + ((2 * (w & 1)) * 72 + 8 * (4 * rank + 2 * wg + (w >> 1)) + r) * 2;
        uint32_t om0, om1;
        {
            const float a = 1.0f - bf_lo(lds16(gate_row)), b = 1.0f - bf_lo(lds16(gate_row + 72 * 2));
            om0 = pack_bf16(a, a); om1 = pack_bf16(b, b);
        }
        __nv_bfloat16* hf = p.s->Hf + (size_t)(rb * 128 + wg * 64 + w * 16 + r) * kF + q * 8 + 2048 + 192 * j8;
        uint32_t bias_s = sbase + kBiasOff + q * 16;
#define FFN_SLICE(J)                                                                                   \
    {                                                                                                  \
        const uint4 bv = lds128(bias_s + (J) * 64);                                                    \
        const uint32_t bb[4] = {bv.x, bv.y, bv.z, bv.w};                                               \
        _Pragma("unroll") for (int jj = 0; jj < 4; ++jj) {                                             \
            const uint32_t r0 = bf2_add_relu(pk[8 * (J) + 2 * jj], bb[jj]), r1 = bf2_add_relu(pk[8 * (J) + 2 * jj + 1], bb[jj]); \
            pk[8 * (J) + 2 * jj] = bf2_mul(bf2_mul(r0, r0), om0);                                      \
            pk[8 * (J) + 2 * jj + 1] = bf2_mul(bf2_mul(r1, r1), om1);                                  \
        }                                                                                              \
        stg128(hf + 32 * (J), pk[8 * (J)], pk[8 * (J) + 2], pk[8 * (J) + 4], pk[8 * (J) + 6]);         \
        stg128(hf + 8 * kF + 32 * (J), pk[8 * (J) + 1], pk[8 * (J) + 3], pk[8 * (J) + 5], pk[8 * (J) + 7]); \
    }
        const uint32_t x_s = sbase + kXOff + (wg * 64 + w * 16 + (lane & 15)) * 128 + (((lane >> 4) ^ (lane & 7)) << 4);
        {
            uint32_t j = 0, nsl = 6;
#pragma unroll 1
            for (uint32_t it = 34; it < 88; ++it, ++j) {
                const uint32_t so = (it & 3) * (kStageBytes >> 4);
                if (wg == 1 && (it == 86 || (ORDER && it == 47))) bar_sync(7, 256);
                KB_OPEN(it, false);
                if ((it & ~15u) == 48) {
                    wgmma_fence();
                    mma_kblock<3>(acc, a_lo + so, b_lo + so, it != 48);
                    wgmma_commit();
                } else {
                    wgmma_fence();
                    mma_kblock<2>(acc, a_lo + so, b_lo + so, 1);
                    wgmma_commit();
                }
                if (wg == 0 && (it == 87 || (ORDER && it == 47))) bar_arrive(7, 256);
                KB_CLOSE(it, false, it != 48);
                if (j < nsl) {
                    if (j & 4) {
                        if (j & 2) { if (j & 1) FFN_SLICE(7) else FFN_SLICE(6) } else { if (j & 1) FFN_SLICE(5) else FFN_SLICE(4) }
                    } else {
                        if (j & 2) { if (j & 1) FFN_SLICE(3) else FFN_SLICE(2) } else { if (j & 1) FFN_SLICE(1) else FFN_SLICE(0) }
                    }
                    if (j + 1 == nsl) bar_arrive(1 + (nsl >> 1), 288);
                } else if (it == 47) {
                    hf += 64 * j8 - 2048;
                    bias_s += 6 * 64;
                    j = -1; nsl = 8;
                    TILE_END();
                    STAMPA(tid == 0, 4);
#pragma unroll
                    for (int i = 0; i < 64; ++i) pk[i] = pack_bf16_v(acc[2 * i], acc[2 * i + 1]);
                } else if (it == 84) {
                    mbar_wait(bar_e, 0);
                }
            }
        }
#define TAIL_MMA(T)                                                                                    \
    {                                                                                                  \
        PIN_R(a_lo);                                                                                   \
        wgmma_fence();                                                                                 \
        mma_kblock<4>(acc, a_lo + (T) * (kStageBytes >> 4), b_lo + (T) * (kStageBytes >> 4), 1);       \
        _Pragma("unroll") for (int kk = 0; kk < 4; ++kk)                                               \
            wgmma_n128_rs(acc, pk[16 * (T) + 4 * kk], pk[16 * (T) + 4 * kk + 1], pk[16 * (T) + 4 * kk + 2], pk[16 * (T) + 4 * kk + 3], \
                          kDescHi | (uint64_t)(b_lo + (((T) * kStageBytes + 8192 + (kk >> 1) * 16384 + (kk & 1) * 2048) >> 4) + (256u << 16))); \
        wgmma_commit();                                                                                \
    }
        TILE_END();
        sched_fence(a_lo);
        {
            const uint8_t* xi = p.s->X + (size_t)(role * 2 + rank) * kXBytes + tid * 16;
            uint8_t* xo = const_cast<uint8_t*>(xi) + (kh ? -8 * kXBytes : 8 * kXBytes);
            uint4 rx[8], ev[8];
            uint32_t rs;
#define RXLOAD()                                                                                       \
    {                                                                                                  \
        rs = ld_relaxed32((const unsigned*)(xi + 32768 - tid * 12));                                   \
        _Pragma("unroll") for (int u = 0; u < 8; ++u) rx[u] = ld_relaxed2x64(xi + u * 4096);           \
    }
            {
                STAMP(tid == 0, 15); STAMPB(tid == 128, 1);
                float m[4] = {0.f, 0.f, 0.f, 0.f};
#pragma unroll
                for (int i = 64; i < 128; ++i) m[i & 3] = fmaxf(m[i & 3], fabsf(acc[i]));
                const uint32_t eb = max(__float_as_uint(fmaxf(fmaxf(m[0], m[1]), fmaxf(m[2], m[3]))) >> 23, 15u);
                const float xsc = __uint_as_float((268u - eb) << 23);
                st_relaxed32(xo + 32768 - tid * 12, (eb - 14u) << 23);
#pragma unroll
                for (int u = 0; u < 8; ++u) {
                    const int v = 64 + 8 * u;
                    st_relaxed2x64(xo + u * 4096, pack_f16(acc[v] * xsc, acc[v + 1] * xsc) | 1, pack_f16(acc[v + 2] * xsc, acc[v + 3] * xsc),
                                   pack_f16(acc[v + 4] * xsc, acc[v + 5] * xsc) | 1, pack_f16(acc[v + 6] * xsc, acc[v + 7] * xsc));
                }
                STAMP(tid == 0, 12); STAMPB(tid == 128, 2);
            }
            mbar_wait(bar_full, 0);
            TAIL_MMA(0);
            mbar_wait(bar_full + 8, 0);
            TAIL_MMA(1);
            if (wg == 1) bar_arrive(8, 256);
#pragma unroll
            for (int u = 0; u < 8; ++u) ev[u] = ldsm4((x_s ^ ((u & 3) << 5)) + (u >> 2) * 16384);
            if (wg == 1) mbar_wait(bar_full + 24, 0);
            bar_sync(8 + wg, 256);
            STAMPB(tid == 0, 9);
            RXLOAD();
            mbar_wait(bar_full + 16, 0);
            STAMPB(tid == 0, 10);
            STAMPB(tid == 128, 3);
            TAIL_MMA(2);
            if (wg == 0) mbar_wait(bar_full + 24, 0);
            STAMPB(tid == 0, 11);
            TAIL_MMA(3);
            if (wg == 0) bar_arrive(9, 256);
            sched_fence(a_lo);
            unsigned spins = 0;
#pragma unroll 1
            while (true) {
                uint32_t ok = rs != 0;
#pragma unroll
                for (int u = 0; u < 8; ++u) ok &= rx[u].x & rx[u].z;
                if (__all_sync(0xffffffffu, ok) || ++spins > kSpinLimit) break;
                RXLOAD();
                RESPIN();
            }
            STAMP(tid == 0, 13);
            const float xsc = __uint_as_float(rs);
#pragma unroll
            for (int u = 0; u < 8; ++u) {
                const uint32_t rr[4] = {rx[u].x, rx[u].y, rx[u].z, rx[u].w}, ee[4] = {ev[u].x, ev[u].y, ev[u].z, ev[u].w};
#pragma unroll
                for (int k = 0; k < 4; ++k) {
                    const int v = 64 + 8 * u + 2 * k;
                    const float2 f = __half22float2(*reinterpret_cast<const __half2*>(&rr[k]));
                    acc[v] = fmaf(f.x, xsc, bf_lo(ee[k])); acc[v + 1] = fmaf(f.y, xsc, bf_hi(ee[k]));
                    PIN_F(acc[v]); PIN_F(acc[v + 1]);
                }
            }
            sched_fence(a_lo);
            STAMP(tid == 0, 14);
        }
        wgmma_wait<0>();
        STAMP(tid == 0, 6); STAMPB(tid == 128, 4);
        {
            const bool odd = q & 1;
            const int tb = c * 256 + 128 * (w & 1) + 8 * (4 * rank + 2 * wg + (w >> 1));
            float* o0 = p.out + (size_t)(tb + r) * kD + colK + (odd ? 2 * q + 6 : 2 * q);
#pragma unroll
            for (int i = 0; i < 16; i += 2) {
#pragma unroll
                for (int h = 0; h < 2; ++h) {
                    const int va = 4 * i + 2 * h, vb = va + 4;
                    PIN_F(acc[va]); PIN_F(acc[va + 1]); PIN_F(acc[vb]); PIN_F(acc[vb + 1]);
                    const float a0 = acc[va] + acc[64 + va], a1 = acc[va + 1] + acc[65 + va];
                    const float b0 = acc[vb] + acc[64 + vb], b1 = acc[vb + 1] + acc[65 + vb];
                    const float t0 = __shfl_xor_sync(0xffffffffu, odd ? a0 : b0, 1), t1 = __shfl_xor_sync(0xffffffffu, odd ? a1 : b1, 1);
                    stg128f(o0 + h * 64 * kD + 8 * i, odd ? t0 : a0, odd ? t1 : a1, odd ? b0 : t0, odd ? b1 : t1);
                }
            }
        }
        STAMP(tid == 0, 7);
        STAMP(tid == 128, 5);
    }
}

typedef CUresult (*EncodeFn)(CUtensorMap*, CUtensorMapDataType, cuuint32_t, void*, const cuuint64_t*, const cuuint64_t*,
                             const cuuint32_t*, const cuuint32_t*, CUtensorMapInterleave, CUtensorMapSwizzle,
                             CUtensorMapL2promotion, CUtensorMapFloatOOBfill);

bool encode(EncodeFn fn, CUtensorMap* m, const void* base, int rank, const cuuint64_t* dims, const cuuint64_t* strides,
            const cuuint32_t* box) {
    cuuint32_t es[5] = {1, 1, 1, 1, 1};
    return fn(m, CU_TENSOR_MAP_DATA_TYPE_BFLOAT16, rank, const_cast<void*>(base), dims, strides, box, es,
              CU_TENSOR_MAP_INTERLEAVE_NONE, CU_TENSOR_MAP_SWIZZLE_128B, CU_TENSOR_MAP_L2_PROMOTION_L2_256B,
              CU_TENSOR_MAP_FLOAT_OOB_FILL_NONE) == CUDA_SUCCESS;
}

}

extern "C" void kernel_launch(void* const* d_in, const int* in_sizes, int n_in, void* d_out, int out_size) {
    (void)in_sizes; (void)n_in; (void)out_size;
    typedef const __nv_bfloat16* bp;
    bp x = (bp)d_in[0], lam_re = (bp)d_in[1], lam_im = (bp)d_in[2], B_re = (bp)d_in[3], B_im = (bp)d_in[4];
    bp C_re = (bp)d_in[5], C_im = (bp)d_in[6], log_dt = (bp)d_in[7], dskip = (bp)d_in[8];
    bp w1 = (bp)d_in[10], b1 = (bp)d_in[11], w2 = (bp)d_in[12], b2 = (bp)d_in[13], gate_w = (bp)d_in[14];

    static EncodeFn fn = nullptr;
    static Scratch* ps = nullptr;
    if (!fn) {
        void* f = nullptr;
        cudaDriverEntryPointQueryResult qr;
        cudaGetDriverEntryPoint("cuTensorMapEncodeTiled", &f, cudaEnableDefault, &qr);
        fn = (EncodeFn)f;
        cudaGetSymbolAddress((void**)&ps, g_s);
        cudaFuncSetAttribute(fused_kernel, cudaFuncAttributeMaxDynamicSharedMemorySize, kSmemBytes);
    }
    cudaStream_t stream = cudaStreamPerThread;

    Params p;
    p.x = x; p.lam_re = lam_re; p.lam_im = lam_im; p.log_dt = log_dt; p.dskip = dskip; p.b1 = b1; p.b2 = b2;
    p.gate_w = gate_w; p.b_re = B_re; p.b_im = B_im; p.out = (float*)d_out; p.s = ps;
    char* const pHs = (char*)ps + offsetof(Scratch, Hs);
    char* const pHf = (char*)ps + offsetof(Scratch, Hf);
    char* const pBc = (char*)ps + offsetof(Scratch, Bcopy);

    const char* lo = (const char*)B_re; const char* hi = (const char*)B_im;
    p.swap = 0;
    if (hi < lo) { const char* t = lo; lo = hi; hi = t; p.swap = 1; }
    unsigned long long diff = (unsigned long long)(hi - lo);
    if (diff >= (1ull << 40) || (diff & 15) || diff == 0) {
        cudaMemcpyAsync(pBc, B_re, 2u << 20, cudaMemcpyDeviceToDevice, stream);
        cudaMemcpyAsync((char*)pBc + (2u << 20), B_im, 2u << 20, cudaMemcpyDeviceToDevice, stream);
        lo = (const char*)pBc; diff = 2u << 20; p.swap = 0;
    }

    CUtensorMap mB, mXs, mXf, mW1a, mW1b, mHs, mHf, mCre, mCim, mW2, mW2n;
    bool ok = true;
    { cuuint64_t d[4] = {1024, 8, 2, 128}, s[3] = {2048, diff, 16384}; cuuint32_t b[4] = {64, 8, 2, 8};
      ok &= encode(fn, &mB, lo, 4, d, s, b); }
    { cuuint64_t d[5] = {1024, 2, 4, 32, 8}, s[4] = {2048, 64 * 2048, 2 * 2048, 256 * 2048}; cuuint32_t b[5] = {64, 2, 4, 16, 1};
      ok &= encode(fn, &mXs, x, 5, d, s, b); }
    { cuuint64_t d[5] = {1024, 8, 4, 8, 8}, s[4] = {2048, 64 * 2048, 8 * 2048, 256 * 2048}; cuuint32_t b[5] = {64, 8, 4, 4, 1};
      ok &= encode(fn, &mXf, x, 5, d, s, b); }
    { cuuint64_t d[3] = {64, 1024, 56}, s[2] = {7168, 128}; cuuint32_t ba[3] = {64, 32, 4}, bb[3] = {64, 32, 3};
      ok &= encode(fn, &mW1a, w1, 3, d, s, ba); ok &= encode(fn, &mW1b, w1, 3, d, s, bb); }
    { cuuint64_t d[3] = {64, 2048, 32}, s[2] = {4096, 128}; cuuint32_t b[3] = {64, 64, 2};
      ok &= encode(fn, &mHs, pHs, 3, d, s, b); }
    { cuuint64_t d[2] = {3584, 2048}, s[1] = {7168}; cuuint32_t b[2] = {64, 128};
      ok &= encode(fn, &mHf, pHf, 2, d, s, b); }
    { cuuint64_t d[2] = {1024, 1024}, s[1] = {2048}; cuuint32_t b[2] = {64, 128};
      ok &= encode(fn, &mCre, C_re, 2, d, s, b); ok &= encode(fn, &mCim, C_im, 2, d, s, b); }
    { cuuint64_t d[5] = {64, 2, 448, 4, 16}, s[4] = {2048, 8 * 2048, 2 * 2048, 128}; cuuint32_t b[5] = {64, 2, 4, 4, 2};
      ok &= encode(fn, &mW2, w2, 5, d, s, b); }
    { cuuint64_t d[3] = {64, 3584, 16}, s[2] = {2048, 128}; cuuint32_t b[3] = {64, 32, 2};
      ok &= encode(fn, &mW2n, w2, 3, d, s, b); }
    if (!ok) return;

    fused_kernel<<<128, 384, kSmemBytes, stream>>>(mB, mXs, mXf, mW1b, mW1a, mHs, mHf, mCre, mCim, mW2, mW2n, p);
}
```

```cpp
#include <cuda_runtime.h>
#include <cuda_bf16.h>
#include <cuda_fp16.h>
#include <cuda.h>
#include <stdint.h>
#include <stddef.h>

#define XLDKB 40
#define PF0LINES 1
#define PFKB 80
#define SKEW 2
#define CLREV 0
#define CLRNS 64
#define SPREAD 1
#define BACKOFF 100
#define RXPOS 1
#define MC0 0
#define PFTOP 0
#define INITW 0
#define PRODCOND warp >= 8
#define ORDER 0

namespace {

constexpr int kD = 1024, kF = 3584;
constexpr int kStages = 4;
constexpr int kStageBytes = 49152;
constexpr int kABytes = 16384;
constexpr int kXOff = kStages * kStageBytes;
constexpr int kTabOff = kXOff + 2048;
constexpr int kGateOff = kXOff + 32768;
constexpr int kBiasOff = kGateOff + 4 * 72 * 2;
constexpr int kBarOff = kBiasOff + 56 * 16;
constexpr int kSmemBytes = 232448;
static_assert(kBarOff + 160 <= kSmemBytes, "smem");
constexpr int kXBytes = 33792;
constexpr uint32_t kSmemOrg = 1024;
constexpr unsigned kSpinLimit = 1u << 18;
constexpr int kTotal = 92;

__host__ __device__ constexpr int pass2_kb(int s) {
    return s < 2 ? 6 : s < 8 ? 7 : s < 12 ? 8 : s < 18 ? 9 : s < 22 ? 10 : s < 28 ? 11 : s < 32 ? 12 : s < 38 ? 13 : s < 42 ? 14 : s < 48 ? 15 : s < 56 ? 16 : 17;
}

struct Scratch {
    unsigned claim[64];
    unsigned epoch, pad0[31];
    unsigned done, pad1[31];
    unsigned cnt[40 * 32];
    uint2 gate[2048];
    uint4 agg[8 * 1024];
    __align__(1024) uint8_t X[128 * kXBytes];
    __align__(1024) __nv_bfloat16 Hs[2048 * 2048];
    __align__(1024) __nv_bfloat16 Hf[2048 * 3584];
    __align__(1024) __nv_bfloat16 Bcopy[2 * 1024 * 1024];
};
__device__ Scratch g_s;

#define TRAP() break
#define PIN_F(x) asm volatile("" : "+f"(x))
#define PIN_R(x) asm volatile("" : "+r"(x))
#define UNDEF_F(x) asm volatile("" : "=f"(x))
#define UNDEF_R(x) asm volatile("" : "=r"(x))
#define RESPIN()
__device__ __forceinline__ uint32_t smem_u32(const void* p) { return (uint32_t)__cvta_generic_to_shared(p); }
__device__ __forceinline__ void mbar_init(uint32_t bar, uint32_t count) {
    asm volatile("mbarrier.init.shared::cta.b64 [%0], %1;" ::"r"(bar), "r"(count) : "memory");
}
__device__ __forceinline__ void mbar_expect_tx(uint32_t bar, uint32_t bytes) {
    asm volatile("mbarrier.arrive.expect_tx.shared::cta.b64 _, [%0], %1;" ::"r"(bar), "r"(bytes) : "memory");
}
__device__ __forceinline__ void mbar_wait(uint32_t bar, uint32_t parity) {
    asm volatile(
        "{\n.reg .pred p;\n.reg .u32 n;\n"
        "mbarrier.try_wait.parity.shared::cta.b64 p, [%0], %1;\n"
        "@p bra DONE;\n"
        "mov.u32 n, 0;\n"
        "LOOP:\n"
        "mbarrier.try_wait.parity.shared::cta.b64 p, [%0], %1;\n"
        "@p bra DONE;\n"
        "add.u32 n, n, 1;\n"
        "setp.lt.u32 p, n, %2;\n"
        "@p bra LOOP;\n"
        "DONE:\n}\n"
        ::"r"(bar), "r"(parity), "n"(kSpinLimit) : "memory");
}
__device__ __forceinline__ void sched_fence(uint32_t nonzero) {
    asm volatile("{\n.reg .pred p;\n.reg .u32 n;\nsetp.ne.u32 p, %0, 0;\n@p bra DONE;\nLOOP:\nmov.u32 n, %%clock;\n"
                 "setp.eq.u32 p, n, 0;\n@p bra LOOP;\nDONE:\n}\n" ::"r"(nonzero) : "memory");
}
__device__ __forceinline__ void mbar_arrive_local(uint32_t bar) {
    asm volatile("mbarrier.arrive.shared::cta.b64 _, [%0];" ::"r"(bar) : "memory");
}
__device__ __forceinline__ void mbar_arrive_cluster(uint32_t cluster_addr) {
    asm volatile("mbarrier.arrive.shared::cluster.b64 _, [%0];" ::"r"(cluster_addr) : "memory");
}
__device__ __forceinline__ uint32_t mapa(uint32_t addr, uint32_t rank) {
    uint32_t r;
    asm("mapa.shared::cluster.u32 %0, %1, %2;" : "=r"(r) : "r"(addr), "r"(rank));
    return r;
}
__device__ __forceinline__ void cluster_arrive() { asm volatile("barrier.cluster.arrive.relaxed.aligned;" ::: "memory"); }
__device__ __forceinline__ void cluster_wait() { asm volatile("barrier.cluster.wait.acquire.aligned;" ::: "memory"); }
__device__ __forceinline__ void bar_sync(int id, int n) { asm volatile("bar.sync %0, %1;" ::"r"(id), "r"(n) : "memory"); }
__device__ __forceinline__ void bar_arrive(int id, int n) { asm volatile("bar.arrive %0, %1;" ::"r"(id), "r"(n) : "memory"); }
__device__ __forceinline__ bool elect_one() {
    uint32_t p;
    asm volatile("{\n.reg .pred P;\nelect.sync _|P, 0xffffffff;\nselp.u32 %0, 1, 0, P;\n}\n" : "=r"(p));
    return p != 0;
}

__device__ __forceinline__ void tma2(uint32_t dst, const CUtensorMap* m, uint32_t bar, int c0, int c1) {
    asm volatile("cp.async.bulk.tensor.2d.shared::cluster.global.mbarrier::complete_tx::bytes [%0], [%1, {%3, %4}], [%2];"
                 ::"r"(dst), "l"(m), "r"(bar), "r"(c0), "r"(c1) : "memory");
}
__device__ __forceinline__ void tma3(uint32_t dst, const CUtensorMap* m, uint32_t bar, int c0, int c1, int c2) {
    asm volatile("cp.async.bulk.tensor.3d.shared::cluster.global.mbarrier::complete_tx::bytes [%0], [%1, {%3, %4, %5}], [%2];"
                 ::"r"(dst), "l"(m), "r"(bar), "r"(c0), "r"(c1), "r"(c2) : "memory");
}
__device__ __forceinline__ void tma4(uint32_t dst, const CUtensorMap* m, uint32_t bar, int c0, int c1, int c2, int c3) {
    asm volatile("cp.async.bulk.tensor.4d.shared::cluster.global.mbarrier::complete_tx::bytes [%0], [%1, {%3, %4, %5, %6}], [%2];"
                 ::"r"(dst), "l"(m), "r"(bar), "r"(c0), "r"(c1), "r"(c2), "r"(c3) : "memory");
}
__device__ __forceinline__ void tma5(uint32_t dst, const CUtensorMap* m, uint32_t bar, int c0, int c1, int c2, int c3, int c4) {
    asm volatile("cp.async.bulk.tensor.5d.shared::cluster.global.mbarrier::complete_tx::bytes [%0], [%1, {%3, %4, %5, %6, %7}], [%2];"
                 ::"r"(dst), "l"(m), "r"(bar), "r"(c0), "r"(c1), "r"(c2), "r"(c3), "r"(c4) : "memory");
}
__device__ __forceinline__ void tma2_mc(uint32_t dst, const CUtensorMap* m, uint32_t bar, int c0, int c1) {
    asm volatile("cp.async.bulk.tensor.2d.shared::cluster.global.mbarrier::complete_tx::bytes.multicast::cluster [%0], [%1, {%3, %4}], [%2], %5;"
                 ::"r"(dst), "l"(m), "r"(bar), "r"(c0), "r"(c1), "h"((uint16_t)3) : "memory");
}
__device__ __forceinline__ void tma3_mc(uint32_t dst, const CUtensorMap* m, uint32_t bar, int c0, int c1, int c2) {
    asm volatile("cp.async.bulk.tensor.3d.shared::cluster.global.mbarrier::complete_tx::bytes.multicast::cluster [%0], [%1, {%3, %4, %5}], [%2], %6;"
                 ::"r"(dst), "l"(m), "r"(bar), "r"(c0), "r"(c1), "r"(c2), "h"((uint16_t)3) : "memory");
}
__device__ __forceinline__ void tma5_mc(uint32_t dst, const CUtensorMap* m, uint32_t bar, int c0, int c1, int c2, int c3, int c4) {
    asm volatile("cp.async.bulk.tensor.5d.shared::cluster.global.mbarrier::complete_tx::bytes.multicast::cluster [%0], [%1, {%3, %4, %5, %6, %7}], [%2], %8;"
                 ::"r"(dst), "l"(m), "r"(bar), "r"(c0), "r"(c1), "r"(c2), "r"(c3), "r"(c4), "h"((uint16_t)3) : "memory");
}
__device__ __forceinline__ void tma3_pf(const CUtensorMap* m, int c0, int c1, int c2) {
    asm volatile("cp.async.bulk.prefetch.tensor.3d.L2.global [%0, {%1, %2, %3}];" ::"l"(m), "r"(c0), "r"(c1), "r"(c2) : "memory");
}
__device__ __forceinline__ void tma2_pf(const CUtensorMap* m, int c0, int c1) {
    asm volatile("cp.async.bulk.prefetch.tensor.2d.L2.global [%0, {%1, %2}];" ::"l"(m), "r"(c0), "r"(c1) : "memory");
}
__device__ __forceinline__ void bulk_store(void* dst, uint32_t src, uint32_t bytes) {
    asm volatile("cp.async.bulk.global.shared::cta.bulk_group [%0], [%1], %2;" ::"l"(dst), "r"(src), "r"(bytes) : "memory");
}
__device__ __forceinline__ void tma4_store(const CUtensorMap* m, uint32_t src, int c2, int c3) {
    asm volatile("cp.async.bulk.tensor.4d.global.shared::cta.bulk_group [%0, {%2, %2, %3, %4}], [%1];"
                 ::"l"(m), "r"(src), "r"(0), "r"(c2), "r"(c3) : "memory");
}
__device__ __forceinline__ void bulk_commit() { asm volatile("cp.async.bulk.commit_group;" ::: "memory"); }
__device__ __forceinline__ void bulk_wait_read() { asm volatile("cp.async.bulk.wait_group.read 0;" ::: "memory"); }
__device__ __forceinline__ void fence_async_smem() { asm volatile("fence.proxy.async.shared::cta;" ::: "memory"); }
__device__ __forceinline__ void bulk_load(uint32_t dst, const void* src, uint32_t bytes, uint32_t bar) {
    asm volatile("cp.async.bulk.shared::cluster.global.mbarrier::complete_tx::bytes [%0], [%1], %2, [%3];"
                 ::"r"(dst), "l"(src), "r"(bytes), "r"(bar) : "memory");
}
__device__ __forceinline__ unsigned atom_exch(unsigned* p, unsigned v) {
    unsigned r;
    asm volatile("atom.relaxed.gpu.global.exch.b32 %0, [%1], %2;" : "=r"(r) : "l"(p), "r"(v) : "memory");
    return r;
}
__device__ __forceinline__ void st_async32(uint32_t a, uint32_t v, uint32_t bar) {
    asm volatile("st.async.shared::cluster.mbarrier::complete_tx::bytes.u32 [%0], %1, [%2];" ::"r"(a), "r"(v), "r"(bar) : "memory");
}
__device__ __forceinline__ void sts128f(uint32_t a, float x, float y, float z, float w) {
    asm volatile("st.shared.v4.f32 [%0], {%1, %2, %3, %4};" ::"r"(a), "f"(x), "f"(y), "f"(z), "f"(w) : "memory");
}
__device__ __forceinline__ void prefetch_map(const CUtensorMap* m) {
    asm volatile("prefetch.tensormap [%0];" ::"l"(m) : "memory");
}

__device__ __forceinline__ void prefetch_l2(const void* p, uint32_t bytes) {
    asm volatile("cp.async.bulk.prefetch.L2.global [%0], %1;" ::"l"(p), "r"(bytes) : "memory");
}

__device__ __forceinline__ void wgmma_fence() { asm volatile("wgmma.fence.sync.aligned;" ::: "memory"); }
__device__ __forceinline__ void wgmma_commit() { asm volatile("wgmma.commit_group.sync.aligned;" ::: "memory"); }
template <int N>
__device__ __forceinline__ void wgmma_wait() { asm volatile("wgmma.wait_group.sync.aligned %0;" ::"n"(N) : "memory"); }

__device__ __forceinline__ uint32_t pack_bf16(float lo, float hi) {
    uint32_t r;
    asm("cvt.rn.bf16x2.f32 %0, %1, %2;" : "=r"(r) : "f"(hi), "f"(lo));
    return r;
}
__device__ __forceinline__ uint32_t pack_f16(float lo, float hi) {
    uint32_t r;
    asm("cvt.rn.f16x2.f32 %0, %1, %2;" : "=r"(r) : "f"(hi), "f"(lo));
    return r;
}
__device__ __forceinline__ uint32_t pack_bf16_v(float lo, float hi) {
    uint32_t r;
    asm volatile("cvt.rn.bf16x2.f32 %0, %1, %2;" : "=r"(r) : "f"(hi), "f"(lo));
    return r;
}
template <int LUT>
__device__ __forceinline__ uint32_t lop3(uint32_t a, uint32_t b, uint32_t c) {
    uint32_t r;
    asm("lop3.b32 %0, %1, %2, %3, %4;" : "=r"(r) : "r"(a), "r"(b), "r"(c), "n"(LUT));
    return r;
}
__device__ __forceinline__ float bf_lo(uint32_t v) { return __uint_as_float(v << 16); }
__device__ __forceinline__ float bf_hi(uint32_t v) { return __uint_as_float(v & 0xffff0000u); }
__device__ __forceinline__ float bf16_round(float v) { return __bfloat162float(__float2bfloat16_rn(v)); }
__device__ __forceinline__ uint32_t bf2_mul(uint32_t a, uint32_t b) {
    uint32_t r;
    asm("mul.rn.bf16x2 %0, %1, %2;" : "=r"(r) : "r"(a), "r"(b));
    return r;
}
__device__ __forceinline__ uint32_t bf2_add_relu(uint32_t a, uint32_t b) {
    uint32_t r;
    asm("fma.rn.relu.bf16x2 %0, %1, %2, %3;" : "=r"(r) : "r"(a), "r"(0x3f803f80u), "r"(b));
    return r;
}
__device__ __forceinline__ uint4 ldg128(const void* p) {
    uint4 v;
    asm volatile("ld.global.nc.v4.u32 {%0, %1, %2, %3}, [%4];" : "=r"(v.x), "=r"(v.y), "=r"(v.z), "=r"(v.w) : "l"(p));
    return v;
}
__device__ __forceinline__ uint32_t ldg32(const void* p) {
    uint32_t v;
    asm volatile("ld.global.nc.u32 %0, [%1];" : "=r"(v) : "l"(p));
    return v;
}
__device__ __forceinline__ uint32_t ldg32na(const void* p) {
    uint32_t v;
    asm volatile("ld.global.nc.L1::no_allocate.u32 %0, [%1];" : "=r"(v) : "l"(p));
    return v;
}
__device__ __forceinline__ uint32_t ldg16(const __nv_bfloat16* p) {
    uint32_t v;
    asm volatile("ld.global.nc.u16 %0, [%1];" : "=r"(v) : "l"(p));
    return v;
}
__device__ __forceinline__ uint4 ld_relaxed128(const void* p) {
    uint4 v;
    asm volatile("ld.relaxed.gpu.global.v4.u32 {%0, %1, %2, %3}, [%4];" : "=r"(v.x), "=r"(v.y), "=r"(v.z), "=r"(v.w) : "l"(p) : "memory");
    return v;
}
__device__ __forceinline__ uint2 ld_relaxed64(const void* p) {
    unsigned long long v;
    asm volatile("ld.relaxed.gpu.global.u64 %0, [%1];" : "=l"(v) : "l"(p) : "memory");
    return make_uint2((uint32_t)v, (uint32_t)(v >> 32));
}
__device__ __forceinline__ void st_relaxed64(void* p, uint32_t lo, uint32_t hi) {
    unsigned long long v = ((unsigned long long)hi << 32) | lo;
    asm volatile("st.relaxed.gpu.global.u64 [%0], %1;" ::"l"(p), "l"(v) : "memory");
}
__device__ __forceinline__ void st_relaxed2x64(void* p, uint32_t a, uint32_t b, uint32_t c, uint32_t d) {
    unsigned long long v0 = ((unsigned long long)b << 32) | a, v1 = ((unsigned long long)d << 32) | c;
    asm volatile("st.relaxed.gpu.global.v2.u64 [%0], {%1, %2};" ::"l"(p), "l"(v0), "l"(v1) : "memory");
}
__device__ __forceinline__ uint4 ld_relaxed2x64(const void* p) {
    unsigned long long v0, v1;
    asm volatile("ld.relaxed.gpu.global.v2.u64 {%0, %1}, [%2];" : "=l"(v0), "=l"(v1) : "l"(p) : "memory");
    return make_uint4((uint32_t)v0, (uint32_t)(v0 >> 32), (uint32_t)v1, (uint32_t)(v1 >> 32));
}
__device__ __forceinline__ void stg128(void* p, uint32_t a, uint32_t b, uint32_t c, uint32_t d) {
    asm volatile("st.global.v4.u32 [%0], {%1, %2, %3, %4};" ::"l"(p), "r"(a), "r"(b), "r"(c), "r"(d) : "memory");
}
__device__ __forceinline__ void stg64f(void* p, float a, float b) {
    asm volatile("st.global.v2.f32 [%0], {%1, %2};" ::"l"(p), "f"(a), "f"(b) : "memory");
}
__device__ __forceinline__ uint4 lds128(uint32_t a) {
    uint4 v;
    asm volatile("ld.shared.v4.u32 {%0, %1, %2, %3}, [%4];" : "=r"(v.x), "=r"(v.y), "=r"(v.z), "=r"(v.w) : "r"(a) : "memory");
    return v;
}
__device__ __forceinline__ uint2 lds64(uint32_t a) {
    uint2 v;
    asm volatile("ld.shared.v2.u32 {%0, %1}, [%2];" : "=r"(v.x), "=r"(v.y) : "r"(a) : "memory");
    return v;
}
__device__ __forceinline__ uint4 ldsm4(uint32_t a) {
    uint4 v;
    asm volatile("ldmatrix.sync.aligned.m8n8.x4.shared.b16 {%0, %1, %2, %3}, [%4];" : "=r"(v.x), "=r"(v.y), "=r"(v.z), "=r"(v.w) : "r"(a) : "memory");
    return v;
}
__device__ __forceinline__ uint32_t lds16(uint32_t a) {
    uint32_t v;
    asm volatile("ld.shared.u16 %0, [%1];" : "=r"(v) : "r"(a) : "memory");
    return v;
}
__device__ __forceinline__ void sts16(uint32_t a, uint32_t x) {
    asm volatile("st.shared.u16 [%0], %1;" ::"r"(a), "h"((uint16_t)x) : "memory");
}
__device__ __forceinline__ void st_relaxed32(void* p, uint32_t v) {
    asm volatile("st.relaxed.gpu.global.u32 [%0], %1;" ::"l"(p), "r"(v) : "memory");
}
__device__ __forceinline__ float lds32f(uint32_t a) {
    float v;
    asm volatile("ld.shared.f32 %0, [%1];" : "=f"(v) : "r"(a) : "memory");
    return v;
}
__device__ __forceinline__ void sts128(uint32_t a, uint32_t x, uint32_t y, uint32_t z, uint32_t w) {
    asm volatile("st.shared.v4.u32 [%0], {%1, %2, %3, %4};" ::"r"(a), "r"(x), "r"(y), "r"(z), "r"(w) : "memory");
}
__device__ __forceinline__ void sts64f(uint32_t a, float x, float y) {
    asm volatile("st.shared.v2.f32 [%0], {%1, %2};" ::"r"(a), "f"(x), "f"(y) : "memory");
}
__device__ __forceinline__ float4 lds128f(uint32_t a) {
    float4 v;
    asm volatile("ld.shared.v4.f32 {%0, %1, %2, %3}, [%4];" : "=f"(v.x), "=f"(v.y), "=f"(v.z), "=f"(v.w) : "r"(a) : "memory");
    return v;
}
__device__ __forceinline__ uint32_t lds32(uint32_t a) {
    uint32_t v;
    asm volatile("ld.shared.u32 %0, [%1];" : "=r"(v) : "r"(a) : "memory");
    return v;
}
__device__ __forceinline__ void sts32(uint32_t a, uint32_t x) {
    asm volatile("st.shared.u32 [%0], %1;" ::"r"(a), "r"(x) : "memory");
}
__device__ __forceinline__ void stg128f(void* p, float a, float b, float c, float d) {
    asm volatile("st.global.v4.f32 [%0], {%1, %2, %3, %4};" ::"l"(p), "f"(a), "f"(b), "f"(c), "f"(d) : "memory");
}
__device__ __forceinline__ unsigned ld_relaxed32(const unsigned* p) {
    unsigned v;
    asm volatile("ld.relaxed.gpu.global.u32 %0, [%1];" : "=r"(v) : "l"(p) : "memory");
    return v;
}
__device__ __forceinline__ void wait_counter(const unsigned* p, unsigned target) {
    unsigned n = 0, v;
    while (true) {
        asm volatile("ld.acquire.gpu.global.u32 %0, [%1];" : "=r"(v) : "l"(p) : "memory");
        if ((int)(v - target) >= 0) break;
        if (++n > kSpinLimit) TRAP();
        __nanosleep(32);
    }
}
#define KT(IT, W) do { } while (0)
#define STAMP(cond, slot) do { } while (0)
#define STAMPA(cond, slot) STAMP(cond, slot)
#define STAMPB(cond, slot) do { } while (0)

#define STAMPC(cond, slot) do { } while (0)
#define STAMPD(cond, slot) do { } while (0)
template <int TA, int TB>
__device__ __forceinline__ void wgmma_n256(float (&d)[128], uint64_t da, uint64_t db, int keep) {
    asm volatile(
        "{\n.reg .pred p;\nsetp.ne.b32 p, %132, 0;\n"
        "wgmma.mma_async.sync.aligned.m64n256k16.f32.bf16.bf16 "
        "{%0, %1, %2, %3, %4, %5, %6, %7, %8, %9, %10, %11, %12, %13, %14, %15, "
        "%16, %17, %18, %19, %20, %21, %22, %23, %24, %25, %26, %27, %28, %29, %30, %31, "
        "%32, %33, %34, %35, %36, %37, %38, %39, %40, %41, %42, %43, %44, %45, %46, %47, "
        "%48, %49, %50, %51, %52, %53, %54, %55, %56, %57, %58, %59, %60, %61, %62, %63, "
        "%64, %65, %66, %67, %68, %69, %70, %71, %72, %73, %74, %75, %76, %77, %78, %79, "
        "%80, %81, %82, %83, %84, %85, %86, %87, %88, %89, %90, %91, %92, %93, %94, %95, "
        "%96, %97, %98, %99, %100, %101, %102, %103, %104, %105, %106, %107, %108, %109, %110, %111, "
        "%112, %113, %114, %115, %116, %117, %118, %119, %120, %121, %122, %123, %124, %125, %126, %127}, "
        "%128, %129, p, 1, 1, %130, %131;\n}\n"
        : "+f"(d[0]), "+f"(d[1]), "+f"(d[2]), "+f"(d[3]), "+f"(d[4]), "+f"(d[5]), "+f"(d[6]), "+f"(d[7]),
          "+f"(d[8]), "+f"(d[9]), "+f"(d[10]), "+f"(d[11]), "+f"(d[12]), "+f"(d[13]), "+f"(d[14]), "+f"(d[15]),
          "+f"(d[16]), "+f"(d[17]), "+f"(d[18]), "+f"(d[19]), "+f"(d[20]), "+f"(d[21]), "+f"(d[22]), "+f"(d[23]),
          "+f"(d[24]), "+f"(d[25]), "+f"(d[26]), "+f"(d[27]), "+f"(d[28]), "+f"(d[29]), "+f"(d[30]), "+f"(d[31]),
          "+f"(d[32]), "+f"(d[33]), "+f"(d[34]), "+f"(d[35]), "+f"(d[36]), "+f"(d[37]), "+f"(d[38]), "+f"(d[39]),
          "+f"(d[40]), "+f"(d[41]), "+f"(d[42]), "+f"(d[43]), "+f"(d[44]), "+f"(d[45]), "+f"(d[46]), "+f"(d[47]),
          "+f"(d[48]), "+f"(d[49]), "+f"(d[50]), "+f"(d[51]), "+f"(d[52]), "+f"(d[53]), "+f"(d[54]), "+f"(d[55]),
          "+f"(d[56]), "+f"(d[57]), "+f"(d[58]), "+f"(d[59]), "+f"(d[60]), "+f"(d[61]), "+f"(d[62]), "+f"(d[63]),
          "+f"(d[64]), "+f"(d[65]), "+f"(d[66]), "+f"(d[67]), "+f"(d[68]), "+f"(d[69]), "+f"(d[70]), "+f"(d[71]),
          "+f"(d[72]), "+f"(d[73]), "+f"(d[74]), "+f"(d[75]), "+f"(d[76]), "+f"(d[77]), "+f"(d[78]), "+f"(d[79]),
          "+f"(d[80]), "+f"(d[81]), "+f"(d[82]), "+f"(d[83]), "+f"(d[84]), "+f"(d[85]), "+f"(d[86]), "+f"(d[87]),
          "+f"(d[88]), "+f"(d[89]), "+f"(d[90]), "+f"(d[91]), "+f"(d[92]), "+f"(d[93]), "+f"(d[94]), "+f"(d[95]),
          "+f"(d[96]), "+f"(d[97]), "+f"(d[98]), "+f"(d[99]), "+f"(d[100]), "+f"(d[101]), "+f"(d[102]), "+f"(d[103]),
          "+f"(d[104]), "+f"(d[105]), "+f"(d[106]), "+f"(d[107]), "+f"(d[108]), "+f"(d[109]), "+f"(d[110]), "+f"(d[111]),
          "+f"(d[112]), "+f"(d[113]), "+f"(d[114]), "+f"(d[115]), "+f"(d[116]), "+f"(d[117]), "+f"(d[118]), "+f"(d[119]),
          "+f"(d[120]), "+f"(d[121]), "+f"(d[122]), "+f"(d[123]), "+f"(d[124]), "+f"(d[125]), "+f"(d[126]), "+f"(d[127])
        : "l"(da), "l"(db), "n"(TA), "n"(TB), "r"(keep));
}
template <int TA, int TB>
__device__ __forceinline__ void wgmma_n192(float (&d)[128], uint64_t da, uint64_t db, int keep) {
    asm volatile(
        "{\n.reg .pred p;\nsetp.ne.b32 p, %100, 0;\n"
        "wgmma.mma_async.sync.aligned.m64n192k16.f32.bf16.bf16 "
        "{%0, %1, %2, %3, %4, %5, %6, %7, %8, %9, %10, %11, %12, %13, %14, %15, "
        "%16, %17, %18, %19, %20, %21, %22, %23, %24, %25, %26, %27, %28, %29, %30, %31, "
        "%32, %33, %34, %35, %36, %37, %38, %39, %40, %41, %42, %43, %44, %45, %46, %47, "
        "%48, %49, %50, %51, %52, %53, %54, %55, %56, %57, %58, %59, %60, %61, %62, %63, "
        "%64, %65, %66, %67, %68, %69, %70, %71, %72, %73, %74, %75, %76, %77, %78, %79, "
        "%80, %81, %82, %83, %84, %85, %86, %87, %88, %89, %90, %91, %92, %93, %94, %95}, "
        "%96, %97, p, 1, 1, %98, %99;\n}\n"
        : "+f"(d[0]), "+f"(d[1]), "+f"(d[2]), "+f"(d[3]), "+f"(d[4]), "+f"(d[5]), "+f"(d[6]), "+f"(d[7]),
          "+f"(d[8]), "+f"(d[9]), "+f"(d[10]), "+f"(d[11]), "+f"(d[12]), "+f"(d[13]), "+f"(d[14]), "+f"(d[15]),
          "+f"(d[16]), "+f"(d[17]), "+f"(d[18]), "+f"(d[19]), "+f"(d[20]), "+f"(d[21]), "+f"(d[22]), "+f"(d[23]),
          "+f"(d[24]), "+f"(d[25]), "+f"(d[26]), "+f"(d[27]), "+f"(d[28]), "+f"(d[29]), "+f"(d[30]), "+f"(d[31]),
          "+f"(d[32]), "+f"(d[33]), "+f"(d[34]), "+f"(d[35]), "+f"(d[36]), "+f"(d[37]), "+f"(d[38]), "+f"(d[39]),
          "+f"(d[40]), "+f"(d[41]), "+f"(d[42]), "+f"(d[43]), "+f"(d[44]), "+f"(d[45]), "+f"(d[46]), "+f"(d[47]),
          "+f"(d[48]), "+f"(d[49]), "+f"(d[50]), "+f"(d[51]), "+f"(d[52]), "+f"(d[53]), "+f"(d[54]), "+f"(d[55]),
          "+f"(d[56]), "+f"(d[57]), "+f"(d[58]), "+f"(d[59]), "+f"(d[60]), "+f"(d[61]), "+f"(d[62]), "+f"(d[63]),
          "+f"(d[64]), "+f"(d[65]), "+f"(d[66]), "+f"(d[67]), "+f"(d[68]), "+f"(d[69]), "+f"(d[70]), "+f"(d[71]),
          "+f"(d[72]), "+f"(d[73]), "+f"(d[74]), "+f"(d[75]), "+f"(d[76]), "+f"(d[77]), "+f"(d[78]), "+f"(d[79]),
          "+f"(d[80]), "+f"(d[81]), "+f"(d[82]), "+f"(d[83]), "+f"(d[84]), "+f"(d[85]), "+f"(d[86]), "+f"(d[87]),
          "+f"(d[88]), "+f"(d[89]), "+f"(d[90]), "+f"(d[91]), "+f"(d[92]), "+f"(d[93]), "+f"(d[94]), "+f"(d[95])
        : "l"(da), "l"(db), "n"(TA), "n"(TB), "r"(keep));
}
template <int TA, int TB>
__device__ __forceinline__ void wgmma_n128(float (&d)[128], uint64_t da, uint64_t db, int keep) {
    asm volatile(
        "{\n.reg .pred p;\nsetp.ne.b32 p, %68, 0;\n"
        "wgmma.mma_async.sync.aligned.m64n128k16.f32.bf16.bf16 "
        "{%0, %1, %2, %3, %4, %5, %6, %7, %8, %9, %10, %11, %12, %13, %14, %15, "
        "%16, %17, %18, %19, %20, %21, %22, %23, %24, %25, %26, %27, %28, %29, %30, %31, "
        "%32, %33, %34, %35, %36, %37, %38, %39, %40, %41, %42, %43, %44, %45, %46, %47, "
        "%48, %49, %50, %51, %52, %53, %54, %55, %56, %57, %58, %59, %60, %61, %62, %63}, "
        "%64, %65, p, 1, 1, %66, %67;\n}\n"
        : "+f"(d[0]), "+f"(d[1]), "+f"(d[2]), "+f"(d[3]), "+f"(d[4]), "+f"(d[5]), "+f"(d[6]), "+f"(d[7]),
          "+f"(d[8]), "+f"(d[9]), "+f"(d[10]), "+f"(d[11]), "+f"(d[12]), "+f"(d[13]), "+f"(d[14]), "+f"(d[15]),
          "+f"(d[16]), "+f"(d[17]), "+f"(d[18]), "+f"(d[19]), "+f"(d[20]), "+f"(d[21]), "+f"(d[22]), "+f"(d[23]),
          "+f"(d[24]), "+f"(d[25]), "+f"(d[26]), "+f"(d[27]), "+f"(d[28]), "+f"(d[29]), "+f"(d[30]), "+f"(d[31]),
          "+f"(d[32]), "+f"(d[33]), "+f"(d[34]), "+f"(d[35]), "+f"(d[36]), "+f"(d[37]), "+f"(d[38]), "+f"(d[39]),
          "+f"(d[40]), "+f"(d[41]), "+f"(d[42]), "+f"(d[43]), "+f"(d[44]), "+f"(d[45]), "+f"(d[46]), "+f"(d[47]),
          "+f"(d[48]), "+f"(d[49]), "+f"(d[50]), "+f"(d[51]), "+f"(d[52]), "+f"(d[53]), "+f"(d[54]), "+f"(d[55]),
          "+f"(d[56]), "+f"(d[57]), "+f"(d[58]), "+f"(d[59]), "+f"(d[60]), "+f"(d[61]), "+f"(d[62]), "+f"(d[63])
        : "l"(da), "l"(db), "n"(TA), "n"(TB), "r"(keep));
}
__device__ __forceinline__ void wgmma_n128_rs(float (&d)[128], uint32_t a0, uint32_t a1, uint32_t a2, uint32_t a3, uint64_t db) {
    asm volatile(
        "{\n.reg .pred p;\nsetp.ne.b32 p, 1, 0;\n"
        "wgmma.mma_async.sync.aligned.m64n128k16.f32.bf16.bf16 "
        "{%0, %1, %2, %3, %4, %5, %6, %7, %8, %9, %10, %11, %12, %13, %14, %15, "
        "%16, %17, %18, %19, %20, %21, %22, %23, %24, %25, %26, %27, %28, %29, %30, %31, "
        "%32, %33, %34, %35, %36, %37, %38, %39, %40, %41, %42, %43, %44, %45, %46, %47, "
        "%48, %49, %50, %51, %52, %53, %54, %55, %56, %57, %58, %59, %60, %61, %62, %63}, "
        "{%64, %65, %66, %67}, %68, p, 1, 1, 1;\n}\n"
        : "+f"(d[0]), "+f"(d[1]), "+f"(d[2]), "+f"(d[3]), "+f"(d[4]), "+f"(d[5]), "+f"(d[6]), "+f"(d[7]),
          "+f"(d[8]), "+f"(d[9]), "+f"(d[10]), "+f"(d[11]), "+f"(d[12]), "+f"(d[13]), "+f"(d[14]), "+f"(d[15]),
          "+f"(d[16]), "+f"(d[17]), "+f"(d[18]), "+f"(d[19]), "+f"(d[20]), "+f"(d[21]), "+f"(d[22]), "+f"(d[23]),
          "+f"(d[24]), "+f"(d[25]), "+f"(d[26]), "+f"(d[27]), "+f"(d[28]), "+f"(d[29]), "+f"(d[30]), "+f"(d[31]),
          "+f"(d[32]), "+f"(d[33]), "+f"(d[34]), "+f"(d[35]), "+f"(d[36]), "+f"(d[37]), "+f"(d[38]), "+f"(d[39]),
          "+f"(d[40]), "+f"(d[41]), "+f"(d[42]), "+f"(d[43]), "+f"(d[44]), "+f"(d[45]), "+f"(d[46]), "+f"(d[47]),
          "+f"(d[48]), "+f"(d[49]), "+f"(d[50]), "+f"(d[51]), "+f"(d[52]), "+f"(d[53]), "+f"(d[54]), "+f"(d[55]),
          "+f"(d[56]), "+f"(d[57]), "+f"(d[58]), "+f"(d[59]), "+f"(d[60]), "+f"(d[61]), "+f"(d[62]), "+f"(d[63])
        : "r"(a0), "r"(a1), "r"(a2), "r"(a3), "l"(db));
}

constexpr uint64_t kDescHi = (uint64_t)(64u | 0x40000000u) << 32;
template <int MODE>
__device__ __forceinline__ void mma_kblock(float (&acc)[128], uint32_t a_lo, uint32_t b_lo, int keep) {
    constexpr uint32_t HALF = (MODE == 1) ? 12288u : 16384u;
    constexpr bool BN = (MODE == 1 || MODE == 2 || MODE == 4);
#pragma unroll
    for (int kk = 0; kk < 4; ++kk) {
        const uint32_t ao = (MODE == 3) ? kk * 2048u : kk * 32u;
        const uint32_t bo = BN ? ((kk >> 1) * HALF + (kk & 1) * 2048u) : kk * 32u;
        const uint64_t da = kDescHi | (uint64_t)(a_lo + (ao >> 4) + (1u << 16));
        const uint64_t db = kDescHi | (uint64_t)(b_lo + (bo >> 4) + (BN ? (256u << 16) : (1u << 16)));
        if (MODE == 1) wgmma_n192<0, 1>(acc, da, db, kk == 0 ? keep : 1);
        else if (MODE == 4) wgmma_n128<0, 1>(acc, da, db, 1);
        else wgmma_n256<(MODE == 3), BN>(acc, da, db, kk == 0 ? keep : 1);
    }
}

struct Params {
    Scratch* s;
    const __nv_bfloat16* x;
    const __nv_bfloat16* b_re;
    const __nv_bfloat16* b_im;
    const __nv_bfloat16* gate_w;
    const __nv_bfloat16* lam_re;
    const __nv_bfloat16* lam_im;
    const __nv_bfloat16* log_dt;
    const __nv_bfloat16* dskip;
    const __nv_bfloat16* b1;
    const __nv_bfloat16* b2;
    float* out;
    int swap;
};

#define CMUL(rr, ri, ar, ai, br, bi) do { float _r = (ar) * (br) - (ai) * (bi); float _i = (ar) * (bi) + (ai) * (br); rr = _r; ri = _i; } while (0)
#define CFMA(rr, ri, ar, ai, br, bi) do { float _r = fmaf(-(ai), (bi), fmaf((ar), (br), rr)); float _i = fmaf((ai), (br), fmaf((ar), (bi), ri)); rr = _r; ri = _i; } while (0)

#define KB_OPEN(IT, LAST)                                                                        \
    KT(IT, 0);                                                                                   \
    if (ORDER && (LAST) && wg == 1) bar_sync(7, 256);                                            \
    mbar_wait(bar_full + 8 * ((IT) & 3), ((IT) >> 2) & 1);                                \
    KT(IT, 1);
#define KB_CLOSE(IT, LAST, REL)                                                                  \
    if (ORDER && (LAST) && wg == 0) bar_arrive(7, 256);                                          \
    wgmma_wait<1>();                                                                             \
    if (lane < 2 && (REL)) mbar_arrive_cluster(rel_addr + 8 * (((IT) - 1) & 3));
#define KBLOCK(MODE, IT, FIRST, LAST)                                                            \
    {                                                                                            \
        const uint32_t so = ((IT) & 3) * (kStageBytes >> 4);                                     \
        KB_OPEN(IT, LAST);                                                                       \
        wgmma_fence();                                                                           \
        mma_kblock<MODE>(acc, a_lo + so, b_lo + so, !(FIRST));                                   \
        wgmma_commit();                                                                          \
        KB_CLOSE(IT, LAST, !(FIRST));                                                            \
    }
#define TILE_END() do { wgmma_wait<0>(); if (lane < 2) mbar_arrive_cluster(rel_addr + 24); } while (0)

__global__ void __cluster_dims__(2, 1, 1) __launch_bounds__(384, 1)
fused_kernel(const __grid_constant__ CUtensorMap mB, const __grid_constant__ CUtensorMap mXs, const __grid_constant__ CUtensorMap mXf,
             const __grid_constant__ CUtensorMap mW1b, const __grid_constant__ CUtensorMap mW1a, const __grid_constant__ CUtensorMap mHs,
             const __grid_constant__ CUtensorMap mHf, const __grid_constant__ CUtensorMap mCre, const __grid_constant__ CUtensorMap mCim,
             const __grid_constant__ CUtensorMap mW2, const __grid_constant__ CUtensorMap mW2n, const Params p) {
    extern __shared__ __align__(1024) uint8_t smem_raw[];
    if (PFTOP) { prefetch_map(&mB); prefetch_map(&mXs); }
    const uint32_t sbase = smem_u32(smem_raw);
    if ((sbase & 0x3ffffu) != kSmemOrg) return;
    const uint32_t bar_full = sbase + kBarOff, bar_empty = bar_full + 32, bar_dep = bar_full + 64;
    const uint32_t bar_x = bar_full + 88, bar_c = bar_full + 96, role_s = bar_full + 104, bar_role = bar_full + 120, bar_e = bar_full + 128, tag_s = bar_full + 112 + (threadIdx.x & 1) * 4;

    const int tid = threadIdx.x, lane = tid & 31;
    const int warp = __shfl_sync(0xffffffffu, tid >> 5, 0);
    const uint32_t rank = blockIdx.x & 1;

    int pref;
    {
        unsigned smid;
        asm("mov.u32 %0, %%smid;" : "=r"(smid));
        const int t = smid >> 1, u = t - 32, d = (u * 37) >> 8;
        pref = (t < 32) ? (t & 7) * 8 + (t >> 3) : (t < 60) ? (1 + u - 7 * d) * 8 + 4 + d : ((t - 58) & 7);
    }
    STAMP(tid == 0, 0);
    int role = pref;
#define ROLE_VARS()                                                                                               \
    const int c = role >> 3;                                                             \
    const int j8 = role & 7;                                                        \
    const int cb = j8 * 2 + (int)rank;                                             \
    const int rb = 2 * c + (int)rank;                                               \
    const int kh = j8 >> 2;                 \
    const int colK = (j8 & 3) * 256 + kh * 128, colS = colK ^ 128;    \
    (void)cb; (void)rb; (void)colS;

#define INIT_ALL()                                                                                    \
    if (warp == INITW && elect_one()) {                                                               \
        if (!PFTOP) { prefetch_map(&mB); prefetch_map(&mXs); }                                        \
        _Pragma("unroll") for (int s = 0; s < kStages; ++s) {                                         \
            mbar_init(bar_full + 8 * s, 1);                                                           \
            mbar_init(bar_empty + 8 * s, 16);                                                         \
            mbar_init(bar_dep + 8 * s, 1);                                \
        }                                                                                             \
        mbar_init(bar_c, 96);                                                                         \
        mbar_init(bar_role, 1);                                                                       \
        mbar_init(bar_e, 32);                                                                         \
        asm volatile("fence.mbarrier_init.release.cluster;\nfence.proxy.async.shared::cta;" ::: "memory"); \
        mbar_expect_tx(bar_full, 49152);            \
        tma4(sbase, &mB, bar_full, 0, 0, 0, ((pref & 7) * 2 + (int)rank) * 8);                        \
        if (!MC0) {                                                                                   \
        tma5(sbase + kABytes, &mXs, bar_full, 0, 0, 0, 0, pref >> 3);                                 \
        tma5(sbase + kABytes + 16384, &mXs, bar_full, 0, 0, 0, 16, pref >> 3);                        \
        }                                                                                             \
        mbar_expect_tx(bar_x, 2048);                                                                  \
        bulk_load(sbase + kXOff, p.gate_w, 2048, bar_x);                                              \
        mbar_expect_tx(bar_role, 8);                                                                  \
    }
    if (PRODCOND) {
        asm volatile("setmaxnreg.dec.sync.aligned.u32 24;");
        unsigned taken = 0;
        if (tid == 352 && rank == 0) {
            taken = atom_exch(&p.s->claim[pref], 1u);
        }
        __syncwarp();
        cluster_arrive();
        cluster_wait();
        if (warp > 8) {
            if (tid == 352) {
#pragma unroll 1
                for (int i = 0; taken != 0 && i < 64; ++i) { role = i + 256; taken = atom_exch(&p.s->claim[i], 1u); }
                st_async32(mapa(role_s + 4 * rank, 0), role, mapa(bar_role, 0));
                st_async32(mapa(role_s + 4 * rank, 1), role, mapa(bar_role, 1));
            }
            __syncwarp();
            mbar_wait(bar_role, 0);
            role = __shfl_sync(0xffffffffu, (int)lds32(role_s), 0) & 63;
            ROLE_VARS();
            if (warp == 11) {
                if (lane < 9) prefetch_map(&mXf + lane);
#pragma unroll 1
                for (int en = lane; en < 56; en += 32) {
                    const int J = en >> 2;
                    const __nv_bfloat16* src = p.b1 + 32 * J + 2 * (en & 3) + ((J < 6) ? 2048 + 192 * j8 : 256 * j8 - 192);
                    sts128(sbase + kBiasOff + en * 16, ldg32(src), ldg32(src + 8), ldg32(src + 16), ldg32(src + 24));
                }
                mbar_arrive_local(bar_c);
                const uint4 dq = ldg128(p.dskip + colK + (lane & 15) * 8), bq = ldg128(p.b2 + colK + (lane & 15) * 8);
                mbar_wait(bar_x, 0);
                mbar_wait(bar_x, 1);
#pragma unroll 1
                for (int i = lane >> 4; i < 128; i += 2) {
                    const uint32_t xa_s = sbase + kXOff + (lane & 8) * 2048 + i * 128 + (((lane ^ i) & 7) << 4);
                    const uint4 xq = lds128(xa_s);
                    const float g = bf_lo(lds16(sbase + kGateOff + (((i >> 3) & 3) * 72 + 8 * (4 * rank + (i >> 5)) + (i & 7)) * 2));
                    const float om = bf16_round(1.0f - g);
                    uint32_t z = i >> 7;
                    PIN_R(z);
                    const uint32_t dv[4] = {dq.x, dq.y, dq.z, dq.w}, bv[4] = {bq.x, bq.y, bq.z, bq.w};
                    uint32_t xv[4] = {xq.x, xq.y, xq.z, xq.w};
#pragma unroll
                    for (int k = 0; k < 4; ++k) {
                        const uint32_t xd = bf2_mul(xv[k], dv[k]);
                        xv[k] = pack_bf16(fmaf(g, bf_lo(xd), om * __uint_as_float(__byte_perm(bv[k], z, 0x1044))),
                                          fmaf(g, bf_hi(xd), om * __uint_as_float(__byte_perm(bv[k], z, 0x3244))));
                    }
                    sts128(xa_s, xv[0], xv[1], xv[2], xv[3]);
                }
                mbar_arrive_local(bar_e);
                STAMPA(lane == 0, 10);
            } else {
                {
                    sts32(tag_s, ld_relaxed32(&p.s->epoch) + 1);
                    const int ch = cb * 64 + (tid - 288);
                    const uint32_t t_s = sbase + kTabOff + (tid - 288) * 64;
                    const float Lr = bf_lo(ldg16(p.lam_re + ch)), Li = bf_lo(ldg16(p.lam_im + ch));
                    const float dt = bf16_round(expf(bf_lo(ldg16(p.log_dt + ch))));
                    const float ea = expf(dt * Lr);
                    float lr, li;
                    sincospif((dt * Li) * 0.31830988618379067f, &li, &lr);
                    lr *= ea; li *= ea;
                    const float nr = lr - 1.0f, ni = li;
                    const bool big = fabsf(Lr) >= fabsf(Li);
                    const float u = big ? Lr : Li, v = big ? Li : Lr;
                    const float t = v / u, d = 2.0f / fmaf(v, t, u);
                    const float cr = (big ? fmaf(ni, t, nr) : fmaf(nr, t, ni)) * d, ci = (big ? fmaf(-nr, t, ni) : fmaf(ni, t, -nr)) * d;
                    if (p.swap) li = -li;
                    const float m00 = p.swap ? -ci : cr, m01 = p.swap ? cr : -ci, m10 = p.swap ? -cr : -ci, m11 = p.swap ? -ci : -cr;
#pragma unroll
                    for (int q = 0; q < 4; ++q) {
                        sts128f(t_s + q * 16, lr, li, m00, m01);
                        sts128f(t_s + 12288 + q * 16, 0.f, 0.f, 0.f, 0.f);
                    }
#pragma unroll 1
                    for (int i = 0; i < 6; ++i) CMUL(lr, li, lr, li, lr, li);
                    float ar, ai, br, bi;
                    CMUL(ar, ai, lr, li, lr, li);
                    CMUL(br, bi, ar, ai, lr, li);
                    sts128f(t_s + 4096, m10, m11, 0.f, 0.f);
#pragma unroll
                    for (int q = 1; q < 4; ++q) sts128f(t_s + 4096 + q * 16, m10, m11, lr, li);
                    sts128f(t_s + 8192, 0.f, 0.f, 1.f, 0.f);
                    sts128f(t_s + 8192 + 16, 0.f, 0.f, lr, li);
                    sts128f(t_s + 8192 + 32, ar, ai, ar, ai);
                    sts128f(t_s + 8192 + 48, ar, ai, br, bi);
                    CMUL(ar, ai, ar, ai, ar, ai);
                    br = 1.f; bi = 0.f;
#pragma unroll 1
                    for (int k = c - 1; k >= 0; --k) {
                        sts64f(t_s + 12288 + (k & 3) * 16 + (k >> 2) * 8, br, bi);
                        CMUL(br, bi, br, bi, ar, ai);
                    }
                    mbar_arrive_local(bar_c);
                }
                if (warp == 9) {
#pragma unroll 1
                    for (int ev = 0; ev < 3; ++ev) {
                        if (ev == CLREV) {
                            uint8_t* box = p.s->X + (size_t)(role * 2 + rank) * kXBytes + lane * 16;
#pragma unroll 1
                            for (int i = 0; i < kXBytes; i += 512) { stg128(box + i, 0, 0, 0, 0); if (CLRNS) __nanosleep(CLRNS); }
                        }
                        bar_sync(3 + ev, 288);
                        if (lane == 0) {
                            unsigned* cnt = &p.s->cnt[(ev == 0 ? c : 16 * ev - 8 + rb) * 32];
                            asm volatile("fence.acq_rel.gpu;\nfence.proxy.async.global;" ::: "memory");
                            asm volatile("red.relaxed.gpu.global.add.u32 [%0], 1;" ::"l"(cnt) : "memory");
                        }
                        __syncwarp();
                    }
                } else if (lane == 0) {
                    const unsigned tag = lds32(tag_s);
#pragma unroll 1
                    for (int ev = 0; ev < 3; ++ev) {
                        wait_counter(&p.s->cnt[(ev == 0 ? c : 16 * ev - 8 + rb) * 32], tag * (ev == 0 ? 16u : 8u));
                        mbar_arrive_local(bar_dep + 8 * ev);
                        if (ev == 0 && atomicInc(&p.s->done, 127u) == 127u) {
                            st_relaxed32(&p.s->epoch, tag);
#pragma unroll 1
                            for (int i = 0; i < 64; i += 4) stg128(&p.s->claim[i], 0, 0, 0, 0);
                        }
                    }
                }
            }
        } else if (elect_one()) {
            int it = 1, again = 15;
            if (MC0) tma5_mc(sbase + kABytes + rank * 16384, &mXs, bar_full, 0, 0, 0, rank * 16, role >> 3);
#define ACQUIRE(BYTES)                                                   \
    const uint32_t st = sbase + (it & 3) * kStageBytes, fb = bar_full + 8 * (it & 3); \
    mbar_wait(bar_empty + 8 * (it & 3), ((it >> 2) & 1) ^ 1);     \
    mbar_expect_tx(fb, BYTES);
#pragma unroll 1
            for (; it < 16; ++it) {
                ACQUIRE(49152);
                tma4(st, &mB, fb, it * 64, 0, 0, ((role & 7) * 2 + (int)rank) * 8);
                tma5_mc(st + kABytes + rank * 16384, &mXs, fb, it * 64, 0, 0, rank * 16, role >> 3);
                if (it == again) {
                    mbar_wait(bar_role, 0);
                    const uint2 fin = lds64(role_s);
                    role = fin.x & 63;
                    if (fin.x != fin.y) { it = -1; again = 16; }
                }
            }
            ROLE_VARS();
#pragma unroll 1
            for (; it < 48; ++it) {
                const bool t1 = it < 32;
                const int k0 = (it & 15) * 64;
                ACQUIRE(t1 ? 40960 : 49152);
                tma5(st, &mXf, fb, k0, 0, 0, rank * 4, c);
                tma3_mc(st + kABytes + rank * (t1 ? 12288 : 16384), t1 ? &mW1b : &mW1a, fb, 0, k0 + rank * 32, t1 ? 32 + 3 * j8 : 4 * j8);
                if ((it & ~2) == XLDKB) {
                    const int h = (it >> 1) & 1;
                    if (h == 0) mbar_expect_tx(bar_x, 32768);
                    tma5(sbase + kXOff + h * 16384, &mXf, bar_x, colK + h * 64, 0, 0, rank * 4, c);
                }
            }
            STAMPA(true, 8);
            mbar_wait(bar_dep, 0);
            asm volatile("fence.proxy.async.global;" ::: "memory");
            STAMPA(true, 9);
#pragma unroll 1
            for (; it < 64; ++it) {
                const int k0 = (it & 15) * 64;
                ACQUIRE(49152);
                tma3(st, &mHs, fb, 0, kh * 1024 + k0, rb * 2);
                tma2_mc(st + kABytes + rank * 16384, kh ? &mCim : &mCre, fb, k0, rank ? colS : colK);
            }
            int f0 = 2048 + 768 * kh;
#pragma unroll 1
            for (; it < kTotal; ++it, f0 += 64) {
                if (it == 64 || it == 76) {
                    mbar_wait(bar_dep + (it == 64 ? 8 : 16), 0);
                    asm volatile("fence.proxy.async.global;" ::: "memory");
                    if (it == 76) f0 = 1024 * kh;
                }
                if (f0 == 256 * j8) f0 += 256;
                if (it == 88) f0 = 256 * (j8 ^ 4);
                ACQUIRE(49152);
                tma2(st, &mHf, fb, f0, rb * 128);
                tma5_mc(st + kABytes + rank * 16384, &mW2, fb, 0, 0, (f0 >> 3) + 4 * rank, 0, colK >> 6);
                if (it < 88) tma5_mc(st + kABytes + rank * 16384 + 8192, &mW2, fb, 0, 0, (f0 >> 3) + 4 * rank, 0, colS >> 6);
                else tma3_mc(st + kABytes + rank * 16384 + 8192, &mW2n, fb, 0, (f0 ^ 1024) + 32 * rank, colK >> 6);
                if ((it >> 3) == PFKB / 8) tma3_pf(&mW2n, 0, 256 * (j8 & 3) + (it & 4) * 256 + (it & 3) * 64 + 32 * rank, colK >> 6);
            }
        }
    } else {
        INIT_ALL();
        if (warp >= 8 - PF0LINES) {
            const int row = blockIdx.x * 32 + lane;
            const __nv_bfloat16* src = (row < 2048) ? p.x : (row < 3072) ? p.b_re - 2048 * kD : p.b_im - 3072 * kD;
            asm volatile("prefetch.global.L2 [%0];" ::"l"(src + row * kD + (7 - warp) * 64) : "memory");
        }
        __syncwarp();
        cluster_arrive();
        asm volatile("setmaxnreg.inc.sync.aligned.u32 240;");
        const int wg = warp >> 2, w = warp & 3, r = lane >> 2, q = lane & 3, tw = tid & 127;
        uint32_t a_lo = (kSmemOrg + wg * 8192) >> 4;
        constexpr uint32_t b_lo = (kSmemOrg + kABytes) >> 4;
        const uint32_t rel_addr = mapa(bar_empty, (uint32_t)(lane & 1));
        const uint32_t gate_s = sbase + kGateOff;
        float acc[128];
        uint32_t pk[64];
        unsigned tag;
        UNDEF_R(tag);

#pragma unroll
        for (int i = 0; i < 128; ++i) UNDEF_F(acc[i]);
        float gs = 0.f;
        {
            const uint32_t gx_s = sbase + kABytes + (16 * rank + 2 * warp + (lane >> 4)) * 128 +
                                  ((((lane & 15) >> 1) ^ (2 * w + (lane >> 4))) << 4) + (lane & 1) * 8;
            const uint32_t gw_s = sbase + kXOff + (lane & 15) * 8;
            uint32_t again = 15;
            cluster_wait();
#pragma unroll 1
            for (uint32_t it = 0; it < 16; ++it) {
                const uint32_t so = (it & 3) * (kStageBytes >> 4);
                KB_OPEN(it, it == 15);
                wgmma_fence();
                mma_kblock<0>(acc, a_lo + so, b_lo + so, it != 0);
                wgmma_commit();
                KB_CLOSE(it, it == 15, it + again != 15);
                STAMPA(tid == 0 && it == 0, 1);
                mbar_wait(bar_x, 0);
                const uint2 xa = lds64(gx_s + (role & 7) * 4096 + (it & 3) * kStageBytes), wa = lds64(gw_s + it * 128);
                const uint32_t pa = bf2_mul(xa.x, wa.x), pb = bf2_mul(xa.y, wa.y);
                gs += (bf_lo(pa) + bf_hi(pa)) + (bf_lo(pb) + bf_hi(pb));
                if (it == again) {
                    mbar_wait(bar_c, 0);
                    const uint2 fin = lds64(role_s);
                    role = fin.x & 63;
                    if (__shfl_sync(0xffffffffu, fin.x != fin.y, 0)) { it = -1; again = 16; gs = 0.f; }
                }
            }
        }
        role = __shfl_sync(0xffffffffu, role, 0);
        ROLE_VARS();
        {
            tag = lds32(tag_s);
#pragma unroll
            for (int o = 8; o > 0; o >>= 1) gs += __shfl_xor_sync(0xffffffffu, gs, o);
            const float g = bf16_round(__frcp_rn(1.0f + expf(-bf16_round(gs))));
            if ((lane & 15) == 0) st_relaxed64(&p.s->gate[c * 256 + (lane >> 4) + 64 * w + 4 * cb + 2 * wg], __float_as_uint(g), tag);
        }
        const uint32_t tab_s = sbase + kTabOff + tid * 16;
        const float4 k0 = lds128f(tab_s);
        TILE_END();
        STAMPA(tid == 0, 2);
#pragma unroll
        for (int s = 0; s < 64; ++s) pk[s] = pack_bf16_v(acc[4 * (s >> 1) + (s & 1)], acc[4 * (s >> 1) + 2 + (s & 1)]);
#pragma unroll
        for (int i = 0; i < 96; ++i) UNDEF_F(acc[i]);

        const float lr = k0.x, li = k0.y, m00 = k0.z, m01 = k0.w;
        float m10, m11, hr = 0.f, hi = 0.f;
        uint32_t gg[4], orr[4], oii[4];
        const int ch = cb * 64 + warp * 8 + r;
        __nv_bfloat16* hs = p.s->Hs + (size_t)ch * 2048 + c * 256 + q * 8;
#define PASS2(KB)                                                                                      \
    _Pragma("unroll") for (int s = 0; s < 64; s += 2) {                                                \
        if (pass2_kb(s) != (KB)) continue;                                                             \
        if ((s & 7) == 0) {                                                                            \
            const uint4 ga = lds128(gate_s + (q * 72 + s) * 2);                                        \
            gg[0] = ga.x; gg[1] = ga.y; gg[2] = ga.z; gg[3] = ga.w;                                    \
        }                                                                                              \
        float o0[2], o1[2];                                                                            \
        _Pragma("unroll") for (int k = 0; k < 2; ++k) {                                                \
            PIN_R(pk[s + k]);                                                                          \
            float nr = bf_lo(pk[s + k]), ni = bf_hi(pk[s + k]);                                        \
            CFMA(nr, ni, lr, li, hr, hi);                                                              \
            hr = nr; hi = ni;                                                                          \
            o0[k] = fmaf(m00, hr, m01 * hi);                                                           \
            o1[k] = fmaf(m10, hr, m11 * hi);                                                           \
        }                                                                                              \
        orr[(s >> 1) & 3] = bf2_mul(pack_bf16(o0[0], o0[1]), gg[(s >> 1) & 3]);                        \
        oii[(s >> 1) & 3] = bf2_mul(pack_bf16(o1[0], o1[1]), gg[(s >> 1) & 3]);                        \
        if ((s & 7) == 6) {                                                                            \
            stg128(hs + 32 * (s >> 3), orr[0], orr[1], orr[2], orr[3]);                                \
            stg128(hs + 1024 * 2048 + 32 * (s >> 3), oii[0], oii[1], oii[2], oii[3]);                  \
        }                                                                                              \
    }                                                                                                  \
    PIN_F(hr); PIN_F(hi);
        {
            uint4 av0, av1, gv;
            float lqr, lqi;
#pragma unroll
            for (int kb = 0; kb < 16; ++kb) {
                PIN_R(a_lo);
                KBLOCK(1, 16 + kb, kb == 0, kb == 15);
                if (kb < 4) {
#pragma unroll
                    for (int s = kb * 16; s < kb * 16 + 16; ++s) {
                        float nr = bf_lo(pk[s]), ni = bf_hi(pk[s]);
                        CFMA(nr, ni, lr, li, hr, hi);
                        hr = nr; hi = ni;
                    }
                    PIN_F(hr); PIN_F(hi);
                }
                if (kb == 2) gv = ld_relaxed2x64(&p.s->gate[c * 256 + 2 * tw]);
                if (kb == 3) {
                    const float4 k1 = lds128f(tab_s + 4096), k2 = lds128f(tab_s + 8192);
                    m10 = k1.x; m11 = k1.y; lqr = k2.z; lqi = k2.w;
                    float tr = __shfl_up_sync(0xffffffffu, hr, 1, 4), ti = __shfl_up_sync(0xffffffffu, hi, 1, 4);
                    if (q >= 1) CFMA(hr, hi, k1.z, k1.w, tr, ti);
                    tr = __shfl_up_sync(0xffffffffu, hr, 2, 4); ti = __shfl_up_sync(0xffffffffu, hi, 2, 4);
                    if (q >= 2) CFMA(hr, hi, k2.x, k2.y, tr, ti);
                    if (q == 3) st_relaxed2x64(&p.s->agg[c * 1024 + ch], __float_as_uint(hr), tag, __float_as_uint(hi), tag);
                    tr = __shfl_up_sync(0xffffffffu, hr, 1, 4); ti = __shfl_up_sync(0xffffffffu, hi, 1, 4);
                    hr = (q >= 1) ? tr : 0.f; hi = (q >= 1) ? ti : 0.f;
                }
                if (kb == 4) {
                    unsigned spins = 0;
                    while (__any_sync(0xffffffffu, gv.y != tag || gv.w != tag)) {
                        if (++spins > kSpinLimit) break;
                        gv = ld_relaxed2x64(&p.s->gate[c * 256 + 2 * tw]);
                    }
                    sts32(gate_s + ((tw >> 5) * 72 + 2 * lane) * 2, __byte_perm(gv.x, gv.z, 0x7632));
                }
                if (kb == 5) {
                    av0 = make_uint4(0, tag, 0, tag); av1 = av0;
                    if (q < c) av0 = ld_relaxed2x64(&p.s->agg[q * 1024 + ch]);
                    if (q + 4 < c) av1 = ld_relaxed2x64(&p.s->agg[(q + 4) * 1024 + ch]);
                    bar_sync(1 + wg, 128);
                }
                if (kb == 6) {
                    const float4 k3 = lds128f(tab_s + 12288);
                    unsigned spins = 0;
                    while (__any_sync(0xffffffffu, av0.y != tag || av0.w != tag || av1.y != tag || av1.w != tag)) {
                        if (++spins > kSpinLimit) break;
                        if (q < c) av0 = ld_relaxed2x64(&p.s->agg[q * 1024 + ch]);
                        if (q + 4 < c) av1 = ld_relaxed2x64(&p.s->agg[(q + 4) * 1024 + ch]);
                    }
                    float vr, vi;
                    CMUL(vr, vi, k3.x, k3.y, __uint_as_float(av0.x), __uint_as_float(av0.z));
                    CFMA(vr, vi, k3.z, k3.w, __uint_as_float(av1.x), __uint_as_float(av1.z));
                    vr += __shfl_xor_sync(0xffffffffu, vr, 1); vi += __shfl_xor_sync(0xffffffffu, vi, 1);
                    vr += __shfl_xor_sync(0xffffffffu, vr, 2); vi += __shfl_xor_sync(0xffffffffu, vi, 2);
                    CFMA(hr, hi, lqr, lqi, vr, vi);
                }
                if (kb >= 6) { PASS2(kb); }
            }
            TILE_END();
        }
        STAMPA(tid == 0, 3);
#pragma unroll
        for (int i = 0; i < 48; ++i) pk[i] = pack_bf16_v(acc[2 * i], acc[2 * i + 1]);
#pragma unroll
        for (int i = 0; i < 128; ++i) UNDEF_F(acc[i]);

        PIN_R(a_lo);
        KBLOCK(2, 32, true, false);
        PASS2(16);
        PIN_R(a_lo);
        KBLOCK(2, 33, false, false);
        PASS2(17);
        bar_arrive(3, 288);
        const uint32_t gate_row = gate_s + ((2 * (w & 1)) * 72 + 8 * (4 * rank + 2 * wg + (w >> 1)) + r) * 2;
        uint32_t om0, om1;
        {
            const float a = 1.0f - bf_lo(lds16(gate_row)), b = 1.0f - bf_lo(lds16(gate_row + 72 * 2));
            om0 = pack_bf16(a, a); om1 = pack_bf16(b, b);
        }
        __nv_bfloat16* hf = p.s->Hf + (size_t)(rb * 128 + wg * 64 + w * 16 + r) * kF + q * 8 + 2048 + 192 * j8;
        uint32_t bias_s = sbase + kBiasOff + q * 16;
#define FFN_SLICE(J)                                                                                   \
    {                                                                                                  \
        const uint4 bv = lds128(bias_s + (J) * 64);                                                    \
        const uint32_t bb[4] = {bv.x, bv.y, bv.z, bv.w};                                               \
        _Pragma("unroll") for (int jj = 0; jj < 4; ++jj) {                                             \
            const uint32_t r0 = bf2_add_relu(pk[8 * (J) + 2 * jj], bb[jj]), r1 = bf2_add_relu(pk[8 * (J) + 2 * jj + 1], bb[jj]); \
            pk[8 * (J) + 2 * jj] = bf2_mul(bf2_mul(r0, r0), om0);                                      \
            pk[8 * (J) + 2 * jj + 1] = bf2_mul(bf2_mul(r1, r1), om1);                                  \
        }                                                                                              \
        stg128(hf + 32 * (J), pk[8 * (J)], pk[8 * (J) + 2], pk[8 * (J) + 4], pk[8 * (J) + 6]);         \
        stg128(hf + 8 * kF + 32 * (J), pk[8 * (J) + 1], pk[8 * (J) + 3], pk[8 * (J) + 5], pk[8 * (J) + 7]); \
    }
        const uint32_t x_s = sbase + kXOff + (wg * 64 + w * 16 + (lane & 15)) * 128 + (((lane >> 4) ^ (lane & 7)) << 4);
        {
            uint32_t j = 0, nsl = SPREAD ? 11 : 6;
#pragma unroll 1
            for (uint32_t it = 34; it < 88; ++it, ++j) {
                const uint32_t so = (it & 3) * (kStageBytes >> 4);
                if (wg == 1 && (it == 86 || (ORDER && it == 47))) bar_sync(7, 256);
                KB_OPEN(it, false);
                if ((it & ~15u) == 48) {
                    wgmma_fence();
                    mma_kblock<3>(acc, a_lo + so, b_lo + so, it != 48);
                    wgmma_commit();
                } else {
                    wgmma_fence();
                    mma_kblock<2>(acc, a_lo + so, b_lo + so, 1);
                    wgmma_commit();
                }
                if (wg == 0 && (it == 87 || (ORDER && it == 47))) bar_arrive(7, 256);
                KB_CLOSE(it, false, it != 48);
                if (j < nsl) {
                    if (SPREAD && (j & 1)) continue;
                    if (j & (4 << SPREAD)) {
                        if (j & (2 << SPREAD)) { if (j & (1 << SPREAD)) FFN_SLICE(7) else FFN_SLICE(6) } else { if (j & (1 << SPREAD)) FFN_SLICE(5) else FFN_SLICE(4) }
                    } else {
                        if (j & (2 << SPREAD)) { if (j & (1 << SPREAD)) FFN_SLICE(3) else FFN_SLICE(2) } else { if (j & (1 << SPREAD)) FFN_SLICE(1) else FFN_SLICE(0) }
                    }
                    if (j + 1 == nsl) bar_arrive(SPREAD ? 2 + (nsl >> 2) : 1 + (nsl >> 1), 288);
                } else if (it == 47) {
                    hf += 64 * j8 - 2048;
                    bias_s += 6 * 64;
                    j = -1; nsl = SPREAD ? 15 : 8;
                    TILE_END();
                    STAMPA(tid == 0, 4);
#pragma unroll
                    for (int i = 0; i < 64; ++i) pk[i] = pack_bf16_v(acc[2 * i], acc[2 * i + 1]);
                } else if (it == 84) {
                    mbar_wait(bar_e, 0);
                }
            }
        }
#define TAIL_MMA(T)                                                                                    \
    {                                                                                                  \
        PIN_R(a_lo);                                                                                   \
        wgmma_fence();                                                                                 \
        mma_kblock<4>(acc, a_lo + (T) * (kStageBytes >> 4), b_lo + (T) * (kStageBytes >> 4), 1);       \
        _Pragma("unroll") for (int kk = 0; kk < 4; ++kk)                                               \
            wgmma_n128_rs(acc, pk[16 * (T) + 4 * kk], pk[16 * (T) + 4 * kk + 1], pk[16 * (T) + 4 * kk + 2], pk[16 * (T) + 4 * kk + 3], \
                          kDescHi | (uint64_t)(b_lo + (((T) * kStageBytes + 8192 + (kk >> 1) * 16384 + (kk & 1) * 2048) >> 4) + (256u << 16))); \
        wgmma_commit();                                                                                \
    }
        TILE_END();
        sched_fence(a_lo);
        {
            const uint8_t* xi = p.s->X + (size_t)(role * 2 + rank) * kXBytes + tid * 16;
            uint8_t* xo = const_cast<uint8_t*>(xi) + (kh ? -8 * kXBytes : 8 * kXBytes);
            uint4 rx[8], ev[8];
            uint32_t rs;
#define RXLOAD()                                                                                       \
    {                                                                                                  \
        rs = ld_relaxed32((const unsigned*)(xi + 32768 - tid * 12));                                   \
        _Pragma("unroll") for (int u = 0; u < 8; ++u) rx[u] = ld_relaxed2x64(xi + u * 4096);           \
    }
            {
                STAMP(tid == 0, 15); STAMPB(tid == 128, 1);
                float m[4] = {0.f, 0.f, 0.f, 0.f};
#pragma unroll
                for (int i = 64; i < 128; ++i) m[i & 3] = fmaxf(m[i & 3], fabsf(acc[i]));
                const uint32_t eb = max(__float_as_uint(fmaxf(fmaxf(m[0], m[1]), fmaxf(m[2], m[3]))) >> 23, 15u);
                const float xsc = __uint_as_float((268u - eb) << 23);
                st_relaxed32(xo + 32768 - tid * 12, (eb - 14u) << 23);
#pragma unroll
                for (int u = 0; u < 8; ++u) {
                    const int v = 64 + 8 * u;
                    st_relaxed2x64(xo + u * 4096, pack_f16(acc[v] * xsc, acc[v + 1] * xsc) | 1, pack_f16(acc[v + 2] * xsc, acc[v + 3] * xsc),
                                   pack_f16(acc[v + 4] * xsc, acc[v + 5] * xsc) | 1, pack_f16(acc[v + 6] * xsc, acc[v + 7] * xsc));
                }
                STAMP(tid == 0, 12); STAMPB(tid == 128, 2);
            }
            mbar_wait(bar_full, 0);
            TAIL_MMA(0);
            mbar_wait(bar_full + 8, 0);
            TAIL_MMA(1);
            if (wg == 1) bar_arrive(8, 256);
#pragma unroll
            for (int u = 0; u < 8; ++u) ev[u] = ldsm4((x_s ^ ((u & 3) << 5)) + (u >> 2) * 16384);
            if (wg == 1) mbar_wait(bar_full + 24, 0);
            bar_sync(8 + wg, 256);
            STAMPB(tid == 0, 9);
            RXLOAD();
            mbar_wait(bar_full + 16, 0);
            STAMPB(tid == 0, 10);
            STAMPB(tid == 128, 3);
            TAIL_MMA(2);
            if (wg == 0) mbar_wait(bar_full + 24, 0);
            STAMPB(tid == 0, 11);
            TAIL_MMA(3);
            if (wg == 0) bar_arrive(9, 256);
            sched_fence(a_lo);
            unsigned spins = 0;
#pragma unroll 1
            while (true) {
                uint32_t ok = rs != 0;
#pragma unroll
                for (int u = 0; u < 8; ++u) ok &= rx[u].x & rx[u].z;
                if (__all_sync(0xffffffffu, ok) || ++spins > kSpinLimit) break;
                RXLOAD();
                RESPIN();
            }
            STAMP(tid == 0, 13);
            const float xsc = __uint_as_float(rs);
#pragma unroll
            for (int u = 0; u < 8; ++u) {
                const uint32_t rr[4] = {rx[u].x, rx[u].y, rx[u].z, rx[u].w}, ee[4] = {ev[u].x, ev[u].y, ev[u].z, ev[u].w};
#pragma unroll
                for (int k = 0; k < 4; ++k) {
                    const int v = 64 + 8 * u + 2 * k;
                    const float2 f = __half22float2(*reinterpret_cast<const __half2*>(&rr[k]));
                    acc[v] = fmaf(f.x, xsc, bf_lo(ee[k])); acc[v + 1] = fmaf(f.y, xsc, bf_hi(ee[k]));
                    PIN_F(acc[v]); PIN_F(acc[v + 1]);
                }
            }
            sched_fence(a_lo);
            STAMP(tid == 0, 14);
        }
        wgmma_wait<0>();
        STAMP(tid == 0, 6); STAMPB(tid == 128, 4);
        {
            const bool odd = q & 1;
            const int tb = c * 256 + 128 * (w & 1) + 8 * (4 * rank + 2 * wg + (w >> 1));
            float* o0 = p.out + (size_t)(tb + r) * kD + colK + (odd ? 2 * q + 6 : 2 * q);
#pragma unroll
            for (int i = 0; i < 16; i += 2) {
#pragma unroll
                for (int h = 0; h < 2; ++h) {
                    const int va = 4 * i + 2 * h, vb = va + 4;
                    PIN_F(acc[va]); PIN_F(acc[va + 1]); PIN_F(acc[vb]); PIN_F(acc[vb + 1]);
                    const float a0 = acc[va] + acc[64 + va], a1 = acc[va + 1] + acc[65 + va];
                    const float b0 = acc[vb] + acc[64 + vb], b1 = acc[vb + 1] + acc[65 + vb];
                    const float t0 = __shfl_xor_sync(0xffffffffu, odd ? a0 : b0, 1), t1 = __shfl_xor_sync(0xffffffffu, odd ? a1 : b1, 1);
                    stg128f(o0 + h * 64 * kD + 8 * i, odd ? t0 : a0, odd ? t1 : a1, odd ? b0 : t0, odd ? b1 : t1);
                }
            }
        }
        STAMP(tid == 0, 7);
        STAMP(tid == 128, 5);
    }
}

typedef CUresult (*EncodeFn)(CUtensorMap*, CUtensorMapDataType, cuuint32_t, void*, const cuuint64_t*, const cuuint64_t*,
                             const cuuint32_t*, const cuuint32_t*, CUtensorMapInterleave, CUtensorMapSwizzle,
                             CUtensorMapL2promotion, CUtensorMapFloatOOBfill);

bool encode(EncodeFn fn, CUtensorMap* m, const void* base, int rank, const cuuint64_t* dims, const cuuint64_t* strides,
            const cuuint32_t* box) {
    cuuint32_t es[5] = {1, 1, 1, 1, 1};
    return fn(m, CU_TENSOR_MAP_DATA_TYPE_BFLOAT16, rank, const_cast<void*>(base), dims, strides, box, es,
              CU_TENSOR_MAP_INTERLEAVE_NONE, CU_TENSOR_MAP_SWIZZLE_128B, CU_TENSOR_MAP_L2_PROMOTION_L2_256B,
              CU_TENSOR_MAP_FLOAT_OOB_FILL_NONE) == CUDA_SUCCESS;
}

}

extern "C" void kernel_launch(void* const* d_in, const int* in_sizes, int n_in, void* d_out, int out_size) {
    (void)in_sizes; (void)n_in; (void)out_size;
    typedef const __nv_bfloat16* bp;
    bp x = (bp)d_in[0], lam_re = (bp)d_in[1], lam_im = (bp)d_in[2], B_re = (bp)d_in[3], B_im = (bp)d_in[4];
    bp C_re = (bp)d_in[5], C_im = (bp)d_in[6], log_dt = (bp)d_in[7], dskip = (bp)d_in[8];
    bp w1 = (bp)d_in[10], b1 = (bp)d_in[11], w2 = (bp)d_in[12], b2 = (bp)d_in[13], gate_w = (bp)d_in[14];

    static EncodeFn fn = nullptr;
    static Scratch* ps = nullptr;
    if (!fn) {
        void* f = nullptr;
        cudaDriverEntryPointQueryResult qr;
        cudaGetDriverEntryPoint("cuTensorMapEncodeTiled", &f, cudaEnableDefault, &qr);
        fn = (EncodeFn)f;
        cudaGetSymbolAddress((void**)&ps, g_s);
        cudaFuncSetAttribute(fused_kernel, cudaFuncAttributeMaxDynamicSharedMemorySize, kSmemBytes);
    }
    cudaStream_t stream = cudaStreamPerThread;

    Params p;
    p.x = x; p.lam_re = lam_re; p.lam_im = lam_im; p.log_dt = log_dt; p.dskip = dskip; p.b1 = b1; p.b2 = b2;
    p.gate_w = gate_w; p.b_re = B_re; p.b_im = B_im; p.out = (float*)d_out; p.s = ps;
    char* const pHs = (char*)ps + offsetof(Scratch, Hs);
    char* const pHf = (char*)ps + offsetof(Scratch, Hf);
    char* const pBc = (char*)ps + offsetof(Scratch, Bcopy);

    const char* lo = (const char*)B_re; const char* hi = (const char*)B_im;
    p.swap = 0;
    if (hi < lo) { const char* t = lo; lo = hi; hi = t; p.swap = 1; }
    unsigned long long diff = (unsigned long long)(hi - lo);
    if (diff >= (1ull << 40) || (diff & 15) || diff == 0) {
        cudaMemcpyAsync(pBc, B_re, 2u << 20, cudaMemcpyDeviceToDevice, stream);
        cudaMemcpyAsync((char*)pBc + (2u << 20), B_im, 2u << 20, cudaMemcpyDeviceToDevice, stream);
        lo = (const char*)pBc; diff = 2u << 20; p.swap = 0;
    }

    CUtensorMap mB, mXs, mXf, mW1a, mW1b, mHs, mHf, mCre, mCim, mW2, mW2n;
    bool ok = true;
    { cuuint64_t d[4] = {1024, 8, 2, 128}, s[3] = {2048, diff, 16384}; cuuint32_t b[4] = {64, 8, 2, 8};
      ok &= encode(fn, &mB, lo, 4, d, s, b); }
    { cuuint64_t d[5] = {1024, 2, 4, 32, 8}, s[4] = {2048, 64 * 2048, 2 * 2048, 256 * 2048}; cuuint32_t b[5] = {64, 2, 4, 16, 1};
      ok &= encode(fn, &mXs, x, 5, d, s, b); }
    { cuuint64_t d[5] = {1024, 8, 4, 8, 8}, s[4] = {2048, 64 * 2048, 8 * 2048, 256 * 2048}; cuuint32_t b[5] = {64, 8, 4, 4, 1};
      ok &= encode(fn, &mXf, x, 5, d, s, b); }
    { cuuint64_t d[3] = {64, 1024, 56}, s[2] = {7168, 128}; cuuint32_t ba[3] = {64, 32, 4}, bb[3] = {64, 32, 3};
      ok &= encode(fn, &mW1a, w1, 3, d, s, ba); ok &= encode(fn, &mW1b, w1, 3, d, s, bb); }
    { cuuint64_t d[3] = {64, 2048, 32}, s[2] = {4096, 128}; cuuint32_t b[3] = {64, 64, 2};
      ok &= encode(fn, &mHs, pHs, 3, d, s, b); }
    { cuuint64_t d[2] = {3584, 2048}, s[1] = {7168}; cuuint32_t b[2] = {64, 128};
      ok &= encode(fn, &mHf, pHf, 2, d, s, b); }
    { cuuint64_t d[2] = {1024, 1024}, s[1] = {2048}; cuuint32_t b[2] = {64, 128};
      ok &= encode(fn, &mCre, C_re, 2, d, s, b); ok &= encode(fn, &mCim, C_im, 2, d, s, b); }
    { cuuint64_t d[5] = {64, 2, 448, 4, 16}, s[4] = {2048, 8 * 2048, 2 * 2048, 128}; cuuint32_t b[5] = {64, 2, 4, 4, 2};
      ok &= encode(fn, &mW2, w2, 5, d, s, b); }
    { cuuint64_t d[3] = {64, 3584, 16}, s[2] = {2048, 128}; cuuint32_t b[3] = {64, 32, 2};
      ok &= encode(fn, &mW2n, w2, 3, d, s, b); }
    if (!ok) return;

    fused_kernel<<<128, 384, kSmemBytes, stream>>>(mB, mXs, mXf, mW1b, mW1a, mHs, mHf, mCre, mCim, mW2, mW2n, p);
}
```

```cpp
#include <cuda_runtime.h>
#include <cuda_bf16.h>
#include <cuda_fp16.h>
#include <cuda.h>
#include <stdint.h>
#include <stddef.h>

#define XLDKB 40
#define W64MAIN 0
#define HPFKB 82
#define HPFD 3
#define W1SPLIT 1
#define PF0LINES 1
#define PFKB 80
#define SKEW 2
#define CLREV 0
#define CLRNS 64
#define SPREAD 1
#define BACKOFF 100
#define RXPOS 1
#define MC0 0
#define PFTOP 0
#define INITW 8
#define PRODCOND warp >= 8
#define CP0 1
#define PFL0 0
#define PFN 2
#define INITFIRST 1
#define SPLIT0 1
#define ARVTOP 1
#define NSOLO 1
#define OPAQUE 1
#define HOIST 0
#define EARLYARV 0
#define ORDER 0

namespace {

constexpr int kD = 1024, kF = 3584;
constexpr int kStages = 4;
constexpr int kStageBytes = 49152;
constexpr int kABytes = 16384;
constexpr int kXOff = kStages * kStageBytes;
constexpr int kTabOff = kXOff + 2048;
constexpr int kGateOff = kXOff + 32768;
constexpr int kBiasOff = kGateOff + 4 * 72 * 2;
constexpr int kBarOff = kBiasOff + 56 * 16;
constexpr int kSmemBytes = 232448;
static_assert(kBarOff + 160 <= kSmemBytes, "smem");
constexpr int kXBytes = 33792;
constexpr uint32_t kSmemOrg = 1024;
constexpr unsigned kSpinLimit = 1u << 18;
constexpr int kTotal = 92;

__host__ __device__ constexpr int pass2_kb(int s) {
    return s < 2 ? 6 : s < 8 ? 7 : s < 12 ? 8 : s < 18 ? 9 : s < 22 ? 10 : s < 28 ? 11 : s < 32 ? 12 : s < 38 ? 13 : s < 42 ? 14 : s < 48 ? 15 : s < 56 ? 16 : 17;
}

struct Scratch {
    unsigned claim[64];
    unsigned epoch, pad0[31];
    unsigned done, pad1[31];
    unsigned cnt[56 * 32];
    uint2 gate[2048];
    uint4 agg[8 * 1024];
    __align__(1024) uint8_t X[128 * kXBytes];
    __align__(1024) __nv_bfloat16 Hs[2048 * 2048];
    __align__(1024) __nv_bfloat16 Hf[2048 * 3584];
    __align__(1024) __nv_bfloat16 Bcopy[2 * 1024 * 1024];
};
__device__ Scratch g_s;

#define TRAP() break
#define PIN_F(x) asm volatile("" : "+f"(x))
#define PIN_R(x) asm volatile("" : "+r"(x))
#define UNDEF_F(x) asm volatile("" : "=f"(x))
#define UNDEF_R(x) asm volatile("" : "=r"(x))
#define RESPIN()
__device__ __forceinline__ uint32_t smem_u32(const void* p) { return (uint32_t)__cvta_generic_to_shared(p); }
__device__ __forceinline__ void mbar_init(uint32_t bar, uint32_t count) {
    asm volatile("mbarrier.init.shared::cta.b64 [%0], %1;" ::"r"(bar), "r"(count) : "memory");
}
__device__ __forceinline__ void mbar_expect_tx(uint32_t bar, uint32_t bytes) {
    asm volatile("mbarrier.arrive.expect_tx.shared::cta.b64 _, [%0], %1;" ::"r"(bar), "r"(bytes) : "memory");
}
__device__ __forceinline__ void mbar_wait(uint32_t bar, uint32_t parity) {
    asm volatile(
        "{\n.reg .pred p;\n.reg .u32 n;\n"
        "mbarrier.try_wait.parity.shared::cta.b64 p, [%0], %1;\n"
        "@p bra DONE;\n"
        "mov.u32 n, 0;\n"
        "LOOP:\n"
        "mbarrier.try_wait.parity.shared::cta.b64 p, [%0], %1;\n"
        "@p bra DONE;\n"
        "add.u32 n, n, 1;\n"
        "setp.lt.u32 p, n, %2;\n"
        "@p bra LOOP;\n"
        "DONE:\n}\n"
        ::"r"(bar), "r"(parity), "n"(kSpinLimit) : "memory");
}
__device__ __forceinline__ void sched_fence(uint32_t nonzero) {
    asm volatile("{\n.reg .pred p;\n.reg .u32 n;\nsetp.ne.u32 p, %0, 0;\n@p bra DONE;\nLOOP:\nmov.u32 n, %%clock;\n"
                 "setp.eq.u32 p, n, 0;\n@p bra LOOP;\nDONE:\n}\n" ::"r"(nonzero) : "memory");
}
__device__ __forceinline__ void mbar_arrive_local(uint32_t bar) {
    asm volatile("mbarrier.arrive.shared::cta.b64 _, [%0];" ::"r"(bar) : "memory");
}
__device__ __forceinline__ void mbar_arrive_cluster(uint32_t cluster_addr) {
    asm volatile("mbarrier.arrive.shared::cluster.b64 _, [%0];" ::"r"(cluster_addr) : "memory");
}
__device__ __forceinline__ uint32_t mapa(uint32_t addr, uint32_t rank) {
    uint32_t r;
    asm("mapa.shared::cluster.u32 %0, %1, %2;" : "=r"(r) : "r"(addr), "r"(rank));
    return r;
}
__device__ __forceinline__ void cluster_arrive() { asm volatile("barrier.cluster.arrive.relaxed.aligned;" ::: "memory"); }
__device__ __forceinline__ void cluster_wait() { asm volatile("barrier.cluster.wait.acquire.aligned;" ::: "memory"); }
__device__ __forceinline__ void bar_sync(int id, int n) { asm volatile("bar.sync %0, %1;" ::"r"(id), "r"(n) : "memory"); }
__device__ __forceinline__ void bar_arrive(int id, int n) { asm volatile("bar.arrive %0, %1;" ::"r"(id), "r"(n) : "memory"); }
__device__ __forceinline__ bool elect_one() {
    uint32_t p;
    asm volatile("{\n.reg .pred P;\nelect.sync _|P, 0xffffffff;\nselp.u32 %0, 1, 0, P;\n}\n" : "=r"(p));
    return p != 0;
}

__device__ __forceinline__ void tma2(uint32_t dst, const CUtensorMap* m, uint32_t bar, int c0, int c1) {
    asm volatile("cp.async.bulk.tensor.2d.shared::cluster.global.mbarrier::complete_tx::bytes [%0], [%1, {%3, %4}], [%2];"
                 ::"r"(dst), "l"(m), "r"(bar), "r"(c0), "r"(c1) : "memory");
}
__device__ __forceinline__ void tma3(uint32_t dst, const CUtensorMap* m, uint32_t bar, int c0, int c1, int c2) {
    asm volatile("cp.async.bulk.tensor.3d.shared::cluster.global.mbarrier::complete_tx::bytes [%0], [%1, {%3, %4, %5}], [%2];"
                 ::"r"(dst), "l"(m), "r"(bar), "r"(c0), "r"(c1), "r"(c2) : "memory");
}
__device__ __forceinline__ void tma4(uint32_t dst, const CUtensorMap* m, uint32_t bar, int c0, int c1, int c2, int c3) {
    asm volatile("cp.async.bulk.tensor.4d.shared::cluster.global.mbarrier::complete_tx::bytes [%0], [%1, {%3, %4, %5, %6}], [%2];"
                 ::"r"(dst), "l"(m), "r"(bar), "r"(c0), "r"(c1), "r"(c2), "r"(c3) : "memory");
}
__device__ __forceinline__ void tma5(uint32_t dst, const CUtensorMap* m, uint32_t bar, int c0, int c1, int c2, int c3, int c4) {
    asm volatile("cp.async.bulk.tensor.5d.shared::cluster.global.mbarrier::complete_tx::bytes [%0], [%1, {%3, %4, %5, %6, %7}], [%2];"
                 ::"r"(dst), "l"(m), "r"(bar), "r"(c0), "r"(c1), "r"(c2), "r"(c3), "r"(c4) : "memory");
}
__device__ __forceinline__ void tma2_mc(uint32_t dst, const CUtensorMap* m, uint32_t bar, int c0, int c1) {
    asm volatile("cp.async.bulk.tensor.2d.shared::cluster.global.mbarrier::complete_tx::bytes.multicast::cluster [%0], [%1, {%3, %4}], [%2], %5;"
                 ::"r"(dst), "l"(m), "r"(bar), "r"(c0), "r"(c1), "h"((uint16_t)3) : "memory");
}
__device__ __forceinline__ void tma3_mc(uint32_t dst, const CUtensorMap* m, uint32_t bar, int c0, int c1, int c2) {
    asm volatile("cp.async.bulk.tensor.3d.shared::cluster.global.mbarrier::complete_tx::bytes.multicast::cluster [%0], [%1, {%3, %4, %5}], [%2], %6;"
                 ::"r"(dst), "l"(m), "r"(bar), "r"(c0), "r"(c1), "r"(c2), "h"((uint16_t)3) : "memory");
}
__device__ __forceinline__ void tma4_mc(uint32_t dst, const CUtensorMap* m, uint32_t bar, int c0, int c1, int c2, int c3) {
    asm volatile("cp.async.bulk.tensor.4d.shared::cluster.global.mbarrier::complete_tx::bytes.multicast::cluster [%0], [%1, {%3, %4, %5, %6}], [%2], %7;"
                 ::"r"(dst), "l"(m), "r"(bar), "r"(c0), "r"(c1), "r"(c2), "r"(c3), "h"((uint16_t)3) : "memory");
}
__device__ __forceinline__ void tma5_mc(uint32_t dst, const CUtensorMap* m, uint32_t bar, int c0, int c1, int c2, int c3, int c4) {
    asm volatile("cp.async.bulk.tensor.5d.shared::cluster.global.mbarrier::complete_tx::bytes.multicast::cluster [%0], [%1, {%3, %4, %5, %6, %7}], [%2], %8;"
                 ::"r"(dst), "l"(m), "r"(bar), "r"(c0), "r"(c1), "r"(c2), "r"(c3), "r"(c4), "h"((uint16_t)3) : "memory");
}
__device__ __forceinline__ void tma3_pf(const CUtensorMap* m, int c0, int c1, int c2) {
    asm volatile("cp.async.bulk.prefetch.tensor.3d.L2.global [%0, {%1, %2, %3}];" ::"l"(m), "r"(c0), "r"(c1), "r"(c2) : "memory");
}
__device__ __forceinline__ void tma2_pf(const CUtensorMap* m, int c0, int c1) {
    asm volatile("cp.async.bulk.prefetch.tensor.2d.L2.global [%0, {%1, %2}];" ::"l"(m), "r"(c0), "r"(c1) : "memory");
}
__device__ __forceinline__ void bulk_store(void* dst, uint32_t src, uint32_t bytes) {
    asm volatile("cp.async.bulk.global.shared::cta.bulk_group [%0], [%1], %2;" ::"l"(dst), "r"(src), "r"(bytes) : "memory");
}
__device__ __forceinline__ void tma4_store(const CUtensorMap* m, uint32_t src, int c2, int c3) {
    asm volatile("cp.async.bulk.tensor.4d.global.shared::cta.bulk_group [%0, {%2, %2, %3, %4}], [%1];"
                 ::"l"(m), "r"(src), "r"(0), "r"(c2), "r"(c3) : "memory");
}
__device__ __forceinline__ void bulk_commit() { asm volatile("cp.async.bulk.commit_group;" ::: "memory"); }
__device__ __forceinline__ void bulk_wait_read() { asm volatile("cp.async.bulk.wait_group.read 0;" ::: "memory"); }
__device__ __forceinline__ void fence_async_smem() { asm volatile("fence.proxy.async.shared::cta;" ::: "memory"); }
__device__ __forceinline__ void bulk_load(uint32_t dst, const void* src, uint32_t bytes, uint32_t bar) {
    asm volatile("cp.async.bulk.shared::cluster.global.mbarrier::complete_tx::bytes [%0], [%1], %2, [%3];"
                 ::"r"(dst), "l"(src), "r"(bytes), "r"(bar) : "memory");
}
__device__ __forceinline__ unsigned atom_exch(unsigned* p, unsigned v) {
    unsigned r;
    asm volatile("atom.relaxed.gpu.global.exch.b32 %0, [%1], %2;" : "=r"(r) : "l"(p), "r"(v) : "memory");
    return r;
}
__device__ __forceinline__ void st_async32(uint32_t a, uint32_t v, uint32_t bar) {
    asm volatile("st.async.shared::cluster.mbarrier::complete_tx::bytes.u32 [%0], %1, [%2];" ::"r"(a), "r"(v), "r"(bar) : "memory");
}
__device__ __forceinline__ void sts128f(uint32_t a, float x, float y, float z, float w) {
    asm volatile("st.shared.v4.f32 [%0], {%1, %2, %3, %4};" ::"r"(a), "f"(x), "f"(y), "f"(z), "f"(w) : "memory");
}
__device__ __forceinline__ void cp_async16(uint32_t dst, const void* src) {
    asm volatile("cp.async.cg.shared.global.L2::256B [%0], [%1], 16;" ::"r"(dst), "l"(src) : "memory");
}
__device__ __forceinline__ void prefetch_map(const CUtensorMap* m) {
    asm volatile("prefetch.tensormap [%0];" ::"l"(m) : "memory");
}

__device__ __forceinline__ void prefetch_l2(const void* p, uint32_t bytes) {
    asm volatile("cp.async.bulk.prefetch.L2.global [%0], %1;" ::"l"(p), "r"(bytes) : "memory");
}

__device__ __forceinline__ void wgmma_fence() { asm volatile("wgmma.fence.sync.aligned;" ::: "memory"); }
__device__ __forceinline__ void wgmma_commit() { asm volatile("wgmma.commit_group.sync.aligned;" ::: "memory"); }
template <int N>
__device__ __forceinline__ void wgmma_wait() { asm volatile("wgmma.wait_group.sync.aligned %0;" ::"n"(N) : "memory"); }

__device__ __forceinline__ uint32_t pack_bf16(float lo, float hi) {
    uint32_t r;
    asm("cvt.rn.bf16x2.f32 %0, %1, %2;" : "=r"(r) : "f"(hi), "f"(lo));
    return r;
}
__device__ __forceinline__ uint32_t pack_f16(float lo, float hi) {
    uint32_t r;
    asm("cvt.rn.f16x2.f32 %0, %1, %2;" : "=r"(r) : "f"(hi), "f"(lo));
    return r;
}
__device__ __forceinline__ uint32_t pack_bf16_v(float lo, float hi) {
    uint32_t r;
    asm volatile("cvt.rn.bf16x2.f32 %0, %1, %2;" : "=r"(r) : "f"(hi), "f"(lo));
    return r;
}
template <int LUT>
__device__ __forceinline__ uint32_t lop3(uint32_t a, uint32_t b, uint32_t c) {
    uint32_t r;
    asm("lop3.b32 %0, %1, %2, %3, %4;" : "=r"(r) : "r"(a), "r"(b), "r"(c), "n"(LUT));
    return r;
}
__device__ __forceinline__ float bf_lo(uint32_t v) { return __uint_as_float(v << 16); }
__device__ __forceinline__ float bf_hi(uint32_t v) { return __uint_as_float(v & 0xffff0000u); }
__device__ __forceinline__ float bf16_round(float v) { return __bfloat162float(__float2bfloat16_rn(v)); }
__device__ __forceinline__ uint32_t bf2_mul(uint32_t a, uint32_t b) {
    uint32_t r;
    asm("mul.rn.bf16x2 %0, %1, %2;" : "=r"(r) : "r"(a), "r"(b));
    return r;
}
__device__ __forceinline__ uint32_t bf2_add_relu(uint32_t a, uint32_t b) {
    uint32_t r;
    asm("fma.rn.relu.bf16x2 %0, %1, %2, %3;" : "=r"(r) : "r"(a), "r"(0x3f803f80u), "r"(b));
    return r;
}
__device__ __forceinline__ uint4 ldg128(const void* p) {
    uint4 v;
    asm volatile("ld.global.nc.v4.u32 {%0, %1, %2, %3}, [%4];" : "=r"(v.x), "=r"(v.y), "=r"(v.z), "=r"(v.w) : "l"(p));
    return v;
}
__device__ __forceinline__ uint32_t ldg32(const void* p) {
    uint32_t v;
    asm volatile("ld.global.nc.u32 %0, [%1];" : "=r"(v) : "l"(p));
    return v;
}
__device__ __forceinline__ uint32_t ldg32na(const void* p) {
    uint32_t v;
    asm volatile("ld.global.nc.L1::no_allocate.u32 %0, [%1];" : "=r"(v) : "l"(p));
    return v;
}
__device__ __forceinline__ uint32_t ldg16(const __nv_bfloat16* p) {
    uint32_t v;
    asm volatile("ld.global.nc.u16 %0, [%1];" : "=r"(v) : "l"(p));
    return v;
}
__device__ __forceinline__ uint4 ld_relaxed128(const void* p) {
    uint4 v;
    asm volatile("ld.relaxed.gpu.global.v4.u32 {%0, %1, %2, %3}, [%4];" : "=r"(v.x), "=r"(v.y), "=r"(v.z), "=r"(v.w) : "l"(p) : "memory");
    return v;
}
__device__ __forceinline__ uint4 ld_weak128(const void* p) {
    uint4 v;
    asm volatile("ld.global.ca.v4.u32 {%0, %1, %2, %3}, [%4];" : "=r"(v.x), "=r"(v.y), "=r"(v.z), "=r"(v.w) : "l"(p) : "memory");
    return v;
}
__device__ __forceinline__ uint2 ld_relaxed64(const void* p) {
    unsigned long long v;
    asm volatile("ld.relaxed.gpu.global.u64 %0, [%1];" : "=l"(v) : "l"(p) : "memory");
    return make_uint2((uint32_t)v, (uint32_t)(v >> 32));
}
__device__ __forceinline__ void st_relaxed64(void* p, uint32_t lo, uint32_t hi) {
    unsigned long long v = ((unsigned long long)hi << 32) | lo;
    asm volatile("st.relaxed.gpu.global.u64 [%0], %1;" ::"l"(p), "l"(v) : "memory");
}
__device__ __forceinline__ void st_relaxed2x64(void* p, uint32_t a, uint32_t b, uint32_t c, uint32_t d) {
    unsigned long long v0 = ((unsigned long long)b << 32) | a, v1 = ((unsigned long long)d << 32) | c;
    asm volatile("st.relaxed.gpu.global.v2.u64 [%0], {%1, %2};" ::"l"(p), "l"(v0), "l"(v1) : "memory");
}
__device__ __forceinline__ uint4 ld_relaxed2x64(const void* p) {
    unsigned long long v0, v1;
    asm volatile("ld.relaxed.gpu.global.v2.u64 {%0, %1}, [%2];" : "=l"(v0), "=l"(v1) : "l"(p) : "memory");
    return make_uint4((uint32_t)v0, (uint32_t)(v0 >> 32), (uint32_t)v1, (uint32_t)(v1 >> 32));
}
__device__ __forceinline__ void stg128(void* p, uint32_t a, uint32_t b, uint32_t c, uint32_t d) {
    asm volatile("st.global.v4.u32 [%0], {%1, %2, %3, %4};" ::"l"(p), "r"(a), "r"(b), "r"(c), "r"(d) : "memory");
}
__device__ __forceinline__ void stg64f(void* p, float a, float b) {
    asm volatile("st.global.v2.f32 [%0], {%1, %2};" ::"l"(p), "f"(a), "f"(b) : "memory");
}
__device__ __forceinline__ uint4 lds128(uint32_t a) {
    uint4 v;
    asm volatile("ld.shared.v4.u32 {%0, %1, %2, %3}, [%4];" : "=r"(v.x), "=r"(v.y), "=r"(v.z), "=r"(v.w) : "r"(a) : "memory");
    return v;
}
__device__ __forceinline__ uint2 lds64(uint32_t a) {
    uint2 v;
    asm volatile("ld.shared.v2.u32 {%0, %1}, [%2];" : "=r"(v.x), "=r"(v.y) : "r"(a) : "memory");
    return v;
}
__device__ __forceinline__ uint4 ldsm4(uint32_t a) {
    uint4 v;
    asm volatile("ldmatrix.sync.aligned.m8n8.x4.shared.b16 {%0, %1, %2, %3}, [%4];" : "=r"(v.x), "=r"(v.y), "=r"(v.z), "=r"(v.w) : "r"(a) : "memory");
    return v;
}
__device__ __forceinline__ uint32_t lds16(uint32_t a) {
    uint32_t v;
    asm volatile("ld.shared.u16 %0, [%1];" : "=r"(v) : "r"(a) : "memory");
    return v;
}
__device__ __forceinline__ void sts16(uint32_t a, uint32_t x) {
    asm volatile("st.shared.u16 [%0], %1;" ::"r"(a), "h"((uint16_t)x) : "memory");
}
__device__ __forceinline__ void st_relaxed32(void* p, uint32_t v) {
    asm volatile("st.relaxed.gpu.global.u32 [%0], %1;" ::"l"(p), "r"(v) : "memory");
}
__device__ __forceinline__ float lds32f(uint32_t a) {
    float v;
    asm volatile("ld.shared.f32 %0, [%1];" : "=f"(v) : "r"(a) : "memory");
    return v;
}
__device__ __forceinline__ void sts128(uint32_t a, uint32_t x, uint32_t y, uint32_t z, uint32_t w) {
    asm volatile("st.shared.v4.u32 [%0], {%1, %2, %3, %4};" ::"r"(a), "r"(x), "r"(y), "r"(z), "r"(w) : "memory");
}
__device__ __forceinline__ void sts64f(uint32_t a, float x, float y) {
    asm volatile("st.shared.v2.f32 [%0], {%1, %2};" ::"r"(a), "f"(x), "f"(y) : "memory");
}
__device__ __forceinline__ float4 lds128f(uint32_t a) {
    float4 v;
    asm volatile("ld.shared.v4.f32 {%0, %1, %2, %3}, [%4];" : "=f"(v.x), "=f"(v.y), "=f"(v.z), "=f"(v.w) : "r"(a) : "memory");
    return v;
}
__device__ __forceinline__ uint32_t lds32(uint32_t a) {
    uint32_t v;
    asm volatile("ld.shared.u32 %0, [%1];" : "=r"(v) : "r"(a) : "memory");
    return v;
}
__device__ __forceinline__ void sts32(uint32_t a, uint32_t x) {
    asm volatile("st.shared.u32 [%0], %1;" ::"r"(a), "r"(x) : "memory");
}
__device__ __forceinline__ void stg128f(void* p, float a, float b, float c, float d) {
    asm volatile("st.global.v4.f32 [%0], {%1, %2, %3, %4};" ::"l"(p), "f"(a), "f"(b), "f"(c), "f"(d) : "memory");
}
__device__ __forceinline__ unsigned ld_relaxed32(const unsigned* p) {
    unsigned v;
    asm volatile("ld.relaxed.gpu.global.u32 %0, [%1];" : "=r"(v) : "l"(p) : "memory");
    return v;
}
__device__ __forceinline__ void wait_counter(const unsigned* p, unsigned target) {
    unsigned n = 0, v;
    while (true) {
        asm volatile("ld.acquire.gpu.global.u32 %0, [%1];" : "=r"(v) : "l"(p) : "memory");
        if ((int)(v - target) >= 0) break;
        if (++n > kSpinLimit) TRAP();
        __nanosleep(32);
    }
}
#define KT(IT, W) do { } while (0)
#define STAMP(cond, slot) do { } while (0)
#define STAMPA(cond, slot) STAMP(cond, slot)
#define STAMPB(cond, slot) do { } while (0)

#define STAMPC(cond, slot) do { } while (0)
#define STAMPD(cond, slot) do { } while (0)
#define STAMPP(cond, slot) do { } while (0)
#define STAMPE(cond, slot) STAMP(cond, slot)
template <int TA, int TB>
__device__ __forceinline__ void wgmma_n256(float (&d)[128], uint64_t da, uint64_t db, int keep) {
    asm volatile(
        "{\n.reg .pred p;\nsetp.ne.b32 p, %132, 0;\n"
        "wgmma.mma_async.sync.aligned.m64n256k16.f32.bf16.bf16 "
        "{%0, %1, %2, %3, %4, %5, %6, %7, %8, %9, %10, %11, %12, %13, %14, %15, "
        "%16, %17, %18, %19, %20, %21, %22, %23, %24, %25, %26, %27, %28, %29, %30, %31, "
        "%32, %33, %34, %35, %36, %37, %38, %39, %40, %41, %42, %43, %44, %45, %46, %47, "
        "%48, %49, %50, %51, %52, %53, %54, %55, %56, %57, %58, %59, %60, %61, %62, %63, "
        "%64, %65, %66, %67, %68, %69, %70, %71, %72, %73, %74, %75, %76, %77, %78, %79, "
        "%80, %81, %82, %83, %84, %85, %86, %87, %88, %89, %90, %91, %92, %93, %94, %95, "
        "%96, %97, %98, %99, %100, %101, %102, %103, %104, %105, %106, %107, %108, %109, %110, %111, "
        "%112, %113, %114, %115, %116, %117, %118, %119, %120, %121, %122, %123, %124, %125, %126, %127}, "
        "%128, %129, p, 1, 1, %130, %131;\n}\n"
        : "+f"(d[0]), "+f"(d[1]), "+f"(d[2]), "+f"(d[3]), "+f"(d[4]), "+f"(d[5]), "+f"(d[6]), "+f"(d[7]),
          "+f"(d[8]), "+f"(d[9]), "+f"(d[10]), "+f"(d[11]), "+f"(d[12]), "+f"(d[13]), "+f"(d[14]), "+f"(d[15]),
          "+f"(d[16]), "+f"(d[17]), "+f"(d[18]), "+f"(d[19]), "+f"(d[20]), "+f"(d[21]), "+f"(d[22]), "+f"(d[23]),
          "+f"(d[24]), "+f"(d[25]), "+f"(d[26]), "+f"(d[27]), "+f"(d[28]), "+f"(d[29]), "+f"(d[30]), "+f"(d[31]),
          "+f"(d[32]), "+f"(d[33]), "+f"(d[34]), "+f"(d[35]), "+f"(d[36]), "+f"(d[37]), "+f"(d[38]), "+f"(d[39]),
          "+f"(d[40]), "+f"(d[41]), "+f"(d[42]), "+f"(d[43]), "+f"(d[44]), "+f"(d[45]), "+f"(d[46]), "+f"(d[47]),
          "+f"(d[48]), "+f"(d[49]), "+f"(d[50]), "+f"(d[51]), "+f"(d[52]), "+f"(d[53]), "+f"(d[54]), "+f"(d[55]),
          "+f"(d[56]), "+f"(d[57]), "+f"(d[58]), "+f"(d[59]), "+f"(d[60]), "+f"(d[61]), "+f"(d[62]), "+f"(d[63]),
          "+f"(d[64]), "+f"(d[65]), "+f"(d[66]), "+f"(d[67]), "+f"(d[68]), "+f"(d[69]), "+f"(d[70]), "+f"(d[71]),
          "+f"(d[72]), "+f"(d[73]), "+f"(d[74]), "+f"(d[75]), "+f"(d[76]), "+f"(d[77]), "+f"(d[78]), "+f"(d[79]),
          "+f"(d[80]), "+f"(d[81]), "+f"(d[82]), "+f"(d[83]), "+f"(d[84]), "+f"(d[85]), "+f"(d[86]), "+f"(d[87]),
          "+f"(d[88]), "+f"(d[89]), "+f"(d[90]), "+f"(d[91]), "+f"(d[92]), "+f"(d[93]), "+f"(d[94]), "+f"(d[95]),
          "+f"(d[96]), "+f"(d[97]), "+f"(d[98]), "+f"(d[99]), "+f"(d[100]), "+f"(d[101]), "+f"(d[102]), "+f"(d[103]),
          "+f"(d[104]), "+f"(d[105]), "+f"(d[106]), "+f"(d[107]), "+f"(d[108]), "+f"(d[109]), "+f"(d[110]), "+f"(d[111]),
          "+f"(d[112]), "+f"(d[113]), "+f"(d[114]), "+f"(d[115]), "+f"(d[116]), "+f"(d[117]), "+f"(d[118]), "+f"(d[119]),
          "+f"(d[120]), "+f"(d[121]), "+f"(d[122]), "+f"(d[123]), "+f"(d[124]), "+f"(d[125]), "+f"(d[126]), "+f"(d[127])
        : "l"(da), "l"(db), "n"(TA), "n"(TB), "r"(keep));
}
template <int TA, int TB>
__device__ __forceinline__ void wgmma_n192(float (&d)[128], uint64_t da, uint64_t db, int keep) {
    asm volatile(
        "{\n.reg .pred p;\nsetp.ne.b32 p, %100, 0;\n"
        "wgmma.mma_async.sync.aligned.m64n192k16.f32.bf16.bf16 "
        "{%0, %1, %2, %3, %4, %5, %6, %7, %8, %9, %10, %11, %12, %13, %14, %15, "
        "%16, %17, %18, %19, %20, %21, %22, %23, %24, %25, %26, %27, %28, %29, %30, %31, "
        "%32, %33, %34, %35, %36, %37, %38, %39, %40, %41, %42, %43, %44, %45, %46, %47, "
        "%48, %49, %50, %51, %52, %53, %54, %55, %56, %57, %58, %59, %60, %61, %62, %63, "
        "%64, %65, %66, %67, %68, %69, %70, %71, %72, %73, %74, %75, %76, %77, %78, %79, "
        "%80, %81, %82, %83, %84, %85, %86, %87, %88, %89, %90, %91, %92, %93, %94, %95}, "
        "%96, %97, p, 1, 1, %98, %99;\n}\n"
        : "+f"(d[0]), "+f"(d[1]), "+f"(d[2]), "+f"(d[3]), "+f"(d[4]), "+f"(d[5]), "+f"(d[6]), "+f"(d[7]),
          "+f"(d[8]), "+f"(d[9]), "+f"(d[10]), "+f"(d[11]), "+f"(d[12]), "+f"(d[13]), "+f"(d[14]), "+f"(d[15]),
          "+f"(d[16]), "+f"(d[17]), "+f"(d[18]), "+f"(d[19]), "+f"(d[20]), "+f"(d[21]), "+f"(d[22]), "+f"(d[23]),
          "+f"(d[24]), "+f"(d[25]), "+f"(d[26]), "+f"(d[27]), "+f"(d[28]), "+f"(d[29]), "+f"(d[30]), "+f"(d[31]),
          "+f"(d[32]), "+f"(d[33]), "+f"(d[34]), "+f"(d[35]), "+f"(d[36]), "+f"(d[37]), "+f"(d[38]), "+f"(d[39]),
          "+f"(d[40]), "+f"(d[41]), "+f"(d[42]), "+f"(d[43]), "+f"(d[44]), "+f"(d[45]), "+f"(d[46]), "+f"(d[47]),
          "+f"(d[48]), "+f"(d[49]), "+f"(d[50]), "+f"(d[51]), "+f"(d[52]), "+f"(d[53]), "+f"(d[54]), "+f"(d[55]),
          "+f"(d[56]), "+f"(d[57]), "+f"(d[58]), "+f"(d[59]), "+f"(d[60]), "+f"(d[61]), "+f"(d[62]), "+f"(d[63]),
          "+f"(d[64]), "+f"(d[65]), "+f"(d[66]), "+f"(d[67]), "+f"(d[68]), "+f"(d[69]), "+f"(d[70]), "+f"(d[71]),
          "+f"(d[72]), "+f"(d[73]), "+f"(d[74]), "+f"(d[75]), "+f"(d[76]), "+f"(d[77]), "+f"(d[78]), "+f"(d[79]),
          "+f"(d[80]), "+f"(d[81]), "+f"(d[82]), "+f"(d[83]), "+f"(d[84]), "+f"(d[85]), "+f"(d[86]), "+f"(d[87]),
          "+f"(d[88]), "+f"(d[89]), "+f"(d[90]), "+f"(d[91]), "+f"(d[92]), "+f"(d[93]), "+f"(d[94]), "+f"(d[95])
        : "l"(da), "l"(db), "n"(TA), "n"(TB), "r"(keep));
}
template <int TA, int TB, int O = 0>
__device__ __forceinline__ void wgmma_n128(float (&d)[128], uint64_t da, uint64_t db, int keep) {
    asm volatile(
        "{\n.reg .pred p;\nsetp.ne.b32 p, %68, 0;\n"
        "wgmma.mma_async.sync.aligned.m64n128k16.f32.bf16.bf16 "
        "{%0, %1, %2, %3, %4, %5, %6, %7, %8, %9, %10, %11, %12, %13, %14, %15, "
        "%16, %17, %18, %19, %20, %21, %22, %23, %24, %25, %26, %27, %28, %29, %30, %31, "
        "%32, %33, %34, %35, %36, %37, %38, %39, %40, %41, %42, %43, %44, %45, %46, %47, "
        "%48, %49, %50, %51, %52, %53, %54, %55, %56, %57, %58, %59, %60, %61, %62, %63}, "
        "%64, %65, p, 1, 1, %66, %67;\n}\n"
        : "+f"(d[O + 0]), "+f"(d[O + 1]), "+f"(d[O + 2]), "+f"(d[O + 3]), "+f"(d[O + 4]), "+f"(d[O + 5]), "+f"(d[O + 6]), "+f"(d[O + 7]),
          "+f"(d[O + 8]), "+f"(d[O + 9]), "+f"(d[O + 10]), "+f"(d[O + 11]), "+f"(d[O + 12]), "+f"(d[O + 13]), "+f"(d[O + 14]), "+f"(d[O + 15]),
          "+f"(d[O + 16]), "+f"(d[O + 17]), "+f"(d[O + 18]), "+f"(d[O + 19]), "+f"(d[O + 20]), "+f"(d[O + 21]), "+f"(d[O + 22]), "+f"(d[O + 23]),
          "+f"(d[O + 24]), "+f"(d[O + 25]), "+f"(d[O + 26]), "+f"(d[O + 27]), "+f"(d[O + 28]), "+f"(d[O + 29]), "+f"(d[O + 30]), "+f"(d[O + 31]),
          "+f"(d[O + 32]), "+f"(d[O + 33]), "+f"(d[O + 34]), "+f"(d[O + 35]), "+f"(d[O + 36]), "+f"(d[O + 37]), "+f"(d[O + 38]), "+f"(d[O + 39]),
          "+f"(d[O + 40]), "+f"(d[O + 41]), "+f"(d[O + 42]), "+f"(d[O + 43]), "+f"(d[O + 44]), "+f"(d[O + 45]), "+f"(d[O + 46]), "+f"(d[O + 47]),
          "+f"(d[O + 48]), "+f"(d[O + 49]), "+f"(d[O + 50]), "+f"(d[O + 51]), "+f"(d[O + 52]), "+f"(d[O + 53]), "+f"(d[O + 54]), "+f"(d[O + 55]),
          "+f"(d[O + 56]), "+f"(d[O + 57]), "+f"(d[O + 58]), "+f"(d[O + 59]), "+f"(d[O + 60]), "+f"(d[O + 61]), "+f"(d[O + 62]), "+f"(d[O + 63])
        : "l"(da), "l"(db), "n"(TA), "n"(TB), "r"(keep));
}
__device__ __forceinline__ void wgmma_n128_rs(float (&d)[128], uint32_t a0, uint32_t a1, uint32_t a2, uint32_t a3, uint64_t db) {
    asm volatile(
        "{\n.reg .pred p;\nsetp.ne.b32 p, 1, 0;\n"
        "wgmma.mma_async.sync.aligned.m64n128k16.f32.bf16.bf16 "
        "{%0, %1, %2, %3, %4, %5, %6, %7, %8, %9, %10, %11, %12, %13, %14, %15, "
        "%16, %17, %18, %19, %20, %21, %22, %23, %24, %25, %26, %27, %28, %29, %30, %31, "
        "%32, %33, %34, %35, %36, %37, %38, %39, %40, %41, %42, %43, %44, %45, %46, %47, "
        "%48, %49, %50, %51, %52, %53, %54, %55, %56, %57, %58, %59, %60, %61, %62, %63}, "
        "{%64, %65, %66, %67}, %68, p, 1, 1, 1;\n}\n"
        : "+f"(d[0]), "+f"(d[1]), "+f"(d[2]), "+f"(d[3]), "+f"(d[4]), "+f"(d[5]), "+f"(d[6]), "+f"(d[7]),
          "+f"(d[8]), "+f"(d[9]), "+f"(d[10]), "+f"(d[11]), "+f"(d[12]), "+f"(d[13]), "+f"(d[14]), "+f"(d[15]),
          "+f"(d[16]), "+f"(d[17]), "+f"(d[18]), "+f"(d[19]), "+f"(d[20]), "+f"(d[21]), "+f"(d[22]), "+f"(d[23]),
          "+f"(d[24]), "+f"(d[25]), "+f"(d[26]), "+f"(d[27]), "+f"(d[28]), "+f"(d[29]), "+f"(d[30]), "+f"(d[31]),
          "+f"(d[32]), "+f"(d[33]), "+f"(d[34]), "+f"(d[35]), "+f"(d[36]), "+f"(d[37]), "+f"(d[38]), "+f"(d[39]),
          "+f"(d[40]), "+f"(d[41]), "+f"(d[42]), "+f"(d[43]), "+f"(d[44]), "+f"(d[45]), "+f"(d[46]), "+f"(d[47]),
          "+f"(d[48]), "+f"(d[49]), "+f"(d[50]), "+f"(d[51]), "+f"(d[52]), "+f"(d[53]), "+f"(d[54]), "+f"(d[55]),
          "+f"(d[56]), "+f"(d[57]), "+f"(d[58]), "+f"(d[59]), "+f"(d[60]), "+f"(d[61]), "+f"(d[62]), "+f"(d[63])
        : "r"(a0), "r"(a1), "r"(a2), "r"(a3), "l"(db));
}
template <int TA, int TB>
__device__ __forceinline__ void wgmma_n224(float (&d)[128], uint64_t da, uint64_t db, int keep) {
    asm volatile(
        "{\n.reg .pred p;\nsetp.ne.b32 p, %116, 0;\n"
        "wgmma.mma_async.sync.aligned.m64n224k16.f32.bf16.bf16 "
        "{%0, %1, %2, %3, %4, %5, %6, %7, %8, %9, %10, %11, %12, %13, %14, %15, "
        "%16, %17, %18, %19, %20, %21, %22, %23, %24, %25, %26, %27, %28, %29, %30, %31, "
        "%32, %33, %34, %35, %36, %37, %38, %39, %40, %41, %42, %43, %44, %45, %46, %47, "
        "%48, %49, %50, %51, %52, %53, %54, %55, %56, %57, %58, %59, %60, %61, %62, %63, "
        "%64, %65, %66, %67, %68, %69, %70, %71, %72, %73, %74, %75, %76, %77, %78, %79, "
        "%80, %81, %82, %83, %84, %85, %86, %87, %88, %89, %90, %91, %92, %93, %94, %95, "
        "%96, %97, %98, %99, %100, %101, %102, %103, %104, %105, %106, %107, %108, %109, %110, %111}, "
        "%112, %113, p, 1, 1, %114, %115;\n}\n"
        : "+f"(d[0]), "+f"(d[1]), "+f"(d[2]), "+f"(d[3]), "+f"(d[4]), "+f"(d[5]), "+f"(d[6]), "+f"(d[7]),
          "+f"(d[8]), "+f"(d[9]), "+f"(d[10]), "+f"(d[11]), "+f"(d[12]), "+f"(d[13]), "+f"(d[14]), "+f"(d[15]),
          "+f"(d[16]), "+f"(d[17]), "+f"(d[18]), "+f"(d[19]), "+f"(d[20]), "+f"(d[21]), "+f"(d[22]), "+f"(d[23]),
          "+f"(d[24]), "+f"(d[25]), "+f"(d[26]), "+f"(d[27]), "+f"(d[28]), "+f"(d[29]), "+f"(d[30]), "+f"(d[31]),
          "+f"(d[32]), "+f"(d[33]), "+f"(d[34]), "+f"(d[35]), "+f"(d[36]), "+f"(d[37]), "+f"(d[38]), "+f"(d[39]),
          "+f"(d[40]), "+f"(d[41]), "+f"(d[42]), "+f"(d[43]), "+f"(d[44]), "+f"(d[45]), "+f"(d[46]), "+f"(d[47]),
          "+f"(d[48]), "+f"(d[49]), "+f"(d[50]), "+f"(d[51]), "+f"(d[52]), "+f"(d[53]), "+f"(d[54]), "+f"(d[55]),
          "+f"(d[56]), "+f"(d[57]), "+f"(d[58]), "+f"(d[59]), "+f"(d[60]), "+f"(d[61]), "+f"(d[62]), "+f"(d[63]),
          "+f"(d[64]), "+f"(d[65]), "+f"(d[66]), "+f"(d[67]), "+f"(d[68]), "+f"(d[69]), "+f"(d[70]), "+f"(d[71]),
          "+f"(d[72]), "+f"(d[73]), "+f"(d[74]), "+f"(d[75]), "+f"(d[76]), "+f"(d[77]), "+f"(d[78]), "+f"(d[79]),
          "+f"(d[80]), "+f"(d[81]), "+f"(d[82]), "+f"(d[83]), "+f"(d[84]), "+f"(d[85]), "+f"(d[86]), "+f"(d[87]),
          "+f"(d[88]), "+f"(d[89]), "+f"(d[90]), "+f"(d[91]), "+f"(d[92]), "+f"(d[93]), "+f"(d[94]), "+f"(d[95]),
          "+f"(d[96]), "+f"(d[97]), "+f"(d[98]), "+f"(d[99]), "+f"(d[100]), "+f"(d[101]), "+f"(d[102]), "+f"(d[103]),
          "+f"(d[104]), "+f"(d[105]), "+f"(d[106]), "+f"(d[107]), "+f"(d[108]), "+f"(d[109]), "+f"(d[110]), "+f"(d[111])
        : "l"(da), "l"(db), "n"(TA), "n"(TB), "r"(keep));
}

constexpr uint64_t kDescHi = (uint64_t)(64u | 0x40000000u) << 32;
constexpr uint64_t kDescHi64 = (uint64_t)(32u | 0x80000000u) << 32;
template <int MODE>
__device__ __forceinline__ void mma_kblock(float (&acc)[128], uint32_t a_lo, uint32_t b_lo, int keep) {
    constexpr bool G32 = (MODE == 5 && W64MAIN) || MODE == 6;
    constexpr uint32_t HALF = (MODE == 1) ? 12288u : (MODE == 5 && G32) ? 14336u : 16384u;
    constexpr bool BN = (MODE == 1 || MODE == 2 || MODE >= 4);
#pragma unroll
    for (int kk = 0; kk < 4; ++kk) {
        const uint32_t ao = (MODE == 3) ? kk * 2048u : kk * 32u;
        const uint32_t bo = BN ? ((kk >> 1) * HALF + (kk & 1) * (G32 ? 1024u : 2048u)) : kk * 32u;
        const uint64_t da = kDescHi | (uint64_t)(a_lo + (ao >> 4) + (1u << 16));
        const uint64_t db = (G32 ? kDescHi64 : kDescHi) | (uint64_t)(b_lo + (bo >> 4) + (G32 ? (128u << 16) : BN ? (256u << 16) : (1u << 16)));
        if (MODE == 1) wgmma_n192<0, 1>(acc, da, db, kk == 0 ? keep : 1);
        else if (MODE == 4) wgmma_n128<0, 1>(acc, da, db, 1);
        else if (MODE == 5) wgmma_n224<0, 1>(acc, da, db, kk == 0 ? keep : 1);
        else wgmma_n256<(MODE == 3), BN>(acc, da, db, kk == 0 ? keep : 1);
    }
}

struct Params {
    const __nv_bfloat16* x;
    const __nv_bfloat16* b_lo;
    const __nv_bfloat16* b_hi;
    Scratch* s;
    const __nv_bfloat16* gate_w;
    const __nv_bfloat16* lam_re;
    const __nv_bfloat16* lam_im;
    const __nv_bfloat16* log_dt;
    const __nv_bfloat16* dskip;
    const __nv_bfloat16* b1;
    const __nv_bfloat16* b2;
    float* out;
    int swap;
};

#define CMUL(rr, ri, ar, ai, br, bi) do { float _r = (ar) * (br) - (ai) * (bi); float _i = (ar) * (bi) + (ai) * (br); rr = _r; ri = _i; } while (0)
#define CFMA(rr, ri, ar, ai, br, bi) do { float _r = fmaf(-(ai), (bi), fmaf((ar), (br), rr)); float _i = fmaf((ai), (br), fmaf((ar), (bi), ri)); rr = _r; ri = _i; } while (0)

#define KB_OPEN(IT, LAST)                                                                        \
    KT(IT, 0);                                                                                   \
    if (ORDER && (LAST) && wg == 1) bar_sync(7, 256);                                            \
    mbar_wait(bar_full + 8 * ((IT) & 3), ((IT) >> 2) & 1);                                \
    KT(IT, 1);
#define KB_CLOSE(IT, LAST, REL)                                                                  \
    if (ORDER && (LAST) && wg == 0) bar_arrive(7, 256);                                          \
    wgmma_wait<1>();                                                                             \
    if (lane < 2 && (REL)) mbar_arrive_cluster(rel_addr + 8 * (((IT) - 1) & 3));
#define KBLOCK(MODE, IT, FIRST, LAST)                                                            \
    {                                                                                            \
        const uint32_t so = ((IT) & 3) * (kStageBytes >> 4);                                     \
        KB_OPEN(IT, LAST);                                                                       \
        wgmma_fence();                                                                           \
        mma_kblock<MODE>(acc, a_lo + so, b_lo + so, !(FIRST));                                   \
        wgmma_commit();                                                                          \
        KB_CLOSE(IT, LAST, !(FIRST));                                                            \
    }
#define TILE_END() do { wgmma_wait<0>(); if (lane < 2) mbar_arrive_cluster(rel_addr + 24); } while (0)

#define FFN_SLICE(J, STEP)                                                                              \
    {                                                                                                  \
        const uint4 bv = lds128(bias_s + (J) * 64);                                                    \
        const uint32_t bb[4] = {bv.x, bv.y, bv.z, bv.w};                                               \
        _Pragma("unroll") for (int jj = 0; jj < 4; ++jj) {                                             \
            const uint32_t r0 = bf2_add_relu(pk[8 * (J) + 2 * jj], bb[jj]), r1 = bf2_add_relu(pk[8 * (J) + 2 * jj + 1], bb[jj]); \
            pk[8 * (J) + 2 * jj] = bf2_mul(bf2_mul(r0, r0), om0);                                      \
            pk[8 * (J) + 2 * jj + 1] = bf2_mul(bf2_mul(r1, r1), om1);                                  \
        }                                                                                              \
        stg128(hf + (STEP) * (J), pk[8 * (J)], pk[8 * (J) + 2], pk[8 * (J) + 4], pk[8 * (J) + 6]);         \
        stg128(hf + 8 * kF + (STEP) * (J), pk[8 * (J) + 1], pk[8 * (J) + 3], pk[8 * (J) + 5], pk[8 * (J) + 7]); \
    }

__device__ __forceinline__ void helper_cta(const CUtensorMap* mXf, const CUtensorMap* mW1h, const Params& p, uint32_t sbase) {
    const uint32_t bar_full = sbase + kBarOff, bar_empty = bar_full + 32;
    const int tid = threadIdx.x, lane = tid & 31;
    const int warp = __shfl_sync(0xffffffffu, tid >> 5, 0);
    const uint32_t rank = blockIdx.x & 1;
    const int c0 = (blockIdx.x & 2) * 2;
    if (tid == 0) {
        prefetch_map(mXf); prefetch_map(mW1h);
#pragma unroll
        for (int s = 0; s < kStages; ++s) { mbar_init(bar_full + 8 * s, 1); mbar_init(bar_empty + 8 * s, 16); }
        asm volatile("fence.mbarrier_init.release.cluster;\nfence.proxy.async.shared::cta;" ::: "memory");
    }
    __syncwarp();
    cluster_arrive();
    cluster_wait();
    if (warp >= 8) asm volatile("setmaxnreg.dec.sync.aligned.u32 24;");
    if (warp == 8) {
        if (elect_one()) {
#pragma unroll 1
            for (int it = 0; it < 64; ++it) {
                const uint32_t st = sbase + (it & 3) * kStageBytes, fb = bar_full + 8 * (it & 3);
                const int k0 = (it & 15) * 64;
                mbar_wait(bar_empty + 8 * (it & 3), ((it >> 2) & 1) ^ 1);
                mbar_expect_tx(fb, 49152);
                tma5(st, mXf, fb, k0, 0, 0, rank * 4, c0 + (it >> 4));
                tma3_mc(st + kABytes + rank * 16384, mW1h, fb, 0, k0 + rank * 32, 0);
            }
        }
    } else if (warp == 9) {
        const __nv_bfloat16* src = p.b1 + 256 * (lane >> 2) + 224 + 2 * (lane & 3);
        sts128(sbase + kBiasOff + lane * 16, ldg32(src), ldg32(src + 8), ldg32(src + 16), ldg32(src + 24));
        const unsigned tag = ld_relaxed32(&p.s->epoch) + 1;
        sts32(sbase + kGateOff, tag);
        bar_sync(1, 288);
        if (lane == 0 && atomicInc(&p.s->done, 131u) == 131u) {
            st_relaxed32(&p.s->epoch, tag);
#pragma unroll 1
            for (int i = 0; i < 64; i += 4) stg128(&p.s->claim[i], 0, 0, 0, 0);
        }
        __syncwarp();
#pragma unroll 1
        for (int t = 0; t < 4; ++t) {
            bar_sync(2 + t, 288);
            if (lane == 0) {
                asm volatile("fence.acq_rel.gpu;\nfence.proxy.async.global;" ::: "memory");
                asm volatile("red.relaxed.gpu.global.add.u32 [%0], 1;" ::"l"(&p.s->cnt[(40 + 2 * (c0 + t) + rank) * 32]) : "memory");
            }
            __syncwarp();
        }
    } else if (warp < 8) {
        asm volatile("setmaxnreg.inc.sync.aligned.u32 240;");
        const int wg = warp >> 2, w = warp & 3, r = lane >> 2, q = lane & 3;
        const uint32_t a_lo = (kSmemOrg + wg * 8192) >> 4;
        constexpr uint32_t b_lo = (kSmemOrg + kABytes) >> 4;
        const uint32_t rel_addr = mapa(bar_empty, (uint32_t)(lane & 1));
        float acc[128];
        uint32_t pk[64], om0, om1;
        __nv_bfloat16* hf = p.s->Hf + (ptrdiff_t)((2 * c0 - 2 + (int)rank) * 128 + wg * 64 + w * 16 + r) * kF + q * 8 + 224;
        const uint2* gp = &p.s->gate[c0 * 256 - 256 + 128 * (w & 1) + 8 * (4 * (int)rank + 2 * wg + (w >> 1)) + r];
        const uint32_t bias_s = sbase + kBiasOff + q * 16;
#pragma unroll
        for (int i = 0; i < 128; ++i) UNDEF_F(acc[i]);
#pragma unroll
        for (int i = 0; i < 64; ++i) UNDEF_R(pk[i]);
        UNDEF_R(om0); UNDEF_R(om1);
        bar_sync(1, 288);
#pragma unroll 1
        for (uint32_t it = 0; it < 73; ++it) {
            const uint32_t so = (it & 3) * (kStageBytes >> 4), j = it & 15;
            if (it < 64) {
                mbar_wait(bar_full + 8 * (it & 3), (it >> 2) & 1);
                wgmma_fence();
                mma_kblock<6>(acc, a_lo + so, b_lo + so, j);
                wgmma_commit();
                wgmma_wait<1>();
                if (lane < 2 && j != 0 && it < 61) mbar_arrive_cluster(rel_addr + 8 * ((it - 1) & 3));
            }
            if (j == 15) {
                wgmma_wait<0>();
                if (lane < 2 && it < 60) mbar_arrive_cluster(rel_addr + 24);
#pragma unroll
                for (int i = 0; i < 64; ++i) pk[i] = pack_bf16_v(acc[2 * i], acc[2 * i + 1]);
                hf += 256 * kF;
                gp += 256;
            } else if (it < 16 || j > 8) {
            } else if (j == 0) {
                const unsigned tag = lds32(sbase + kGateOff);
                uint2 g0, g1;
                unsigned spins = 0;
                do {
                    g0 = ld_relaxed64(gp); g1 = ld_relaxed64(gp + 64);
                } while (__any_sync(0xffffffffu, g0.y != tag || g1.y != tag) && ++spins < kSpinLimit);
                const float oa = 1.0f - __uint_as_float(g0.x), ob = 1.0f - __uint_as_float(g1.x);
                om0 = pack_bf16(oa, oa); om1 = pack_bf16(ob, ob);
            } else {
                if (j & 4) {
                    if (j & 2) { if (j & 1) FFN_SLICE(7, 256) else FFN_SLICE(6, 256) } else { if (j & 1) FFN_SLICE(5, 256) else FFN_SLICE(4, 256) }
                } else {
                    if (j & 2) { if (j & 1) FFN_SLICE(3, 256) else FFN_SLICE(2, 256) } else { if (j & 1) FFN_SLICE(1, 256) else FFN_SLICE(0, 256) }
                }
                if (j == 8) bar_arrive(1 + (it >> 4), 288);
            }
        }
        wgmma_wait<0>();
    }
}

__global__ void __cluster_dims__(2, 1, 1) __launch_bounds__(384, 1)
fused_kernel(const Params p, const __grid_constant__ CUtensorMap mB, const __grid_constant__ CUtensorMap mXs, const __grid_constant__ CUtensorMap mXf,
             const __grid_constant__ CUtensorMap mW1b, const __grid_constant__ CUtensorMap mW1a, const __grid_constant__ CUtensorMap mHs,
             const __grid_constant__ CUtensorMap mHf, const __grid_constant__ CUtensorMap mCre, const __grid_constant__ CUtensorMap mCim,
             const __grid_constant__ CUtensorMap mW2, const __grid_constant__ CUtensorMap mW2n, const __grid_constant__ CUtensorMap mW1h) {
    extern __shared__ __align__(1024) uint8_t smem_raw[];
    const uint32_t sbase = smem_u32(smem_raw);
    if ((sbase & 0x3ffffu) != kSmemOrg) return;
    if (blockIdx.x >= 128) { helper_cta(&mXf, &mW1h, p, sbase); return; }
    const uint32_t bar_full = sbase + kBarOff, bar_empty = bar_full + 32, bar_dep = bar_full + 64;
    const uint32_t bar_x = bar_full + 88, bar_c = bar_full + 96, role_s = bar_full + 104, bar_role = bar_full + 120, bar_e = bar_full + 128, bar_cp = bar_full + 136, tag_s = bar_full + 112 + (threadIdx.x & 1) * 4;

    const int tid = threadIdx.x, lane = tid & 31;
    const int warp = __shfl_sync(0xffffffffu, tid >> 5, 0);
    const uint32_t rank = blockIdx.x & 1;

    int pref;
    {
        unsigned smid;
        asm("mov.u32 %0, %%smid;" : "=r"(smid));
        const int t = smid >> 1, u = t - 32, d = (u * 37) >> 8;
        pref = (t < 32) ? (t & 7) * 8 + (t >> 3) : (t < 60) ? (1 + u - 7 * d) * 8 + 4 + d : ((t - 58) & 7);
    }
    STAMP(tid == 0, 0);
    int role = pref;
#define ROLE_VARS()                                                                                               \
    const int c = role >> 3;                                                             \
    const int j8 = role & 7;                                                        \
    const int cb = j8 * 2 + (int)rank;                                             \
    const int rb = 2 * c + (int)rank;                                               \
    const int kh = j8 >> 2;                 \
    const int colK = (j8 & 3) * 256 + kh * 128, colS = colK ^ 128;    \
    (void)cb; (void)rb; (void)colS;

    if (warp >= 8) {
        asm volatile("setmaxnreg.dec.sync.aligned.u32 24;");
        unsigned taken = 0;
        if (warp > 11 - PFN) {
            const int row = blockIdx.x * 32 + lane;
            const __nv_bfloat16* src = (row < 2048) ? p.x : (row < 3072) ? p.b_lo - 2048 * kD : p.b_hi - 3072 * kD;
            asm volatile("prefetch.global.L2 [%0];" ::"l"(src + row * kD + (PFL0 + 11 - warp) * 64) : "memory");
        }
        if (warp == 8 && elect_one()) {
            prefetch_map(&mB); prefetch_map(&mXs);
#pragma unroll
            for (int s = 0; s < kStages; ++s) {
                mbar_init(bar_full + 8 * s, 1);
                mbar_init(bar_empty + 8 * s, 16);
                mbar_init(bar_dep + 8 * s, 1);
            }
            mbar_init(bar_c, 96);
            mbar_init(bar_role, 1);
            mbar_init(bar_e, 32);
            mbar_init(bar_cp, 256);
            asm volatile("fence.mbarrier_init.release.cluster;\nfence.proxy.async.shared::cta;" ::: "memory");
#pragma unroll
            for (int s = 1; s <= NSOLO; ++s) {
                mbar_expect_tx(bar_full + 8 * s, 49152);
                tma4(sbase + s * kStageBytes, &mB, bar_full + 8 * s, 64 * s, 0, 0, ((pref & 7) * 2 + (int)rank) * 8);
                tma5(sbase + s * kStageBytes + kABytes, &mXs, bar_full + 8 * s, 64 * s, 0, 0, 0, pref >> 3);
                tma5(sbase + s * kStageBytes + kABytes + 16384, &mXs, bar_full + 8 * s, 64 * s, 0, 0, 16, pref >> 3);
            }
            mbar_arrive_local(bar_full);
            mbar_expect_tx(bar_x, 2048);
            bulk_load(sbase + kXOff, p.gate_w, 2048, bar_x);
            if (!EARLYARV) mbar_expect_tx(bar_role, 8);
            STAMPP(true, 11);
        }
        if (tid == 352 && rank == 0) taken = atom_exch(&p.s->claim[pref], 1u);
        __syncwarp();
        if (!EARLYARV) cluster_arrive();
        cluster_wait();
        if (warp > 8) {
            if (tid == 352) {
#pragma unroll 1
                for (int i = 0; taken != 0 && i < 64; ++i) { role = i + 256; taken = atom_exch(&p.s->claim[i], 1u); }
                st_async32(mapa(role_s + 4 * rank, 0), role, mapa(bar_role, 0));
                st_async32(mapa(role_s + 4 * rank, 1), role, mapa(bar_role, 1));
            }
            __syncwarp();
            mbar_wait(bar_role, 0);
            role = __shfl_sync(0xffffffffu, (int)lds32(role_s), 0) & 63;
            ROLE_VARS();
            if (warp == 11) {
                if (lane < 9) prefetch_map(&mXf + lane);
#pragma unroll 1
                for (int en = lane; en < 56; en += 32) {
                    const int J = en >> 2;
                    const __nv_bfloat16* src = p.b1 + 32 * J + 2 * (en & 3) + ((J < 6) ? 2048 + 192 * j8 : 256 * j8 - 192);
                    sts128(sbase + kBiasOff + en * 16, ldg32(src), ldg32(src + 8), ldg32(src + 16), ldg32(src + 24));
                }
                mbar_arrive_local(bar_c);
                const uint4 dq = ldg128(p.dskip + colK + (lane & 15) * 8), bq = ldg128(p.b2 + colK + (lane & 15) * 8);
                mbar_wait(bar_x, 0);
                mbar_wait(bar_x, 1);
#pragma unroll 1
                for (int i = lane >> 4; i < 128; i += 2) {
                    const uint32_t xa_s = sbase + kXOff + (lane & 8) * 2048 + i * 128 + (((lane ^ i) & 7) << 4);
                    const uint4 xq = lds128(xa_s);
                    const float g = bf_lo(lds16(sbase + kGateOff + (((i >> 3) & 3) * 72 + 8 * (4 * rank + (i >> 5)) + (i & 7)) * 2));
                    const float om = bf16_round(1.0f - g);
                    uint32_t z = i >> 7;
                    PIN_R(z);
                    const uint32_t dv[4] = {dq.x, dq.y, dq.z, dq.w}, bv[4] = {bq.x, bq.y, bq.z, bq.w};
                    uint32_t xv[4] = {xq.x, xq.y, xq.z, xq.w};
#pragma unroll
                    for (int k = 0; k < 4; ++k) {
                        const uint32_t xd = bf2_mul(xv[k], dv[k]);
                        xv[k] = pack_bf16(fmaf(g, bf_lo(xd), om * __uint_as_float(__byte_perm(bv[k], z, 0x1044))),
                                          fmaf(g, bf_hi(xd), om * __uint_as_float(__byte_perm(bv[k], z, 0x3244))));
                    }
                    sts128(xa_s, xv[0], xv[1], xv[2], xv[3]);
                }
                mbar_arrive_local(bar_e);
                STAMPA(lane == 0, 10);
            } else {
                {
                    sts32(tag_s, ld_relaxed32(&p.s->epoch) + 1);
                    const int ch = cb * 64 + (tid - 288);
                    const uint32_t t_s = sbase + kTabOff + (tid - 288) * 64;
                    const float Lr = bf_lo(ldg16(p.lam_re + ch)), Li = bf_lo(ldg16(p.lam_im + ch));
                    const float dt = bf16_round(expf(bf_lo(ldg16(p.log_dt + ch))));
                    const float ea = expf(dt * Lr);
                    float lr, li;
                    sincospif((dt * Li) * 0.31830988618379067f, &li, &lr);
                    lr *= ea; li *= ea;
                    const float nr = lr - 1.0f, ni = li;
                    const bool big = fabsf(Lr) >= fabsf(Li);
                    const float u = big ? Lr : Li, v = big ? Li : Lr;
                    const float t = v / u, d = 2.0f / fmaf(v, t, u);
                    const float cr = (big ? fmaf(ni, t, nr) : fmaf(nr, t, ni)) * d, ci = (big ? fmaf(-nr, t, ni) : fmaf(ni, t, -nr)) * d;
                    if (p.swap) li = -li;
                    const float m00 = p.swap ? -ci : cr, m01 = p.swap ? cr : -ci, m10 = p.swap ? -cr : -ci, m11 = p.swap ? -ci : -cr;
#pragma unroll
                    for (int q = 0; q < 4; ++q) {
                        sts128f(t_s + q * 16, lr, li, m00, m01);
                        sts128f(t_s + 12288 + q * 16, 0.f, 0.f, 0.f, 0.f);
                    }
#pragma unroll 1
                    for (int i = 0; i < 6; ++i) CMUL(lr, li, lr, li, lr, li);
                    float ar, ai, br, bi;
                    CMUL(ar, ai, lr, li, lr, li);
                    CMUL(br, bi, ar, ai, lr, li);
                    sts128f(t_s + 4096, m10, m11, 0.f, 0.f);
#pragma unroll
                    for (int q = 1; q < 4; ++q) sts128f(t_s + 4096 + q * 16, m10, m11, lr, li);
                    sts128f(t_s + 8192, 0.f, 0.f, 1.f, 0.f);
                    sts128f(t_s + 8192 + 16, 0.f, 0.f, lr, li);
                    sts128f(t_s + 8192 + 32, ar, ai, ar, ai);
                    sts128f(t_s + 8192 + 48, ar, ai, br, bi);
                    CMUL(ar, ai, ar, ai, ar, ai);
                    br = 1.f; bi = 0.f;
#pragma unroll 1
                    for (int k = c - 1; k >= 0; --k) {
                        sts64f(t_s + 12288 + (k & 3) * 16 + (k >> 2) * 8, br, bi);
                        CMUL(br, bi, br, bi, ar, ai);
                    }
                    mbar_arrive_local(bar_c);
                }
                if (warp == 9) {
#pragma unroll 1
                    for (int ev = 0; ev < 3; ++ev) {
                        if (ev == CLREV) {
                            uint8_t* box = p.s->X + (size_t)(role * 2 + rank) * kXBytes + lane * 16;
#pragma unroll 1
                            for (int i = 0; i < kXBytes; i += 512) { stg128(box + i, 0, 0, 0, 0); if (CLRNS) __nanosleep(CLRNS); }
                        }
                        bar_sync(3 + ev, 288);
                        if (lane == 0) {
                            unsigned* cnt = &p.s->cnt[(ev == 0 ? c : 16 * ev - 8 + rb) * 32];
                            asm volatile("fence.acq_rel.gpu;\nfence.proxy.async.global;" ::: "memory");
                            asm volatile("red.relaxed.gpu.global.add.u32 [%0], 1;" ::"l"(cnt) : "memory");
                        }
                        __syncwarp();
                    }
                } else if (lane == 0) {
                    const unsigned tag = lds32(tag_s);
#pragma unroll 1
                    for (int ev = 0; ev < 4; ++ev) {
                        wait_counter(&p.s->cnt[(ev == 0 ? c : 16 * ev - 8 + rb) * 32], tag * (ev == 0 ? 16u : ev == 3 ? 1u : 8u));
                        mbar_arrive_local(bar_dep + (ev == 3 ? 0 : 8 * ev));
                        if (ev == 0 && atomicInc(&p.s->done, 131u) == 131u) {
                            st_relaxed32(&p.s->epoch, tag);
#pragma unroll 1
                            for (int i = 0; i < 64; i += 4) stg128(&p.s->claim[i], 0, 0, 0, 0);
                        }
                    }
                }
            }
        } else if (elect_one()) {
            int it = 1 + NSOLO, again = 15;
#define ACQUIRE(BYTES)                                                   \
    const uint32_t st = sbase + (it & 3) * kStageBytes, fb = bar_full + 8 * (it & 3); \
    mbar_wait(bar_empty + 8 * (it & 3), ((it >> 2) & 1) ^ 1);     \
    mbar_expect_tx(fb, BYTES);
#pragma unroll 1
            for (; it < 16; ++it) {
                ACQUIRE(49152);
                tma4(st, &mB, fb, it * 64, 0, 0, ((role & 7) * 2 + (int)rank) * 8);
                tma5_mc(st + kABytes + rank * 16384, &mXs, fb, it * 64, 0, 0, rank * 16, role >> 3);
                if (it == again) {
                    mbar_wait(bar_role, 0);
                    const uint2 fin = lds64(role_s);
                    role = fin.x & 63;
                    if (fin.x != fin.y) { it = -1; again = 16; }
                }
            }
            ROLE_VARS();
#pragma unroll 1
            for (; it < 48; ++it) {
                const bool t1 = it < 32;
                const int k0 = (it & 15) * 64;
                ACQUIRE(t1 ? 40960 : (W64MAIN || W1SPLIT) ? 45056 : 49152);
                tma5(st, &mXf, fb, k0, 0, 0, rank * 4, c);
                tma3_mc(st + kABytes + rank * (t1 ? 12288 : 16384), &mW1b, fb, 0, k0 + rank * 32, t1 ? 32 + 3 * j8 : 4 * j8);
                if (!t1) tma3_mc(st + kABytes + rank * 16384 + 12288, &mW1a, fb, 0, k0 + rank * 32, 4 * j8 + 3);
                if ((it & ~2) == XLDKB) {
                    const int h = (it >> 1) & 1;
                    if (h == 0) mbar_expect_tx(bar_x, 32768);
                    tma5(sbase + kXOff + h * 16384, &mXf, bar_x, colK + h * 64, 0, 0, rank * 4, c);
                }
            }
            STAMPA(true, 8);
            mbar_wait(bar_dep, 0);
            asm volatile("fence.proxy.async.global;" ::: "memory");
            STAMPA(true, 9);
#pragma unroll 1
            for (; it < 64; ++it) {
                const int k0 = (it & 15) * 64;
                ACQUIRE(49152);
                tma3(st, &mHs, fb, 0, kh * 1024 + k0, rb * 2);
                tma2_mc(st + kABytes + rank * 16384, kh ? &mCim : &mCre, fb, k0, rank ? colS : colK);
            }
            int f0 = 2048 + 768 * kh;
#pragma unroll 1
            for (; it < kTotal; ++it, f0 += 64) {
                if (it == 64 || it == 76 || it == 85) {
                    mbar_wait(bar_dep + (it == 64 ? 8 : it == 76 ? 16 : 0), it == 85);
                    asm volatile("fence.proxy.async.global;" ::: "memory");
                    if (it != 64) f0 = 1024 * kh;
                }
                if (it >= 76 && it < 85 && (f0 & 192) == 192) f0 += 64;
                if (it >= 85 && it < 88) f0 |= 192;
                if ((f0 >> 8) == j8) f0 += 256;
                if (it == 88) f0 = 256 * (j8 ^ 4);
                ACQUIRE(49152);
                tma2(st, &mHf, fb, f0, rb * 128);
                tma5_mc(st + kABytes + rank * 16384, &mW2, fb, 0, 0, (f0 >> 3) + 4 * rank, 0, colK >> 6);
                if (it < 88) tma5_mc(st + kABytes + rank * 16384 + 8192, &mW2, fb, 0, 0, (f0 >> 3) + 4 * rank, 0, colS >> 6);
                else tma3_mc(st + kABytes + rank * 16384 + 8192, &mW2n, fb, 0, (f0 ^ 1024) + 32 * rank, colK >> 6);
                if ((it >> 3) == PFKB / 8) tma3_pf(&mW2n, 0, 256 * (j8 & 3) + (it & 4) * 256 + (it & 3) * 64 + 32 * rank, colK >> 6);
            }
        }
    } else {
        {
            cluster_arrive();
            const int rg = tid >> 3;
            const uint32_t dst = sbase + rg * 128 + (((tid ^ rg) & 7) << 4);
            const __nv_bfloat16* sx = p.x + ((pref >> 3) * 256 + (rg & 1) + 64 * ((rg >> 1) & 3) + 2 * (rg >> 3)) * kD + (tid & 7) * 8;
            const __nv_bfloat16* sb = ((rg & 8) ? p.b_hi : p.b_lo) + (((pref & 7) * 2 + (int)rank) * 64 + (rg >> 4) * 8 + (rg & 7)) * kD + (tid & 7) * 8;
#pragma unroll
            for (int i = 0; i < 4; ++i) {
                cp_async16(dst + i * 4096, sb + i * 16 * kD);
                cp_async16(dst + kABytes + i * 4096, sx + i * 8 * kD);
            }
            asm volatile("cp.async.commit_group;" ::: "memory");
#pragma unroll
            for (int i = 4; i < 8; ++i) cp_async16(dst + kABytes + i * 4096, sx + i * 8 * kD);
            asm volatile("cp.async.commit_group;" ::: "memory");
            STAMPP(tid == 0, 2);
        }
        asm volatile("setmaxnreg.inc.sync.aligned.u32 240;");
        const int wg = warp >> 2, w = warp & 3, r = lane >> 2, q = lane & 3, tw = tid & 127;
        uint32_t a_lo = (kSmemOrg + wg * 8192) >> 4;
        constexpr uint32_t b_lo = (kSmemOrg + kABytes) >> 4;
        const uint32_t rel_addr = mapa(bar_empty, (uint32_t)(lane & 1));
        const uint32_t gate_s = sbase + kGateOff;
        float acc[128];
        uint32_t pk[64];
        unsigned tag;
        UNDEF_R(tag);

#pragma unroll
        for (int i = 0; i < 128; ++i) UNDEF_F(acc[i]);
        float gs = 0.f;
        {
            const uint32_t gx_s = sbase + kABytes + (16 * rank + 2 * warp + (lane >> 4)) * 128 +
                                  ((((lane & 15) >> 1) ^ (2 * w + (lane >> 4))) << 4) + (lane & 1) * 8;
            const uint32_t gw_s = sbase + kXOff + (lane & 15) * 8;
            uint32_t again = 15;
            STAMPP(tid == 0, 3);
            cluster_wait();
            STAMPP(tid == 0, 4);
#define GATE_STEP(IT)                                                                                  \
    {                                                                                                  \
        mbar_wait(bar_x, 0);                                                                           \
        const uint2 xa = lds64(gx_s + (role & 7) * 4096 + ((IT) & 3) * kStageBytes), wa = lds64(gw_s + (IT) * 128); \
        const uint32_t pa = bf2_mul(xa.x, wa.x), pb = bf2_mul(xa.y, wa.y);                             \
        gs += (bf_lo(pa) + bf_hi(pa)) + (bf_lo(pb) + bf_hi(pb));                                       \
    }
            asm volatile("cp.async.mbarrier.arrive.noinc.shared::cta.b64 [%0];" ::"r"(bar_cp) : "memory");
            asm volatile("cp.async.wait_group 1;" ::: "memory");
            STAMPP(tid == 0, 8);
            fence_async_smem();
            bar_sync(6, 256);
            STAMPP(tid == 0, 9);
            KT(0, 0); KT(0, 1);
            wgmma_fence();
#pragma unroll
            for (int kk = 0; kk < 4; ++kk)
                wgmma_n128<0, 0>(acc, kDescHi | (uint64_t)(a_lo + 2 * kk + (1u << 16)), kDescHi | (uint64_t)(b_lo + 2 * kk + (1u << 16)), kk);
            wgmma_commit();
            mbar_wait(bar_cp, 0);
            fence_async_smem();
            wgmma_fence();
#pragma unroll
            for (int kk = 0; kk < 4; ++kk)
                wgmma_n128<0, 0, 64>(acc, kDescHi | (uint64_t)(a_lo + 2 * kk + (1u << 16)), kDescHi | (uint64_t)(b_lo + 1024 + 2 * kk + (1u << 16)), kk);
            wgmma_commit();
            STAMPA(tid == 0, 1); STAMPP(tid == 0, 1);
            GATE_STEP(0);
            mbar_wait(bar_full + 8, 0);
            wgmma_wait<0>();
#pragma unroll 1
            for (uint32_t it = 1; it < 16; ++it) {
                const uint32_t so = (it & 3) * (kStageBytes >> 4);
                KB_OPEN(it, false);
                wgmma_fence();
                mma_kblock<0>(acc, a_lo + so, b_lo + so, it != 0);
                wgmma_commit();
                KB_CLOSE(it, false, true);
                STAMPP(tid == 0 && it == 1, 10);
                GATE_STEP(it);
                if (it == again) {
                    mbar_wait(bar_c, 0);
                    const uint2 fin = lds64(role_s);
                    role = fin.x & 63;
                    if (__shfl_sync(0xffffffffu, fin.x != fin.y, 0)) { it = -1; again = 16; gs = 0.f; }
                }
            }
        }
        role = __shfl_sync(0xffffffffu, role, 0);
        ROLE_VARS();
        {
            tag = lds32(tag_s);
#pragma unroll
            for (int o = 8; o > 0; o >>= 1) gs += __shfl_xor_sync(0xffffffffu, gs, o);
            const float g = bf16_round(__frcp_rn(1.0f + expf(-bf16_round(gs))));
            if ((lane & 15) == 0) st_relaxed64(&p.s->gate[c * 256 + (lane >> 4) + 64 * w + 4 * cb + 2 * wg], __float_as_uint(g), tag);
        }
        const uint32_t tab_s = sbase + kTabOff + tid * 16;
        const float4 k0 = lds128f(tab_s);
        TILE_END();
        STAMPA(tid == 0, 2);
#pragma unroll
        for (int s = 0; s < 64; ++s) pk[s] = pack_bf16_v(acc[4 * (s >> 1) + (s & 1)], acc[4 * (s >> 1) + 2 + (s & 1)]);
#pragma unroll
        for (int i = 0; i < 96; ++i) UNDEF_F(acc[i]);

        const float lr = k0.x, li = k0.y, m00 = k0.z, m01 = k0.w;
        float m10, m11, hr = 0.f, hi = 0.f;
        uint32_t gg[4], orr[4], oii[4];
        const int ch = cb * 64 + warp * 8 + r;
        __nv_bfloat16* hs = p.s->Hs + (size_t)ch * 2048 + c * 256 + q * 8;
#define PASS2(KB)                                                                                      \
    _Pragma("unroll") for (int s = 0; s < 64; s += 2) {                                                \
        if (pass2_kb(s) != (KB)) continue;                                                             \
        if ((s & 7) == 0) {                                                                            \
            const uint4 ga = lds128(gate_s + (q * 72 + s) * 2);                                        \
            gg[0] = ga.x; gg[1] = ga.y; gg[2] = ga.z; gg[3] = ga.w;                                    \
        }                                                                                              \
        float o0[2], o1[2];                                                                            \
        _Pragma("unroll") for (int k = 0; k < 2; ++k) {                                                \
            PIN_R(pk[s + k]);                                                                          \
            float nr = bf_lo(pk[s + k]), ni = bf_hi(pk[s + k]);                                        \
            CFMA(nr, ni, lr, li, hr, hi);                                                              \
            hr = nr; hi = ni;                                                                          \
            o0[k] = fmaf(m00, hr, m01 * hi);                                                           \
            o1[k] = fmaf(m10, hr, m11 * hi);                                                           \
        }                                                                                              \
        orr[(s >> 1) & 3] = bf2_mul(pack_bf16(o0[0], o0[1]), gg[(s >> 1) & 3]);                        \
        oii[(s >> 1) & 3] = bf2_mul(pack_bf16(o1[0], o1[1]), gg[(s >> 1) & 3]);                        \
        if ((s & 7) == 6) {                                                                            \
            stg128(hs + 32 * (s >> 3), orr[0], orr[1], orr[2], orr[3]);                                \
            stg128(hs + 1024 * 2048 + 32 * (s >> 3), oii[0], oii[1], oii[2], oii[3]);                  \
        }                                                                                              \
    }                                                                                                  \
    PIN_F(hr); PIN_F(hi);
        {
            uint4 av0, av1, gv;
            float lqr, lqi;
#pragma unroll
            for (int kb = 0; kb < 16; ++kb) {
                PIN_R(a_lo);
                KBLOCK(1, 16 + kb, kb == 0, kb == 15);
                if (kb < 4) {
#pragma unroll
                    for (int s = kb * 16; s < kb * 16 + 16; ++s) {
                        float nr = bf_lo(pk[s]), ni = bf_hi(pk[s]);
                        CFMA(nr, ni, lr, li, hr, hi);
                        hr = nr; hi = ni;
                    }
                    PIN_F(hr); PIN_F(hi);
                }
                if (kb == 2) gv = ld_relaxed2x64(&p.s->gate[c * 256 + 2 * tw]);
                if (kb == 3) {
                    const float4 k1 = lds128f(tab_s + 4096), k2 = lds128f(tab_s + 8192);
                    m10 = k1.x; m11 = k1.y; lqr = k2.z; lqi = k2.w;
                    float tr = __shfl_up_sync(0xffffffffu, hr, 1, 4), ti = __shfl_up_sync(0xffffffffu, hi, 1, 4);
                    if (q >= 1) CFMA(hr, hi, k1.z, k1.w, tr, ti);
                    tr = __shfl_up_sync(0xffffffffu, hr, 2, 4); ti = __shfl_up_sync(0xffffffffu, hi, 2, 4);
                    if (q >= 2) CFMA(hr, hi, k2.x, k2.y, tr, ti);
                    if (q == 3) st_relaxed2x64(&p.s->agg[c * 1024 + ch], __float_as_uint(hr), tag, __float_as_uint(hi), tag);
                    tr = __shfl_up_sync(0xffffffffu, hr, 1, 4); ti = __shfl_up_sync(0xffffffffu, hi, 1, 4);
                    hr = (q >= 1) ? tr : 0.f; hi = (q >= 1) ? ti : 0.f;
                }
                if (kb == 4) {
                    unsigned spins = 0;
                    while (__any_sync(0xffffffffu, gv.y != tag || gv.w != tag)) {
                        if (++spins > kSpinLimit) break;
                        gv = ld_relaxed2x64(&p.s->gate[c * 256 + 2 * tw]);
                    }
                    sts32(gate_s + ((tw >> 5) * 72 + 2 * lane) * 2, __byte_perm(gv.x, gv.z, 0x7632));
                }
                if (kb == 5) {
                    av0 = make_uint4(0, tag, 0, tag); av1 = av0;
                    if (q < c) av0 = ld_relaxed2x64(&p.s->agg[q * 1024 + ch]);
                    if (q + 4 < c) av1 = ld_relaxed2x64(&p.s->agg[(q + 4) * 1024 + ch]);
                    bar_sync(1 + wg, 128);
                }
                if (kb == 6) {
                    const float4 k3 = lds128f(tab_s + 12288);
                    unsigned spins = 0;
                    while (__any_sync(0xffffffffu, av0.y != tag || av0.w != tag || av1.y != tag || av1.w != tag)) {
                        if (++spins > kSpinLimit) break;
                        if (q < c) av0 = ld_relaxed2x64(&p.s->agg[q * 1024 + ch]);
                        if (q + 4 < c) av1 = ld_relaxed2x64(&p.s->agg[(q + 4) * 1024 + ch]);
                    }
                    float vr, vi;
                    CMUL(vr, vi, k3.x, k3.y, __uint_as_float(av0.x), __uint_as_float(av0.z));
                    CFMA(vr, vi, k3.z, k3.w, __uint_as_float(av1.x), __uint_as_float(av1.z));
                    vr += __shfl_xor_sync(0xffffffffu, vr, 1); vi += __shfl_xor_sync(0xffffffffu, vi, 1);
                    vr += __shfl_xor_sync(0xffffffffu, vr, 2); vi += __shfl_xor_sync(0xffffffffu, vi, 2);
                    CFMA(hr, hi, lqr, lqi, vr, vi);
                }
                if (kb >= 6) { PASS2(kb); }
            }
            TILE_END();
        }
        STAMPA(tid == 0, 3);
#pragma unroll
        for (int i = 0; i < 48; ++i) pk[i] = pack_bf16_v(acc[2 * i], acc[2 * i + 1]);
#pragma unroll
        for (int i = 0; i < 128; ++i) UNDEF_F(acc[i]);

        PIN_R(a_lo);
        KBLOCK(5, 32, true, false);
        PASS2(16);
        PIN_R(a_lo);
        KBLOCK(5, 33, false, false);
        PASS2(17);
        bar_arrive(3, 288);
        const uint32_t gate_row = gate_s + ((2 * (w & 1)) * 72 + 8 * (4 * rank + 2 * wg + (w >> 1)) + r) * 2;
        uint32_t om0, om1;
        {
            const float a = 1.0f - bf_lo(lds16(gate_row)), b = 1.0f - bf_lo(lds16(gate_row + 72 * 2));
            om0 = pack_bf16(a, a); om1 = pack_bf16(b, b);
        }
        __nv_bfloat16* hf = p.s->Hf + (size_t)(rb * 128 + wg * 64 + w * 16 + r) * kF + q * 8 + 2048 + 192 * j8;
        uint32_t bias_s = sbase + kBiasOff + q * 16;
        const uint32_t x_s = sbase + kXOff + (wg * 64 + w * 16 + (lane & 15)) * 128 + (((lane >> 4) ^ (lane & 7)) << 4);
        {
            uint32_t j = 0, nsl = SPREAD ? 11 : 6;
#pragma unroll 1
            for (uint32_t it = 34; it < 88; ++it, ++j) {
                const uint32_t so = (it & 3) * (kStageBytes >> 4);
                if (wg == 1 && (it == 86 || (ORDER && it == 47))) bar_sync(7, 256);
                KB_OPEN(it, false);
                if (it < 48) {
                    wgmma_fence();
                    mma_kblock<5>(acc, a_lo + so, b_lo + so, 1);
                    wgmma_commit();
                } else if (it < 64) {
                    wgmma_fence();
                    mma_kblock<3>(acc, a_lo + so, b_lo + so, it != 48);
                    wgmma_commit();
                } else {
                    wgmma_fence();
                    mma_kblock<2>(acc, a_lo + so, b_lo + so, 1);
                    wgmma_commit();
                }
                if (wg == 0 && (it == 87 || (ORDER && it == 47))) bar_arrive(7, 256);
                KB_CLOSE(it, false, it != 48);
                if (j < nsl) {
                    if (SPREAD && (j & 1)) continue;
                    if (j & (4 << SPREAD)) {
                        if (j & (2 << SPREAD)) { FFN_SLICE(6, 32) } else { if (j & (1 << SPREAD)) FFN_SLICE(5, 32) else FFN_SLICE(4, 32) }
                    } else {
                        if (j & (2 << SPREAD)) { if (j & (1 << SPREAD)) FFN_SLICE(3, 32) else FFN_SLICE(2, 32) } else { if (j & (1 << SPREAD)) FFN_SLICE(1, 32) else FFN_SLICE(0, 32) }
                    }
                    if (j + 1 == nsl) bar_arrive(SPREAD ? 2 + (nsl >> 2) : 1 + (nsl >> 1), 288);
                } else if (it == 47) {
                    hf += 64 * j8 - 2048;
                    bias_s += 6 * 64;
                    j = -1; nsl = 13;
                    TILE_END();
                    STAMPA(tid == 0, 4);
#pragma unroll
                    for (int i = 0; i < 56; ++i) pk[i] = pack_bf16_v(acc[2 * i], acc[2 * i + 1]);
                } else if (it == HPFKB + HPFD * wg) {
                    mbar_wait(bar_e, 0);
                    mbar_wait(bar_dep, 1);
                    const uint4 ha = ld_weak128(hf + 224), hb = ld_weak128(hf + 8 * kF + 224);
                    uint32_t z = j >> 8;
                    PIN_R(z);
                    pk[56] = ha.x ^ z; pk[58] = ha.y ^ z; pk[60] = ha.z ^ z; pk[62] = ha.w ^ z;
                    pk[57] = hb.x ^ z; pk[59] = hb.y ^ z; pk[61] = hb.z ^ z; pk[63] = hb.w ^ z;
                }
            }
        }
#define TAIL_MMA(T)                                                                                    \
    {                                                                                                  \
        PIN_R(a_lo);                                                                                   \
        wgmma_fence();                                                                                 \
        mma_kblock<4>(acc, a_lo + (T) * (kStageBytes >> 4), b_lo + (T) * (kStageBytes >> 4), 1);       \
        _Pragma("unroll") for (int kk = 0; kk < 4; ++kk)                                               \
            wgmma_n128_rs(acc, pk[16 * (T) + 4 * kk], pk[16 * (T) + 4 * kk + 1], pk[16 * (T) + 4 * kk + 2], pk[16 * (T) + 4 * kk + 3], \
                          kDescHi | (uint64_t)(b_lo + (((T) * kStageBytes + 8192 + (kk >> 1) * 16384 + (kk & 1) * 2048) >> 4) + (256u << 16))); \
        wgmma_commit();                                                                                \
    }
        TILE_END();
        sched_fence(a_lo);
        uint4 rx[8], ev[8];
        uint32_t rs;
        {
            const uint8_t* xi = p.s->X + (size_t)(role * 2 + rank) * kXBytes + tid * 16;
            uint8_t* xo = const_cast<uint8_t*>(xi) + (kh ? -8 * kXBytes : 8 * kXBytes);
#define RXLOAD()                                                                                       \
    {                                                                                                  \
        rs = ld_relaxed32((const unsigned*)(xi + 32768 - tid * 12));                                   \
        _Pragma("unroll") for (int u = 0; u < 8; ++u) rx[u] = ld_relaxed2x64(xi + u * 4096);           \
    }
            {
                STAMPE(tid == 0, 15); STAMPB(tid == 128, 1);
                float m[4] = {0.f, 0.f, 0.f, 0.f};
#pragma unroll
                for (int i = 64; i < 128; ++i) m[i & 3] = fmaxf(m[i & 3], fabsf(acc[i]));
                const uint32_t eb = max(__float_as_uint(fmaxf(fmaxf(m[0], m[1]), fmaxf(m[2], m[3]))) >> 23, 15u);
                const float xsc = __uint_as_float((268u - eb) << 23);
                st_relaxed32(xo + 32768 - tid * 12, (eb - 14u) << 23);
#pragma unroll
                for (int u = 0; u < 8; ++u) {
                    const int v = 64 + 8 * u;
                    st_relaxed2x64(xo + u * 4096, pack_f16(acc[v] * xsc, acc[v + 1] * xsc) | 1, pack_f16(acc[v + 2] * xsc, acc[v + 3] * xsc),
                                   pack_f16(acc[v + 4] * xsc, acc[v + 5] * xsc) | 1, pack_f16(acc[v + 6] * xsc, acc[v + 7] * xsc));
                }
                STAMPE(tid == 0, 12); STAMPB(tid == 128, 2);
            }
            mbar_wait(bar_full, 0);
            TAIL_MMA(0);
            mbar_wait(bar_full + 8, 0);
            if (wg == 1) bar_arrive(8, 256);
            TAIL_MMA(1);
#pragma unroll
            for (int u = 0; u < 8; ++u) ev[u] = ldsm4((x_s ^ ((u & 3) << 5)) + (u >> 2) * 16384);
            if (wg == 1) mbar_wait(bar_full + 24, 0);
            bar_sync(8 + wg, 256);
            STAMPB(tid == 0, 9);
            RXLOAD();
            mbar_wait(bar_full + 16, 0);
            STAMPB(tid == 0, 10);
            STAMPB(tid == 128, 3);
            TAIL_MMA(2);
            if (wg == 0) mbar_wait(bar_full + 24, 0);
            STAMPB(tid == 0, 11);
            TAIL_MMA(3);
            if (wg == 0) bar_arrive(9, 256);
            sched_fence(a_lo);
            unsigned spins = 0;
#pragma unroll 1
            while (true) {
                uint32_t ok = rs != 0;
#pragma unroll
                for (int u = 0; u < 8; ++u) ok &= rx[u].x & rx[u].z;
                if (__all_sync(0xffffffffu, ok) || ++spins > kSpinLimit) break;
                RXLOAD();
                RESPIN();
            }
            STAMPE(tid == 0, 13);
            STAMPE(tid == 0, 14);
        }
        wgmma_wait<0>();
        STAMP(tid == 0, 6); STAMPB(tid == 128, 4);
        {
            const bool odd = q & 1;
            const int tb = c * 256 + 128 * (w & 1) + 8 * (4 * rank + 2 * wg + (w >> 1));
            float* o0 = p.out + (size_t)(tb + r) * kD + colK + (odd ? 2 * q + 6 : 2 * q);
#pragma unroll
            for (int i = 0; i < 16; i += 2) {
#pragma unroll
                for (int h = 0; h < 2; ++h) {
                    const int va = 4 * i + 2 * h, vb = va + 4;
                    PIN_F(acc[va]); PIN_F(acc[va + 1]); PIN_F(acc[vb]); PIN_F(acc[vb + 1]);
                    const float xsc = __uint_as_float(rs);
                    uint32_t ra = h ? rx[i >> 1].y : rx[i >> 1].x, rb2 = h ? rx[i >> 1].w : rx[i >> 1].z;
                    PIN_R(ra); PIN_R(rb2);
                    const float2 fa = __half22float2(*reinterpret_cast<const __half2*>(&ra));
                    const float2 fb2 = __half22float2(*reinterpret_cast<const __half2*>(&rb2));
                    const uint32_t ea = h ? ev[i >> 1].y : ev[i >> 1].x, eb = h ? ev[i >> 1].w : ev[i >> 1].z;
                    const float ea0 = bf_lo(ea), ea1 = bf_hi(ea), eb0 = bf_lo(eb), eb1 = bf_hi(eb);
                    const float a0 = acc[va] + fmaf(fa.x, xsc, ea0), a1 = acc[va + 1] + fmaf(fa.y, xsc, ea1);
                    const float b0 = acc[vb] + fmaf(fb2.x, xsc, eb0), b1 = acc[vb + 1] + fmaf(fb2.y, xsc, eb1);
                    const float t0 = __shfl_xor_sync(0xffffffffu, odd ? a0 : b0, 1), t1 = __shfl_xor_sync(0xffffffffu, odd ? a1 : b1, 1);
                    stg128f(o0 + h * 64 * kD + 8 * i, odd ? t0 : a0, odd ? t1 : a1, odd ? b0 : t0, odd ? b1 : t1);
                }
                if (i < 14) sched_fence(a_lo);
            }
        }
        STAMP(tid == 0, 7);
        STAMP(tid == 128, 5);
    }
}

typedef CUresult (*EncodeFn)(CUtensorMap*, CUtensorMapDataType, cuuint32_t, void*, const cuuint64_t*, const cuuint64_t*,
                             const cuuint32_t*, const cuuint32_t*, CUtensorMapInterleave, CUtensorMapSwizzle,
                             CUtensorMapL2promotion, CUtensorMapFloatOOBfill);

bool encode(EncodeFn fn, CUtensorMap* m, const void* base, int rank, const cuuint64_t* dims, const cuuint64_t* strides,
            const cuuint32_t* box, CUtensorMapSwizzle sw = CU_TENSOR_MAP_SWIZZLE_128B) {
    cuuint32_t es[5] = {1, 1, 1, 1, 1};
    return fn(m, CU_TENSOR_MAP_DATA_TYPE_BFLOAT16, rank, const_cast<void*>(base), dims, strides, box, es,
              CU_TENSOR_MAP_INTERLEAVE_NONE, sw, CU_TENSOR_MAP_L2_PROMOTION_L2_256B,
              CU_TENSOR_MAP_FLOAT_OOB_FILL_NONE) == CUDA_SUCCESS;
}

}

extern "C" void kernel_launch(void* const* d_in, const int* in_sizes, int n_in, void* d_out, int out_size) {
    (void)in_sizes; (void)n_in; (void)out_size;
    typedef const __nv_bfloat16* bp;
    bp x = (bp)d_in[0], lam_re = (bp)d_in[1], lam_im = (bp)d_in[2], B_re = (bp)d_in[3], B_im = (bp)d_in[4];
    bp C_re = (bp)d_in[5], C_im = (bp)d_in[6], log_dt = (bp)d_in[7], dskip = (bp)d_in[8];
    bp w1 = (bp)d_in[10], b1 = (bp)d_in[11], w2 = (bp)d_in[12], b2 = (bp)d_in[13], gate_w = (bp)d_in[14];

    static EncodeFn fn = nullptr;
    static Scratch* ps = nullptr;
    if (!fn) {
        void* f = nullptr;
        cudaDriverEntryPointQueryResult qr;
        cudaGetDriverEntryPoint("cuTensorMapEncodeTiled", &f, cudaEnableDefault, &qr);
        fn = (EncodeFn)f;
        cudaGetSymbolAddress((void**)&ps, g_s);
        cudaFuncSetAttribute(fused_kernel, cudaFuncAttributeMaxDynamicSharedMemorySize, kSmemBytes);
    }
    cudaStream_t stream = cudaStreamPerThread;

    Params p;
    p.x = x; p.lam_re = lam_re; p.lam_im = lam_im; p.log_dt = log_dt; p.dskip = dskip; p.b1 = b1; p.b2 = b2;
    p.gate_w = gate_w; p.out = (float*)d_out; p.s = ps;
    char* const pHs = (char*)ps + offsetof(Scratch, Hs);
    char* const pHf = (char*)ps + offsetof(Scratch, Hf);
    char* const pBc = (char*)ps + offsetof(Scratch, Bcopy);

    const char* lo = (const char*)B_re; const char* hi = (const char*)B_im;
    p.swap = 0;
    if (hi < lo) { const char* t = lo; lo = hi; hi = t; p.swap = 1; }
    unsigned long long diff = (unsigned long long)(hi - lo);
    if (diff >= (1ull << 40) || (diff & 15) || diff == 0) {
        cudaMemcpyAsync(pBc, B_re, 2u << 20, cudaMemcpyDeviceToDevice, stream);
        cudaMemcpyAsync((char*)pBc + (2u << 20), B_im, 2u << 20, cudaMemcpyDeviceToDevice, stream);
        lo = (const char*)pBc; diff = 2u << 20; p.swap = 0;
    }

    p.b_lo = p.swap ? B_im : B_re; p.b_hi = p.swap ? B_re : B_im;

    CUtensorMap mB, mXs, mXf, mW1a, mW1b, mHs, mHf, mCre, mCim, mW2, mW2n, mW1h;
    bool ok = true;
    { cuuint64_t d[4] = {1024, 8, 2, 128}, s[3] = {2048, diff, 16384}; cuuint32_t b[4] = {64, 8, 2, 8};
      ok &= encode(fn, &mB, lo, 4, d, s, b); }
    { cuuint64_t d[5] = {1024, 2, 4, 32, 8}, s[4] = {2048, 64 * 2048, 2 * 2048, 256 * 2048}; cuuint32_t b[5] = {64, 2, 4, 16, 1};
      ok &= encode(fn, &mXs, x, 5, d, s, b); }
    { cuuint64_t d[5] = {1024, 8, 4, 8, 8}, s[4] = {2048, 64 * 2048, 8 * 2048, 256 * 2048}; cuuint32_t b[5] = {64, 8, 4, 4, 1};
      ok &= encode(fn, &mXf, x, 5, d, s, b); }
    { cuuint64_t d[3] = {64, 1024, 56}, s[2] = {7168, 128}; cuuint32_t ba[3] = {W1SPLIT ? 32u : 64u, 32, W1SPLIT ? 1u : 4u}, bb[3] = {64, 32, 3};
      ok &= encode(fn, &mW1a, w1, 3, d, s, ba); ok &= encode(fn, &mW1b, w1, 3, d, s, bb); }
    { cuuint64_t d[3] = {64, 2048, 32}, s[2] = {4096, 128}; cuuint32_t b[3] = {64, 64, 2};
      ok &= encode(fn, &mHs, pHs, 3, d, s, b); }
    { cuuint64_t d[2] = {3584, 2048}, s[1] = {7168}; cuuint32_t b[2] = {64, 128};
      ok &= encode(fn, &mHf, pHf, 2, d, s, b); }
    { cuuint64_t d[2] = {1024, 1024}, s[1] = {2048}; cuuint32_t b[2] = {64, 128};
      ok &= encode(fn, &mCre, C_re, 2, d, s, b); ok &= encode(fn, &mCim, C_im, 2, d, s, b); }
    { cuuint64_t d[5] = {64, 2, 448, 4, 16}, s[4] = {2048, 8 * 2048, 2 * 2048, 128}; cuuint32_t b[5] = {64, 2, 4, 4, 2};
      ok &= encode(fn, &mW2, w2, 5, d, s, b); }
    { cuuint64_t d[3] = {64, 3584, 16}, s[2] = {2048, 128}; cuuint32_t b[3] = {64, 32, 2};
      ok &= encode(fn, &mW2n, w2, 3, d, s, b); }
    { cuuint64_t d[3] = {32, 1024, 8}, s[2] = {7168, 512}; cuuint32_t b[3] = {32, 32, 8};
      ok &= encode(fn, &mW1h, w1 + 224, 3, d, s, b, CU_TENSOR_MAP_SWIZZLE_64B); }
    if (W64MAIN) { cuuint64_t d[3] = {32, 1024, 112}, s[2] = {7168, 64}; cuuint32_t b[3] = {32, 32, 7};
      ok &= encode(fn, &mW1a, w1, 3, d, s, b, CU_TENSOR_MAP_SWIZZLE_64B); }
    if (!ok) return;

    fused_kernel<<<132, 384, kSmemBytes, stream>>>(p, mB, mXs, mXf, mW1b, mW1a, mHs, mHf, mCre, mCim, mW2, mW2n, mW1h);
}
```
